```python
import torch

def _softmax(x, axis=-1):
    return torch.softmax(x, dim=axis)
def _gelu(x):
    return torch.nn.functional.gelu(x, approximate="tanh")
def _silu(x):
    return torch.nn.functional.silu(x)
def _sigmoid(x):
    return torch.sigmoid(x)
def _layernorm(x, axis=-1, eps=1e-5):
    m = x.mean(dim=axis, keepdim=True)
    v = x.var(dim=axis, keepdim=True, unbiased=False)
    return (x - m) / torch.sqrt(v + eps)
def _scatter_add(tgt, idx, src, axis=0):
    return tgt.clone().index_add_(axis, idx, src)
def _segment_sum(src, seg, n):
    out = torch.zeros((n,) + src.shape[1:], dtype=src.dtype)
    return out.index_add_(0, seg, src)
def _pad(x, pw):
    flat = tuple(v for pair in reversed(pw) for v in pair)
    return torch.nn.functional.pad(x, flat)

kernel_name = 'concat_heads__sliding_local_dilated__compressed_kv_cla__prompt'

def setup_inputs():

    _w = (lambda a: (lambda t: t.to(torch.bfloat16) if t.is_floating_point() else t)(torch.as_tensor(a)))
    def _A_setup():
        B, S, D = 1, 2048, 1024
        return {
            "x": _w((lambda *s: torch.randn(*s, dtype=torch.bfloat16) * 0.2)(B, S, D)),
            "wqkv": _w((lambda *s: torch.randn(*s, dtype=torch.bfloat16) * 0.2)(D, 3 * D)),
            "wo": _w((lambda *s: torch.randn(*s, dtype=torch.bfloat16) * 0.05)(D, D)),
        }
    _A_in = _A_setup()

    def _B_setup():
        B, H, Sq, Sk, D, M = 1, 32, 2048, 2048, 128, 1024
        Dc = 4 * D
        return {
            "x": _w((lambda *s: torch.randn(*s, dtype=torch.bfloat16) * 0.2)(B, Sq, M)),
            "c_kv": _w((lambda *s: torch.randn(*s, dtype=torch.bfloat16) * 1.6)(B, Sk, Dc)),
            "w_q": _w((lambda *s: torch.randn(*s, dtype=torch.bfloat16) * 3.2)(M, H, D) * (M ** -0.5)),
            "w_uk": _w((lambda *s: torch.randn(*s, dtype=torch.bfloat16) * 3.2)(Dc, H, D) * (Dc ** -0.5)),
            "w_uv": _w((lambda *s: torch.randn(*s, dtype=torch.bfloat16) * 1.6)(Dc, H, D) * (Dc ** -0.5)),
            "w_o": _w((lambda *s: torch.randn(*s, dtype=torch.bfloat16) * 1.6)(H, D, M) * ((H * D) ** -0.5)),
        }
    _B_in = _B_setup()

    return {
        "A_x": _A_in["x"],
        "A_wqkv": _A_in["wqkv"],
        "A_wo": _A_in["wo"],
        "B_x": _B_in["x"],
        "B_c_kv": _B_in["c_kv"],
        "B_w_q": _B_in["w_q"],
        "B_w_uk": _B_in["w_uk"],
        "B_w_uv": _B_in["w_uv"],
        "B_w_o": _B_in["w_o"],
    }

def reference(A_x, A_wqkv, A_wo, B_x, B_c_kv, B_w_q, B_w_uk, B_w_uv, B_w_o):
    def _A_ref(x, wqkv, wo):
        B, S, D = x.shape
        H = 32; Dh = D // H
        W, dil = 8, 2
        qkv = (lambda x, *d: x.permute(*d))((x @ wqkv).reshape(B, S, 3, H, Dh), 2, 0, 3, 1, 4)
        q, k, v = qkv[0], qkv[1], qkv[2]
        scale = Dh ** -0.5
        pos = torch.arange(S)
        off = torch.arange(W) * dil
        idx = pos[:, None] - off[None, :]
        mask = idx >= 0
        idx_c = torch.where(mask, idx, 0).reshape(-1)
        kg = k[:, :, idx_c, :].reshape(B, H, S, W, Dh)
        vg = v[:, :, idx_c, :].reshape(B, H, S, W, Dh)
        logits = torch.einsum("bhsd,bhswd->bhsw", q, kg) * scale
        logits = torch.where(mask[None, None, :, :], logits, -1e9)
        attn = _softmax(logits, axis=-1)
        o = torch.einsum("bhsw,bhswd->bhsd", attn, vg)
        return (lambda x, *d: x.permute(*d))(o, 0, 2, 1, 3).reshape(B, S, D) @ wo

    def _B_ref(x, c_kv, w_q, w_uk, w_uv, w_o):
        B, Sq, M = x.shape[0], x.shape[1], x.shape[2]
        Sk = c_kv.shape[1]
        H, D = w_q.shape[1], w_q.shape[2]
        q = torch.einsum("bqm,mhd->bhqd", x, w_q)
        k = torch.einsum("bkc,chd->bhkd", c_kv, w_uk)
        v = torch.einsum("bkc,chd->bhkd", c_kv, w_uv)
        scores = torch.einsum("bhqd,bhkd->bhqk", q, k) * (D ** -0.5)
        off = Sk - Sq
        qi = torch.arange(Sq)[:, None]
        kj = torch.arange(Sk)[None, :]
        cmask = kj <= (qi + off)
        scores = torch.where(cmask[None, None], scores, -1e9)
        p = _softmax(scores, axis=-1)
        ctx = torch.einsum("bhqk,bhkd->bhqd", p, v)
        return torch.einsum("bhqd,hdm->bqm", ctx, w_o)

    a = _A_ref(A_x, A_wqkv, A_wo)
    b = _B_ref(B_x, B_c_kv, B_w_q, B_w_uk, B_w_uv, B_w_o)
    return torch.concatenate([a, b], axis=-1)
```

```cpp
#include <cuda_runtime.h>
#include <cuda_bf16.h>
#include <cuda.h>
#include <stdint.h>

namespace {

constexpr int SEQ = 2048;
constexpr int NCTA = 132, NPAIR = 66;
constexpr int MAX_ITEMS = 24;

__device__ __align__(1024) __nv_bfloat16 g_kv[32 * SEQ * 256];
__device__ __align__(1024) __nv_bfloat16 g_ctx[SEQ * 4096];
__device__ __align__(1024) __nv_bfloat16 g_oA[SEQ * 1024];
__device__ __align__(1024) uint8_t g_halo[16 * 16 * 2048];
struct Flags { uint32_t m[64]; uint32_t epoch[NCTA]; };
__device__ __align__(128) Flags g_flags;
enum { F_KV = 0, F_CTX = 32, F_QL = 48 };

enum { K_QL = 0, K_QF = 1, K_KV = 2, K_OA = 3, K_OB = 4, K_END = 7 };
enum { M_AX = 0, M_BX, M_CKV, M_OA, M_CTX, M_WQKV, M_WQ, M_WUK, M_WOA, M_WOB, M_WUV, M_KV_LD, M_OA_ST, M_CTX_ST, M_KV_ST, M_OUTA_ST, M_OUTB_ST, M_COUNT };

struct Params {
  CUtensorMap maps[M_COUNT];
  alignas(8) uint16_t sched[NPAIR][MAX_ITEMS];
};

#define TRC(idx, slot)
#define TRW(idx, slot)
#define T4D(n, slot, dep)
#define T4A(slot, dep)
#define T4S(slot, dep)
#define T4G(slot)
#define T4GD(slot, dep)

constexpr uint32_t SB = 1024;
constexpr uint32_t OFF_A = 0;
constexpr uint32_t OFF_B = 65536;
constexpr uint32_t OFF_STG = 196608;
constexpr uint32_t OFF_HALO = 229376;
constexpr uint32_t OFF_BAR = 231424;
constexpr uint32_t OFF_MASK = OFF_BAR + 256;
constexpr uint32_t OFF_LIST = OFF_BAR + 512;
constexpr uint32_t OFF_FILLS = OFF_BAR + 576;
constexpr uint32_t SMEM_BYTES = OFF_BAR + 640;
enum { B_FULL = 0, B_EMPTY = 4, B_QEMPTY = 8, B_STGE = 10, B_STGF = 12, B_FIN = 14, B_QFULL = 16, B_QX = 17, B_LEAD = 18, B_HFULL = 19, B_HEMPTY = 20, B_COUNT = 21 };
__host__ __device__ constexpr uint32_t BAR(int b) { return OFF_BAR + b * 8; }
__host__ __device__ constexpr int bar_count(int b) { return b < B_EMPTY ? 1 : b < B_QEMPTY ? 4 : b < B_STGE ? 8 : b < B_STGF ? 1 : b < B_QFULL ? 4 : b == B_QX ? 2 : 1; }
#define RCONS 232
constexpr int REG_CONS = RCONS, REG_PROD = (64512 - RCONS * 256) / 128 / 8 * 8;
#define PACE_MAX 500
#define WATCH_NS 250
#define HINTS 3
#define JSPLIT 14
#define JEDGE 14
#define JP 12
#define JDIAG 12
#define LEADN 2
#define LEADL LEADN
#define STGA 4
#define STGB 10
#define STGAL STGA
#define STGBL (STGB + 2)
#define PUBD 1

__device__ __forceinline__ uint32_t smem_u32(const void* p) { return (uint32_t)__cvta_generic_to_shared(p); }
__device__ __forceinline__ void wg_fence() { asm volatile("wgmma.fence.sync.aligned;" ::: "memory"); }
__device__ __forceinline__ void wg_commit() { asm volatile("wgmma.commit_group.sync.aligned;" ::: "memory"); }
template <int N> __device__ __forceinline__ void wg_wait() { asm volatile("wgmma.wait_group.sync.aligned %0;" ::"n"(N) : "memory"); }
__host__ __device__ constexpr uint32_t dlo(uint32_t off, uint32_t lbo) { return ((SB + off) >> 4) | ((lbo >> 4) << 16); }
template <uint32_t O> __device__ __forceinline__ void mbar_init(uint32_t a, uint32_t cnt) { asm volatile("mbarrier.init.shared::cta.b64 [%0+%2], %1;" ::"r"(a), "r"(cnt), "n"(O) : "memory"); }
template <uint32_t O> __device__ __forceinline__ void mbar_expect_tx(uint32_t a, uint32_t bytes) { asm volatile("mbarrier.arrive.expect_tx.shared::cta.b64 _, [%0+%2], %1;" ::"r"(a), "r"(bytes), "n"(O) : "memory"); }
template <uint32_t O> __device__ __forceinline__ void mbar_arrive(uint32_t a) { asm volatile("mbarrier.arrive.shared::cta.b64 _, [%0+%1];" ::"r"(a), "n"(O) : "memory"); }
template <uint32_t O> __device__ __forceinline__ void mbar_arrive_if(uint32_t a, bool pred) {
  asm volatile("{\n.reg .pred p;\nsetp.ne.u32 p, %1, 0;\n@p mbarrier.arrive.shared::cta.b64 _, [%0+%2];\n}\n" ::"r"(a), "r"((uint32_t)pred), "n"(O) : "memory");
}
template <uint32_t O> __device__ __forceinline__ void mbar_arrive_cl(uint32_t a, uint32_t off = 0) {
  asm volatile("{\n.reg .pred p;\nsetp.ne.u32 p, %2, 0;\n@p mbarrier.arrive.shared::cluster.b64 _, [%0+%1];\n}\n" ::"r"(a + off), "n"(O), "r"(a) : "memory");
}
template <uint32_t O> __device__ __forceinline__ bool mbar_test(uint32_t a, uint32_t parity) {
  uint32_t ok;
  asm volatile("{\n.reg .pred p;\nmbarrier.test_wait.parity.shared::cta.b64 p, [%1+%3], %2;\nselp.u32 %0, 1, 0, p;\n}\n" : "=r"(ok) : "r"(a), "r"(parity), "n"(O) : "memory");
  return ok;
}
template <uint32_t O> __device__ __forceinline__ void mbar_wait(uint32_t a, uint32_t parity) {
  asm volatile("{\n.reg .pred p, q;\n.reg .u32 n;\nmov.u32 n, 0;\nWAIT_%=:\nadd.u32 n, n, 1;\nmbarrier.try_wait.parity.shared::cta.b64 p, [%0+%2], %1;\n"
               "setp.lt.u32 q, n, 4194304;\nand.pred q, q, !p;\n@q bra WAIT_%=;\n@!p st.shared.u32 [%0+1], n;\n}\n" ::"r"(a), "r"(parity), "n"(O) : "memory");
}
__device__ __forceinline__ void tma_load_2d(uint32_t dst, const CUtensorMap* tm, int c0, int c1, uint32_t bar) {
  asm volatile("cp.async.bulk.tensor.2d.shared::cluster.global.mbarrier::complete_tx::bytes [%0], [%1, {%3, %4}], [%2];" ::"r"(dst), "l"(tm), "r"(bar), "r"(c0), "r"(c1) : "memory");
}
__device__ __forceinline__ void tma_load_3d(uint32_t dst, const CUtensorMap* tm, int c0, int c1, int c2, uint32_t bar) {
  asm volatile("cp.async.bulk.tensor.3d.shared::cluster.global.mbarrier::complete_tx::bytes [%0], [%1, {%3, %4, %5}], [%2];" ::"r"(dst), "l"(tm), "r"(bar), "r"(c0), "r"(c1), "r"(c2) : "memory");
}
__device__ __forceinline__ void tma_load_2d_mc(uint32_t dst, const CUtensorMap* tm, int c0, int c1, uint32_t bar, uint16_t mask) {
  asm volatile("cp.async.bulk.tensor.2d.shared::cluster.global.mbarrier::complete_tx::bytes.multicast::cluster [%0], [%1, {%3, %4}], [%2], %5;"
               ::"r"(dst), "l"(tm), "r"(bar), "r"(c0), "r"(c1), "h"(mask) : "memory");
}
__device__ __forceinline__ void tma_load_3d_mc(uint32_t dst, const CUtensorMap* tm, int c0, int c1, int c2, uint32_t bar, uint16_t mask) {
  asm volatile("cp.async.bulk.tensor.3d.shared::cluster.global.mbarrier::complete_tx::bytes.multicast::cluster [%0], [%1, {%3, %4, %5}], [%2], %6;"
               ::"r"(dst), "l"(tm), "r"(bar), "r"(c0), "r"(c1), "r"(c2), "h"(mask) : "memory");
}
__device__ __forceinline__ void tma_store_3d(const CUtensorMap* tm, uint32_t src, int c0, int c1, int c2, uint64_t pol) {
  asm volatile("cp.async.bulk.tensor.3d.global.shared::cta.bulk_group.L2::cache_hint [%0, {%2, %3, %4}], [%1], %5;" ::"l"(tm), "r"(src), "r"(c0), "r"(c1), "r"(c2), "l"(pol) : "memory");
}
__device__ __forceinline__ void bulk_load(uint32_t dst, const void* src, uint32_t bytes, uint32_t bar) {
  asm volatile("cp.async.bulk.shared::cluster.global.mbarrier::complete_tx::bytes [%0], [%1], %2, [%3];" ::"r"(dst), "l"(src), "r"(bytes), "r"(bar) : "memory");
}
__device__ __forceinline__ void bulk_store(void* dst, uint32_t src, uint32_t bytes) {
  asm volatile("cp.async.bulk.global.shared::cta.bulk_group [%0], [%1], %2;" ::"l"(dst), "r"(src), "r"(bytes) : "memory");
}
__device__ __forceinline__ void bulk_send(uint32_t dst, uint32_t src, uint32_t bytes, uint32_t bar) {
  asm volatile("cp.async.bulk.shared::cluster.shared::cta.mbarrier::complete_tx::bytes [%0], [%1], %2, [%3];" ::"r"(dst), "r"(src), "r"(bytes), "r"(bar) : "memory");
}
__device__ __forceinline__ uint64_t policy_evict_first() { uint64_t p; asm volatile("createpolicy.fractional.L2::evict_first.b64 %0, 1.0;" : "=l"(p)); return p; }
__device__ __forceinline__ uint64_t policy_evict_normal() { uint64_t p; asm volatile("createpolicy.fractional.L2::evict_normal.b64 %0, 1.0;" : "=l"(p)); return p; }
__device__ __forceinline__ uint32_t mapa(uint32_t addr, uint32_t rank) { uint32_t r; asm("mapa.shared::cluster.u32 %0, %1, %2;" : "=r"(r) : "r"(addr), "r"(rank)); return r; }
__device__ __forceinline__ void cluster_arrive_relaxed() { asm volatile("barrier.cluster.arrive.relaxed.aligned;" ::: "memory"); }
__device__ __forceinline__ void cluster_arrive() { asm volatile("barrier.cluster.arrive.release.aligned;" ::: "memory"); }
__device__ __forceinline__ void cluster_wait() { asm volatile("barrier.cluster.wait.acquire.aligned;" ::: "memory"); }
__device__ __forceinline__ void bulk_commit() { asm volatile("cp.async.bulk.commit_group;" ::: "memory"); }
template <int N> __device__ __forceinline__ void bulk_wait_read() { asm volatile("cp.async.bulk.wait_group.read %0;" ::"n"(N) : "memory"); }
__device__ __forceinline__ void bulk_wait_all() { asm volatile("cp.async.bulk.wait_group 0;" ::: "memory"); }
__device__ __forceinline__ void fence_async_smem() { asm volatile("fence.proxy.async.shared::cta;" ::: "memory"); }
__device__ __forceinline__ void fence_async_glob() { asm volatile("fence.proxy.async.global;" ::: "memory"); }
__device__ __forceinline__ uint32_t ld_acquire(const uint32_t* p) { uint32_t v; asm volatile("ld.acquire.gpu.global.u32 %0, [%1];" : "=r"(v) : "l"(p) : "memory"); return v; }
__device__ __forceinline__ void flag_toggle(uint32_t* p, uint32_t v) { asm volatile("red.release.gpu.global.xor.b32 [%0], %1;" ::"l"(p), "r"(v) : "memory"); }
template <uint32_t O> __device__ __forceinline__ uint32_t lds_acquire(uint32_t a) { uint32_t v; asm volatile("ld.acquire.cta.shared::cta.u32 %0, [%1+%2];" : "=r"(v) : "r"(a), "n"(O) : "memory"); return v; }
template <uint32_t O> __device__ __forceinline__ void sts_release(uint32_t a, uint32_t v) { asm volatile("st.release.cta.shared::cta.u32 [%0+%2], %1;" ::"r"(a), "r"(v), "n"(O) : "memory"); }
__device__ __forceinline__ uint32_t item1(uint32_t sb, int idx) { uint32_t c; asm volatile("ld.shared.u16 %0, [%1+%2];" : "=r"(c) : "r"(sb + idx * 2), "n"(OFF_LIST)); return c; }
__device__ __forceinline__ uint32_t item(uint32_t sb, int idx) { return __reduce_or_sync(0xffffffffu, item1(sb, idx)); }
template <int N> __device__ __forceinline__ void reg_alloc() { asm volatile("setmaxnreg.inc.sync.aligned.u32 %0;" ::"n"(N)); }
template <int N> __device__ __forceinline__ void reg_dealloc() { asm volatile("setmaxnreg.dec.sync.aligned.u32 %0;" ::"n"(N)); }
template <int I0, int I1, int N> __device__ __forceinline__ void fence_regs(float (&d)[N]) {
#pragma unroll
  for (int i = I0; i < I1; i++) asm volatile("" : "+f"(d[i])::"memory");
}
template <int N> __device__ __forceinline__ void fence_regs(float (&d)[N]) { fence_regs<0, N, N>(d); }
template <int N> __device__ __forceinline__ void fence_regs(uint32_t (&d)[N]) {
#pragma unroll
  for (int i = 0; i < N; i++) asm volatile("" : "+r"(d[i])::"memory");
}
__device__ __forceinline__ uint32_t pack_bf16(float lo, float hi) { uint32_t r; asm("cvt.rn.bf16x2.f32 %0, %1, %2;" : "=r"(r) : "f"(hi), "f"(lo)); return r; }
template <uint32_t O> __device__ __forceinline__ void stmatrix_x4(uint32_t a, uint32_t r0, uint32_t r1, uint32_t r2, uint32_t r3) {
  asm volatile("stmatrix.sync.aligned.m8n8.x4.shared.b16 [%0+%5], {%1, %2, %3, %4};" ::"r"(a), "r"(r0), "r"(r1), "r"(r2), "r"(r3), "n"(O) : "memory");
}
template <uint32_t O> __device__ __forceinline__ void stmatrix_x4_after(uint32_t a, uint32_t r0, uint32_t r1, uint32_t r2, uint32_t r3, float dep) {
  asm volatile("{\n.reg .pred q;\n.reg .u32 a;\nsetp.ne.u32 q, %6, 0xffffffff;\nselp.u32 a, %0, 0, q;\nstmatrix.sync.aligned.m8n8.x4.shared.b16 [a+%5], {%1, %2, %3, %4};\n}\n"
               ::"r"(a), "r"(r0), "r"(r1), "r"(r2), "r"(r3), "n"(O), "r"(__float_as_uint(dep)) : "memory");
}
template <uint32_t O> __device__ __forceinline__ void stmatrix_x4_trans(uint32_t a, uint32_t r0, uint32_t r1, uint32_t r2, uint32_t r3) {
  asm volatile("stmatrix.sync.aligned.m8n8.x4.trans.shared.b16 [%0+%5], {%1, %2, %3, %4};" ::"r"(a), "r"(r0), "r"(r1), "r"(r2), "r"(r3), "n"(O) : "memory");
}
template <uint32_t O> __device__ __forceinline__ void sts128(uint32_t a, const uint32_t* r) { asm volatile("st.shared.v4.u32 [%0+%5], {%1, %2, %3, %4};" ::"r"(a), "r"(r[0]), "r"(r[1]), "r"(r[2]), "r"(r[3]), "n"(O) : "memory"); }
template <uint32_t O> __device__ __forceinline__ void lds128(uint32_t* r, uint32_t a) { asm volatile("ld.shared.v4.u32 {%0, %1, %2, %3}, [%4+%5];" : "=r"(r[0]), "=r"(r[1]), "=r"(r[2]), "=r"(r[3]) : "r"(a), "n"(O) : "memory"); }
__device__ __forceinline__ uint32_t transpose8(uint32_t a) { uint32_t d; asm volatile("movmatrix.sync.aligned.m8n8.trans.b16 %0, %1;" : "=r"(d) : "r"(a)); return d; }
__device__ __forceinline__ float ex2(float x) { float y; asm("ex2.approx.ftz.f32 %0, %1;" : "=f"(y) : "f"(x)); return y; }
__device__ __forceinline__ float rcp(float x) { float y; asm("rcp.approx.ftz.f32 %0, %1;" : "=f"(y) : "f"(x)); return y; }
__device__ __forceinline__ void bar_sync(int id, int n) { asm volatile("bar.sync %0, %1;" ::"r"(id), "r"(n) : "memory"); }
__device__ __forceinline__ void bar_arrive(int id, int n) { asm volatile("bar.arrive %0, %1;" ::"r"(id), "r"(n) : "memory"); }
__device__ __forceinline__ void mma16816(float (&c)[4], uint32_t a0, uint32_t a1, uint32_t a2, uint32_t a3, uint32_t b0, uint32_t b1) {
  asm("mma.sync.aligned.m16n8k16.row.col.f32.bf16.bf16.f32 {%0, %1, %2, %3}, {%4, %5, %6, %7}, {%8, %9}, {%0, %1, %2, %3};"
      : "+f"(c[0]), "+f"(c[1]), "+f"(c[2]), "+f"(c[3]) : "r"(a0), "r"(a1), "r"(a2), "r"(a3), "r"(b0), "r"(b1));
}
__device__ __forceinline__ void mma16816z(float (&c)[4], uint32_t a0, uint32_t a1, uint32_t a2, uint32_t a3, uint32_t b0, uint32_t b1, float z) {
  asm("mma.sync.aligned.m16n8k16.row.col.f32.bf16.bf16.f32 {%0, %1, %2, %3}, {%4, %5, %6, %7}, {%8, %9}, {%10, %10, %10, %10};"
      : "=f"(c[0]), "=f"(c[1]), "=f"(c[2]), "=f"(c[3]) : "r"(a0), "r"(a1), "r"(a2), "r"(a3), "r"(b0), "r"(b1), "f"(z));
}
__device__ __forceinline__ uint4 ldg128(const void* p) { uint4 v; asm volatile("ld.global.cg.v4.u32 {%0, %1, %2, %3}, [%4];" : "=r"(v.x), "=r"(v.y), "=r"(v.z), "=r"(v.w) : "l"(p) : "memory"); return v; }
__device__ __forceinline__ uint32_t ldg16(const void* p) { uint16_t v; asm volatile("ld.global.cg.u16 %0, [%1];" : "=h"(v) : "l"(p) : "memory"); return v; }
__device__ __forceinline__ float quad_sum(float v) {
  v += __shfl_xor_sync(0xffffffffu, v, 1);
  v += __shfl_xor_sync(0xffffffffu, v, 2);
  return v;
}
#define UNLIKELY(x) __builtin_expect(!!(x), 0)

__device__ __forceinline__ void wg_gemm_init(float (&d)[128], uint32_t alo, uint32_t blo) {
  asm volatile("{\n.reg .pred p;\n.reg .b64 da, db;\nmov.b64 da, {%128, 0x40000040};\nmov.b64 db, {%129, 0x40000040};\nsetp.ne.b32 p, 0, 0;\n"
    "wgmma.mma_async.sync.aligned.m64n256k16.f32.bf16.bf16 {"
    "%0, %1, %2, %3, %4, %5, %6, %7, %8, %9, %10, %11, %12, %13, %14, %15, %16, %17, %18, %19, %20, %21, %22, %23, %24, %25, %26, %27, %28, %29, %30, %31, "
    "%32, %33, %34, %35, %36, %37, %38, %39, %40, %41, %42, %43, %44, %45, %46, %47, %48, %49, %50, %51, %52, %53, %54, %55, %56, %57, %58, %59, %60, %61, %62, %63, "
    "%64, %65, %66, %67, %68, %69, %70, %71, %72, %73, %74, %75, %76, %77, %78, %79, %80, %81, %82, %83, %84, %85, %86, %87, %88, %89, %90, %91, %92, %93, %94, %95, "
    "%96, %97, %98, %99, %100, %101, %102, %103, %104, %105, %106, %107, %108, %109, %110, %111, %112, %113, %114, %115, %116, %117, %118, %119, %120, %121, %122, %123, %124, %125, %126, %127}, "
    "da, db, p, 1, 1, 0, 1;\n}\n"
    : "=f"(d[0]), "=f"(d[1]), "=f"(d[2]), "=f"(d[3]), "=f"(d[4]), "=f"(d[5]), "=f"(d[6]), "=f"(d[7]), "=f"(d[8]), "=f"(d[9]), "=f"(d[10]), "=f"(d[11]), "=f"(d[12]), "=f"(d[13]), "=f"(d[14]), "=f"(d[15]),
      "=f"(d[16]), "=f"(d[17]), "=f"(d[18]), "=f"(d[19]), "=f"(d[20]), "=f"(d[21]), "=f"(d[22]), "=f"(d[23]), "=f"(d[24]), "=f"(d[25]), "=f"(d[26]), "=f"(d[27]), "=f"(d[28]), "=f"(d[29]), "=f"(d[30]), "=f"(d[31]),
      "=f"(d[32]), "=f"(d[33]), "=f"(d[34]), "=f"(d[35]), "=f"(d[36]), "=f"(d[37]), "=f"(d[38]), "=f"(d[39]), "=f"(d[40]), "=f"(d[41]), "=f"(d[42]), "=f"(d[43]), "=f"(d[44]), "=f"(d[45]), "=f"(d[46]), "=f"(d[47]),
      "=f"(d[48]), "=f"(d[49]), "=f"(d[50]), "=f"(d[51]), "=f"(d[52]), "=f"(d[53]), "=f"(d[54]), "=f"(d[55]), "=f"(d[56]), "=f"(d[57]), "=f"(d[58]), "=f"(d[59]), "=f"(d[60]), "=f"(d[61]), "=f"(d[62]), "=f"(d[63]),
      "=f"(d[64]), "=f"(d[65]), "=f"(d[66]), "=f"(d[67]), "=f"(d[68]), "=f"(d[69]), "=f"(d[70]), "=f"(d[71]), "=f"(d[72]), "=f"(d[73]), "=f"(d[74]), "=f"(d[75]), "=f"(d[76]), "=f"(d[77]), "=f"(d[78]), "=f"(d[79]),
      "=f"(d[80]), "=f"(d[81]), "=f"(d[82]), "=f"(d[83]), "=f"(d[84]), "=f"(d[85]), "=f"(d[86]), "=f"(d[87]), "=f"(d[88]), "=f"(d[89]), "=f"(d[90]), "=f"(d[91]), "=f"(d[92]), "=f"(d[93]), "=f"(d[94]), "=f"(d[95]),
      "=f"(d[96]), "=f"(d[97]), "=f"(d[98]), "=f"(d[99]), "=f"(d[100]), "=f"(d[101]), "=f"(d[102]), "=f"(d[103]), "=f"(d[104]), "=f"(d[105]), "=f"(d[106]), "=f"(d[107]), "=f"(d[108]), "=f"(d[109]), "=f"(d[110]), "=f"(d[111]),
      "=f"(d[112]), "=f"(d[113]), "=f"(d[114]), "=f"(d[115]), "=f"(d[116]), "=f"(d[117]), "=f"(d[118]), "=f"(d[119]), "=f"(d[120]), "=f"(d[121]), "=f"(d[122]), "=f"(d[123]), "=f"(d[124]), "=f"(d[125]), "=f"(d[126]), "=f"(d[127])
    : "r"(alo), "r"(blo));
}
__device__ __forceinline__ void wg_gemm_acc(float (&d)[128], uint32_t alo, uint32_t blo) {
  asm volatile("{\n.reg .pred p;\n.reg .b64 da, db;\nmov.b64 da, {%128, 0x40000040};\nmov.b64 db, {%129, 0x40000040};\nsetp.eq.b32 p, 0, 0;\n"
    "wgmma.mma_async.sync.aligned.m64n256k16.f32.bf16.bf16 {"
    "%0, %1, %2, %3, %4, %5, %6, %7, %8, %9, %10, %11, %12, %13, %14, %15, %16, %17, %18, %19, %20, %21, %22, %23, %24, %25, %26, %27, %28, %29, %30, %31, "
    "%32, %33, %34, %35, %36, %37, %38, %39, %40, %41, %42, %43, %44, %45, %46, %47, %48, %49, %50, %51, %52, %53, %54, %55, %56, %57, %58, %59, %60, %61, %62, %63, "
    "%64, %65, %66, %67, %68, %69, %70, %71, %72, %73, %74, %75, %76, %77, %78, %79, %80, %81, %82, %83, %84, %85, %86, %87, %88, %89, %90, %91, %92, %93, %94, %95, "
    "%96, %97, %98, %99, %100, %101, %102, %103, %104, %105, %106, %107, %108, %109, %110, %111, %112, %113, %114, %115, %116, %117, %118, %119, %120, %121, %122, %123, %124, %125, %126, %127}, "
    "da, db, p, 1, 1, 0, 1;\n}\n"
    : "+f"(d[0]), "+f"(d[1]), "+f"(d[2]), "+f"(d[3]), "+f"(d[4]), "+f"(d[5]), "+f"(d[6]), "+f"(d[7]), "+f"(d[8]), "+f"(d[9]), "+f"(d[10]), "+f"(d[11]), "+f"(d[12]), "+f"(d[13]), "+f"(d[14]), "+f"(d[15]),
      "+f"(d[16]), "+f"(d[17]), "+f"(d[18]), "+f"(d[19]), "+f"(d[20]), "+f"(d[21]), "+f"(d[22]), "+f"(d[23]), "+f"(d[24]), "+f"(d[25]), "+f"(d[26]), "+f"(d[27]), "+f"(d[28]), "+f"(d[29]), "+f"(d[30]), "+f"(d[31]),
      "+f"(d[32]), "+f"(d[33]), "+f"(d[34]), "+f"(d[35]), "+f"(d[36]), "+f"(d[37]), "+f"(d[38]), "+f"(d[39]), "+f"(d[40]), "+f"(d[41]), "+f"(d[42]), "+f"(d[43]), "+f"(d[44]), "+f"(d[45]), "+f"(d[46]), "+f"(d[47]),
      "+f"(d[48]), "+f"(d[49]), "+f"(d[50]), "+f"(d[51]), "+f"(d[52]), "+f"(d[53]), "+f"(d[54]), "+f"(d[55]), "+f"(d[56]), "+f"(d[57]), "+f"(d[58]), "+f"(d[59]), "+f"(d[60]), "+f"(d[61]), "+f"(d[62]), "+f"(d[63]),
      "+f"(d[64]), "+f"(d[65]), "+f"(d[66]), "+f"(d[67]), "+f"(d[68]), "+f"(d[69]), "+f"(d[70]), "+f"(d[71]), "+f"(d[72]), "+f"(d[73]), "+f"(d[74]), "+f"(d[75]), "+f"(d[76]), "+f"(d[77]), "+f"(d[78]), "+f"(d[79]),
      "+f"(d[80]), "+f"(d[81]), "+f"(d[82]), "+f"(d[83]), "+f"(d[84]), "+f"(d[85]), "+f"(d[86]), "+f"(d[87]), "+f"(d[88]), "+f"(d[89]), "+f"(d[90]), "+f"(d[91]), "+f"(d[92]), "+f"(d[93]), "+f"(d[94]), "+f"(d[95]),
      "+f"(d[96]), "+f"(d[97]), "+f"(d[98]), "+f"(d[99]), "+f"(d[100]), "+f"(d[101]), "+f"(d[102]), "+f"(d[103]), "+f"(d[104]), "+f"(d[105]), "+f"(d[106]), "+f"(d[107]), "+f"(d[108]), "+f"(d[109]), "+f"(d[110]), "+f"(d[111]),
      "+f"(d[112]), "+f"(d[113]), "+f"(d[114]), "+f"(d[115]), "+f"(d[116]), "+f"(d[117]), "+f"(d[118]), "+f"(d[119]), "+f"(d[120]), "+f"(d[121]), "+f"(d[122]), "+f"(d[123]), "+f"(d[124]), "+f"(d[125]), "+f"(d[126]), "+f"(d[127])
    : "r"(alo), "r"(blo));
}
__device__ __forceinline__ void wg_gemm_init(float (&d)[96], uint32_t alo, uint32_t blo) {
  asm volatile("{\n.reg .pred p;\n.reg .b64 da, db;\nmov.b64 da, {%96, 0x40000040};\nmov.b64 db, {%97, 0x40000040};\nsetp.ne.b32 p, 0, 0;\n"
    "wgmma.mma_async.sync.aligned.m64n192k16.f32.bf16.bf16 {"
    "%0, %1, %2, %3, %4, %5, %6, %7, %8, %9, %10, %11, %12, %13, %14, %15, %16, %17, %18, %19, %20, %21, %22, %23, %24, %25, %26, %27, %28, %29, %30, %31, "
    "%32, %33, %34, %35, %36, %37, %38, %39, %40, %41, %42, %43, %44, %45, %46, %47, %48, %49, %50, %51, %52, %53, %54, %55, %56, %57, %58, %59, %60, %61, %62, %63, "
    "%64, %65, %66, %67, %68, %69, %70, %71, %72, %73, %74, %75, %76, %77, %78, %79, %80, %81, %82, %83, %84, %85, %86, %87, %88, %89, %90, %91, %92, %93, %94, %95}, "
    "da, db, p, 1, 1, 0, 1;\n}\n"
    : "=f"(d[0]), "=f"(d[1]), "=f"(d[2]), "=f"(d[3]), "=f"(d[4]), "=f"(d[5]), "=f"(d[6]), "=f"(d[7]), "=f"(d[8]), "=f"(d[9]), "=f"(d[10]), "=f"(d[11]), "=f"(d[12]), "=f"(d[13]), "=f"(d[14]), "=f"(d[15]),
      "=f"(d[16]), "=f"(d[17]), "=f"(d[18]), "=f"(d[19]), "=f"(d[20]), "=f"(d[21]), "=f"(d[22]), "=f"(d[23]), "=f"(d[24]), "=f"(d[25]), "=f"(d[26]), "=f"(d[27]), "=f"(d[28]), "=f"(d[29]), "=f"(d[30]), "=f"(d[31]),
      "=f"(d[32]), "=f"(d[33]), "=f"(d[34]), "=f"(d[35]), "=f"(d[36]), "=f"(d[37]), "=f"(d[38]), "=f"(d[39]), "=f"(d[40]), "=f"(d[41]), "=f"(d[42]), "=f"(d[43]), "=f"(d[44]), "=f"(d[45]), "=f"(d[46]), "=f"(d[47]),
      "=f"(d[48]), "=f"(d[49]), "=f"(d[50]), "=f"(d[51]), "=f"(d[52]), "=f"(d[53]), "=f"(d[54]), "=f"(d[55]), "=f"(d[56]), "=f"(d[57]), "=f"(d[58]), "=f"(d[59]), "=f"(d[60]), "=f"(d[61]), "=f"(d[62]), "=f"(d[63]),
      "=f"(d[64]), "=f"(d[65]), "=f"(d[66]), "=f"(d[67]), "=f"(d[68]), "=f"(d[69]), "=f"(d[70]), "=f"(d[71]), "=f"(d[72]), "=f"(d[73]), "=f"(d[74]), "=f"(d[75]), "=f"(d[76]), "=f"(d[77]), "=f"(d[78]), "=f"(d[79]),
      "=f"(d[80]), "=f"(d[81]), "=f"(d[82]), "=f"(d[83]), "=f"(d[84]), "=f"(d[85]), "=f"(d[86]), "=f"(d[87]), "=f"(d[88]), "=f"(d[89]), "=f"(d[90]), "=f"(d[91]), "=f"(d[92]), "=f"(d[93]), "=f"(d[94]), "=f"(d[95])
    : "r"(alo), "r"(blo));
}
__device__ __forceinline__ void wg_gemm_acc(float (&d)[96], uint32_t alo, uint32_t blo) {
  asm volatile("{\n.reg .pred p;\n.reg .b64 da, db;\nmov.b64 da, {%96, 0x40000040};\nmov.b64 db, {%97, 0x40000040};\nsetp.eq.b32 p, 0, 0;\n"
    "wgmma.mma_async.sync.aligned.m64n192k16.f32.bf16.bf16 {"
    "%0, %1, %2, %3, %4, %5, %6, %7, %8, %9, %10, %11, %12, %13, %14, %15, %16, %17, %18, %19, %20, %21, %22, %23, %24, %25, %26, %27, %28, %29, %30, %31, "
    "%32, %33, %34, %35, %36, %37, %38, %39, %40, %41, %42, %43, %44, %45, %46, %47, %48, %49, %50, %51, %52, %53, %54, %55, %56, %57, %58, %59, %60, %61, %62, %63, "
    "%64, %65, %66, %67, %68, %69, %70, %71, %72, %73, %74, %75, %76, %77, %78, %79, %80, %81, %82, %83, %84, %85, %86, %87, %88, %89, %90, %91, %92, %93, %94, %95}, "
    "da, db, p, 1, 1, 0, 1;\n}\n"
    : "+f"(d[0]), "+f"(d[1]), "+f"(d[2]), "+f"(d[3]), "+f"(d[4]), "+f"(d[5]), "+f"(d[6]), "+f"(d[7]), "+f"(d[8]), "+f"(d[9]), "+f"(d[10]), "+f"(d[11]), "+f"(d[12]), "+f"(d[13]), "+f"(d[14]), "+f"(d[15]),
      "+f"(d[16]), "+f"(d[17]), "+f"(d[18]), "+f"(d[19]), "+f"(d[20]), "+f"(d[21]), "+f"(d[22]), "+f"(d[23]), "+f"(d[24]), "+f"(d[25]), "+f"(d[26]), "+f"(d[27]), "+f"(d[28]), "+f"(d[29]), "+f"(d[30]), "+f"(d[31]),
      "+f"(d[32]), "+f"(d[33]), "+f"(d[34]), "+f"(d[35]), "+f"(d[36]), "+f"(d[37]), "+f"(d[38]), "+f"(d[39]), "+f"(d[40]), "+f"(d[41]), "+f"(d[42]), "+f"(d[43]), "+f"(d[44]), "+f"(d[45]), "+f"(d[46]), "+f"(d[47]),
      "+f"(d[48]), "+f"(d[49]), "+f"(d[50]), "+f"(d[51]), "+f"(d[52]), "+f"(d[53]), "+f"(d[54]), "+f"(d[55]), "+f"(d[56]), "+f"(d[57]), "+f"(d[58]), "+f"(d[59]), "+f"(d[60]), "+f"(d[61]), "+f"(d[62]), "+f"(d[63]),
      "+f"(d[64]), "+f"(d[65]), "+f"(d[66]), "+f"(d[67]), "+f"(d[68]), "+f"(d[69]), "+f"(d[70]), "+f"(d[71]), "+f"(d[72]), "+f"(d[73]), "+f"(d[74]), "+f"(d[75]), "+f"(d[76]), "+f"(d[77]), "+f"(d[78]), "+f"(d[79]),
      "+f"(d[80]), "+f"(d[81]), "+f"(d[82]), "+f"(d[83]), "+f"(d[84]), "+f"(d[85]), "+f"(d[86]), "+f"(d[87]), "+f"(d[88]), "+f"(d[89]), "+f"(d[90]), "+f"(d[91]), "+f"(d[92]), "+f"(d[93]), "+f"(d[94]), "+f"(d[95])
    : "r"(alo), "r"(blo));
}
__device__ __forceinline__ void wg_qk_init(float (&d)[64], uint32_t alo, uint32_t blo) {
  asm volatile("{\n.reg .pred p;\n.reg .b64 da, db;\nmov.b64 da, {%64, 0x40000040};\nmov.b64 db, {%65, 0x40000040};\nsetp.ne.b32 p, 0, 0;\n"
    "wgmma.mma_async.sync.aligned.m64n128k16.f32.bf16.bf16 {"
    "%0, %1, %2, %3, %4, %5, %6, %7, %8, %9, %10, %11, %12, %13, %14, %15, %16, %17, %18, %19, %20, %21, %22, %23, %24, %25, %26, %27, %28, %29, %30, %31, "
    "%32, %33, %34, %35, %36, %37, %38, %39, %40, %41, %42, %43, %44, %45, %46, %47, %48, %49, %50, %51, %52, %53, %54, %55, %56, %57, %58, %59, %60, %61, %62, %63}, "
    "da, db, p, 1, 1, 0, 0;\n}\n"
    : "=f"(d[0]), "=f"(d[1]), "=f"(d[2]), "=f"(d[3]), "=f"(d[4]), "=f"(d[5]), "=f"(d[6]), "=f"(d[7]), "=f"(d[8]), "=f"(d[9]), "=f"(d[10]), "=f"(d[11]), "=f"(d[12]), "=f"(d[13]), "=f"(d[14]), "=f"(d[15]),
      "=f"(d[16]), "=f"(d[17]), "=f"(d[18]), "=f"(d[19]), "=f"(d[20]), "=f"(d[21]), "=f"(d[22]), "=f"(d[23]), "=f"(d[24]), "=f"(d[25]), "=f"(d[26]), "=f"(d[27]), "=f"(d[28]), "=f"(d[29]), "=f"(d[30]), "=f"(d[31]),
      "=f"(d[32]), "=f"(d[33]), "=f"(d[34]), "=f"(d[35]), "=f"(d[36]), "=f"(d[37]), "=f"(d[38]), "=f"(d[39]), "=f"(d[40]), "=f"(d[41]), "=f"(d[42]), "=f"(d[43]), "=f"(d[44]), "=f"(d[45]), "=f"(d[46]), "=f"(d[47]),
      "=f"(d[48]), "=f"(d[49]), "=f"(d[50]), "=f"(d[51]), "=f"(d[52]), "=f"(d[53]), "=f"(d[54]), "=f"(d[55]), "=f"(d[56]), "=f"(d[57]), "=f"(d[58]), "=f"(d[59]), "=f"(d[60]), "=f"(d[61]), "=f"(d[62]), "=f"(d[63])
    : "r"(alo), "r"(blo));
}
__device__ __forceinline__ void wg_qk_acc(float (&d)[64], uint32_t alo, uint32_t blo) {
  asm volatile("{\n.reg .pred p;\n.reg .b64 da, db;\nmov.b64 da, {%64, 0x40000040};\nmov.b64 db, {%65, 0x40000040};\nsetp.eq.b32 p, 0, 0;\n"
    "wgmma.mma_async.sync.aligned.m64n128k16.f32.bf16.bf16 {"
    "%0, %1, %2, %3, %4, %5, %6, %7, %8, %9, %10, %11, %12, %13, %14, %15, %16, %17, %18, %19, %20, %21, %22, %23, %24, %25, %26, %27, %28, %29, %30, %31, "
    "%32, %33, %34, %35, %36, %37, %38, %39, %40, %41, %42, %43, %44, %45, %46, %47, %48, %49, %50, %51, %52, %53, %54, %55, %56, %57, %58, %59, %60, %61, %62, %63}, "
    "da, db, p, 1, 1, 0, 0;\n}\n"
    : "+f"(d[0]), "+f"(d[1]), "+f"(d[2]), "+f"(d[3]), "+f"(d[4]), "+f"(d[5]), "+f"(d[6]), "+f"(d[7]), "+f"(d[8]), "+f"(d[9]), "+f"(d[10]), "+f"(d[11]), "+f"(d[12]), "+f"(d[13]), "+f"(d[14]), "+f"(d[15]),
      "+f"(d[16]), "+f"(d[17]), "+f"(d[18]), "+f"(d[19]), "+f"(d[20]), "+f"(d[21]), "+f"(d[22]), "+f"(d[23]), "+f"(d[24]), "+f"(d[25]), "+f"(d[26]), "+f"(d[27]), "+f"(d[28]), "+f"(d[29]), "+f"(d[30]), "+f"(d[31]),
      "+f"(d[32]), "+f"(d[33]), "+f"(d[34]), "+f"(d[35]), "+f"(d[36]), "+f"(d[37]), "+f"(d[38]), "+f"(d[39]), "+f"(d[40]), "+f"(d[41]), "+f"(d[42]), "+f"(d[43]), "+f"(d[44]), "+f"(d[45]), "+f"(d[46]), "+f"(d[47]),
      "+f"(d[48]), "+f"(d[49]), "+f"(d[50]), "+f"(d[51]), "+f"(d[52]), "+f"(d[53]), "+f"(d[54]), "+f"(d[55]), "+f"(d[56]), "+f"(d[57]), "+f"(d[58]), "+f"(d[59]), "+f"(d[60]), "+f"(d[61]), "+f"(d[62]), "+f"(d[63])
    : "r"(alo), "r"(blo));
}
__device__ __forceinline__ void wg_qk64_init(float (&d)[64], uint32_t alo, uint32_t blo) {
  asm volatile("{\n.reg .pred p;\n.reg .b64 da, db;\nmov.b64 da, {%32, 0x40000040};\nmov.b64 db, {%33, 0x40000040};\nsetp.ne.b32 p, 0, 0;\n"
    "wgmma.mma_async.sync.aligned.m64n64k16.f32.bf16.bf16 {"
    "%0, %1, %2, %3, %4, %5, %6, %7, %8, %9, %10, %11, %12, %13, %14, %15, %16, %17, %18, %19, %20, %21, %22, %23, %24, %25, %26, %27, %28, %29, %30, %31}, "
    "da, db, p, 1, 1, 0, 0;\n}\n"
    : "=f"(d[0]), "=f"(d[1]), "=f"(d[2]), "=f"(d[3]), "=f"(d[4]), "=f"(d[5]), "=f"(d[6]), "=f"(d[7]), "=f"(d[8]), "=f"(d[9]), "=f"(d[10]), "=f"(d[11]), "=f"(d[12]), "=f"(d[13]), "=f"(d[14]), "=f"(d[15]),
      "=f"(d[16]), "=f"(d[17]), "=f"(d[18]), "=f"(d[19]), "=f"(d[20]), "=f"(d[21]), "=f"(d[22]), "=f"(d[23]), "=f"(d[24]), "=f"(d[25]), "=f"(d[26]), "=f"(d[27]), "=f"(d[28]), "=f"(d[29]), "=f"(d[30]), "=f"(d[31])
    : "r"(alo), "r"(blo));
}
__device__ __forceinline__ void wg_qk64_acc(float (&d)[64], uint32_t alo, uint32_t blo) {
  asm volatile("{\n.reg .pred p;\n.reg .b64 da, db;\nmov.b64 da, {%32, 0x40000040};\nmov.b64 db, {%33, 0x40000040};\nsetp.eq.b32 p, 0, 0;\n"
    "wgmma.mma_async.sync.aligned.m64n64k16.f32.bf16.bf16 {"
    "%0, %1, %2, %3, %4, %5, %6, %7, %8, %9, %10, %11, %12, %13, %14, %15, %16, %17, %18, %19, %20, %21, %22, %23, %24, %25, %26, %27, %28, %29, %30, %31}, "
    "da, db, p, 1, 1, 0, 0;\n}\n"
    : "+f"(d[0]), "+f"(d[1]), "+f"(d[2]), "+f"(d[3]), "+f"(d[4]), "+f"(d[5]), "+f"(d[6]), "+f"(d[7]), "+f"(d[8]), "+f"(d[9]), "+f"(d[10]), "+f"(d[11]), "+f"(d[12]), "+f"(d[13]), "+f"(d[14]), "+f"(d[15]),
      "+f"(d[16]), "+f"(d[17]), "+f"(d[18]), "+f"(d[19]), "+f"(d[20]), "+f"(d[21]), "+f"(d[22]), "+f"(d[23]), "+f"(d[24]), "+f"(d[25]), "+f"(d[26]), "+f"(d[27]), "+f"(d[28]), "+f"(d[29]), "+f"(d[30]), "+f"(d[31])
    : "r"(alo), "r"(blo));
}
__device__ __forceinline__ void wg_pv_sel(float (&d)[64], const uint32_t* a, uint32_t blo, uint32_t accumulate) {
  asm volatile("{\n.reg .pred p;\n.reg .b64 da, db;\nmov.b64 db, {%68, 0x40000040};\nsetp.ne.b32 p, %69, 0;\n"
    "wgmma.mma_async.sync.aligned.m64n128k16.f32.bf16.bf16 {"
    "%0, %1, %2, %3, %4, %5, %6, %7, %8, %9, %10, %11, %12, %13, %14, %15, %16, %17, %18, %19, %20, %21, %22, %23, %24, %25, %26, %27, %28, %29, %30, %31, "
    "%32, %33, %34, %35, %36, %37, %38, %39, %40, %41, %42, %43, %44, %45, %46, %47, %48, %49, %50, %51, %52, %53, %54, %55, %56, %57, %58, %59, %60, %61, %62, %63}, "
    "{%64, %65, %66, %67}, db, p, 1, 1, 1;\n}\n"
    : "+f"(d[0]), "+f"(d[1]), "+f"(d[2]), "+f"(d[3]), "+f"(d[4]), "+f"(d[5]), "+f"(d[6]), "+f"(d[7]), "+f"(d[8]), "+f"(d[9]), "+f"(d[10]), "+f"(d[11]), "+f"(d[12]), "+f"(d[13]), "+f"(d[14]), "+f"(d[15]),
      "+f"(d[16]), "+f"(d[17]), "+f"(d[18]), "+f"(d[19]), "+f"(d[20]), "+f"(d[21]), "+f"(d[22]), "+f"(d[23]), "+f"(d[24]), "+f"(d[25]), "+f"(d[26]), "+f"(d[27]), "+f"(d[28]), "+f"(d[29]), "+f"(d[30]), "+f"(d[31]),
      "+f"(d[32]), "+f"(d[33]), "+f"(d[34]), "+f"(d[35]), "+f"(d[36]), "+f"(d[37]), "+f"(d[38]), "+f"(d[39]), "+f"(d[40]), "+f"(d[41]), "+f"(d[42]), "+f"(d[43]), "+f"(d[44]), "+f"(d[45]), "+f"(d[46]), "+f"(d[47]),
      "+f"(d[48]), "+f"(d[49]), "+f"(d[50]), "+f"(d[51]), "+f"(d[52]), "+f"(d[53]), "+f"(d[54]), "+f"(d[55]), "+f"(d[56]), "+f"(d[57]), "+f"(d[58]), "+f"(d[59]), "+f"(d[60]), "+f"(d[61]), "+f"(d[62]), "+f"(d[63])
    : "r"(a[0]), "r"(a[1]), "r"(a[2]), "r"(a[3]), "r"(blo), "r"(accumulate));
}
__device__ __forceinline__ void wg_pv_acc(float (&d)[64], const uint32_t* a, uint32_t blo) {
  asm volatile("{\n.reg .pred p;\n.reg .b64 da, db;\nmov.b64 db, {%68, 0x40000040};\nsetp.eq.b32 p, 0, 0;\n"
    "wgmma.mma_async.sync.aligned.m64n128k16.f32.bf16.bf16 {"
    "%0, %1, %2, %3, %4, %5, %6, %7, %8, %9, %10, %11, %12, %13, %14, %15, %16, %17, %18, %19, %20, %21, %22, %23, %24, %25, %26, %27, %28, %29, %30, %31, "
    "%32, %33, %34, %35, %36, %37, %38, %39, %40, %41, %42, %43, %44, %45, %46, %47, %48, %49, %50, %51, %52, %53, %54, %55, %56, %57, %58, %59, %60, %61, %62, %63}, "
    "{%64, %65, %66, %67}, db, p, 1, 1, 1;\n}\n"
    : "+f"(d[0]), "+f"(d[1]), "+f"(d[2]), "+f"(d[3]), "+f"(d[4]), "+f"(d[5]), "+f"(d[6]), "+f"(d[7]), "+f"(d[8]), "+f"(d[9]), "+f"(d[10]), "+f"(d[11]), "+f"(d[12]), "+f"(d[13]), "+f"(d[14]), "+f"(d[15]),
      "+f"(d[16]), "+f"(d[17]), "+f"(d[18]), "+f"(d[19]), "+f"(d[20]), "+f"(d[21]), "+f"(d[22]), "+f"(d[23]), "+f"(d[24]), "+f"(d[25]), "+f"(d[26]), "+f"(d[27]), "+f"(d[28]), "+f"(d[29]), "+f"(d[30]), "+f"(d[31]),
      "+f"(d[32]), "+f"(d[33]), "+f"(d[34]), "+f"(d[35]), "+f"(d[36]), "+f"(d[37]), "+f"(d[38]), "+f"(d[39]), "+f"(d[40]), "+f"(d[41]), "+f"(d[42]), "+f"(d[43]), "+f"(d[44]), "+f"(d[45]), "+f"(d[46]), "+f"(d[47]),
      "+f"(d[48]), "+f"(d[49]), "+f"(d[50]), "+f"(d[51]), "+f"(d[52]), "+f"(d[53]), "+f"(d[54]), "+f"(d[55]), "+f"(d[56]), "+f"(d[57]), "+f"(d[58]), "+f"(d[59]), "+f"(d[60]), "+f"(d[61]), "+f"(d[62]), "+f"(d[63])
    : "r"(a[0]), "r"(a[1]), "r"(a[2]), "r"(a[3]), "r"(blo));
}

struct Cons {
  uint32_t sb;
  uint32_t rel;
  uint32_t p0, p1;
  uint32_t lead, round, fpar;
};

template <uint32_t OFF, uint32_t GROUP> __device__ __forceinline__ void tile_write(const uint32_t (&pk)[32], uint32_t base) {
  const uint32_t lane = threadIdx.x & 31, wq = (threadIdx.x >> 5) & 3;
  const uint32_t a = base + (wq * 16 + (lane & 15)) * 128 + (((lane >> 4) ^ (lane & 7)) << 4);
#define TW(j) stmatrix_x4<OFF + (j >> 2) * GROUP>(a ^ ((j & 3) * 32), pk[4 * j + 0], pk[4 * j + 1], pk[4 * j + 2], pk[4 * j + 3])
  TW(0); TW(1); TW(2); TW(3); TW(4); TW(5); TW(6); TW(7);
#undef TW
}
__device__ __forceinline__ void stage_write(const uint32_t (&pk)[32], int w, const Cons& cs) {
  mbar_wait<BAR(B_STGE)>(cs.sb + w * 8, (cs.round & 1) ^ 1);
  tile_write<OFF_STG, 8192>(pk, cs.sb + w * 16384);
}
__device__ __forceinline__ void stage_publish(int w, Cons& cs) {
  fence_async_smem();
  __syncwarp();
  mbar_arrive_if<BAR(B_STGF)>(cs.sb + w * 8, (threadIdx.x & 31) == 0);
  cs.round++;
}

template <int ST, bool INIT, int NA> __device__ __forceinline__ void g_issue(float (&acc)[NA], uint32_t wa) {
  constexpr uint32_t A = dlo(OFF_A + ST * 16384, 16), B = dlo(OFF_B + ST * 32768, NA == 128 ? 8192 : 4096);
  wg_fence();
  if (INIT) wg_gemm_init(acc, A + wa, B); else wg_gemm_acc(acc, A + wa, B);
#pragma unroll
  for (int kk = 1; kk < 4; kk++) wg_gemm_acc(acc, A + wa + kk * 2, B + (NA == 128 ? kk * 128 : (kk >> 1) * 768 + (kk & 1) * 128));
  wg_commit();
}
template <int NA>
__device__ __forceinline__ uint32_t gemm_tile(float (&acc)[NA], int nk4, int idx, int w, Cons& cs, uint32_t pend, const uint32_t (&pkA)[32], const uint32_t (&pkB)[32]) {
  const uint32_t wa = w * 512, sb = cs.sb, rel = cs.rel;
  constexpr int SA = NA == 128 ? STGA : STGAL, SBB = NA == 128 ? STGB : STGBL;
#define HOOK(n) \
  if (n == SA && (pend & 1)) stage_write(pkA, w, cs); \
  if (n == SA + PUBD && (pend & 1)) { stage_publish(w, cs); pend &= 6; } \
  if (n == SBB && (pend & 2)) { stage_write(pkB, w, cs); pend = 4; } \
  if (n == SBB + PUBD && (pend & 4)) { stage_publish(w, cs); pend = 0; }
  T4G(0);
  mbar_wait<BAR(B_FULL + 0)>(sb, cs.p0);
  T4G(1);
  g_issue<0, true>(acc, wa);
  T4G(2);
  HOOK(0);
  mbar_wait<BAR(B_FULL + 1)>(sb, cs.p1);
  g_issue<1, false>(acc, wa);
  T4G(3);
  HOOK(2);
  T4G(4);
  wg_wait<1>();
  T4G(5);
  mbar_arrive_cl<BAR(B_EMPTY + 0)>(rel);
  HOOK(3);
  mbar_wait<BAR(B_FULL + 2)>(sb, cs.p0);
  T4G(6);
  g_issue<2, false>(acc, wa);
  HOOK(4);
  wg_wait<1>();
  T4G(7);
  mbar_arrive_cl<BAR(B_EMPTY + 1)>(rel);
  HOOK(5);
  mbar_wait<BAR(B_FULL + 3)>(sb, cs.p1);
  T4G(8);
  g_issue<3, false>(acc, wa);
  T4G(9);
  HOOK(6);
  T4G(10);
  const uint32_t ncode = item(sb, idx + 1);
  wg_wait<1>();
  T4G(11);
  mbar_arrive_cl<BAR(B_EMPTY + 2)>(rel);
  HOOK(7);
  cs.p0 ^= 1; cs.p1 ^= 1;
  const bool final_tile = (ncode >> 9) == K_END;
  constexpr int LD = NA == 128 ? LEADN : LEADL;
#pragma unroll 1
  for (int q = 1; q < nk4; q++) {
    const bool tail = q == nk4 - 1;
    mbar_wait<BAR(B_FULL + 0)>(sb, cs.p0);
    g_issue<0, false>(acc, wa);
    HOOK(8);
    wg_wait<1>();
    mbar_arrive_cl<BAR(B_EMPTY + 3)>(rel);
    HOOK(9);
    mbar_wait<BAR(B_FULL + 1)>(sb, cs.p1);
    g_issue<1, false>(acc, wa);
    HOOK(10);
    wg_wait<1>();
    mbar_arrive_cl<BAR(B_EMPTY + 0)>(rel);
    HOOK(11);
    mbar_wait<BAR(B_FULL + 2)>(sb, cs.p0);
    if ((LD == 2 || (NA == 128 && final_tile)) && tail && w == 1) mbar_wait<BAR(B_LEAD)>(sb, cs.lead);
    g_issue<2, false>(acc, wa);
    HOOK(12);
    wg_wait<1>();
    mbar_arrive_cl<BAR(B_EMPTY + 1)>(rel);
    HOOK(13);
    mbar_wait<BAR(B_FULL + 3)>(sb, cs.p1);
    if (LD == 1 && tail && w == 1) mbar_wait<BAR(B_LEAD)>(sb, cs.lead);
    g_issue<3, false>(acc, wa);
    mbar_arrive_if<BAR(B_LEAD)>(sb, tail && threadIdx.x == 128);
    HOOK(14);
    wg_wait<1>();
    mbar_arrive_cl<BAR(B_EMPTY + 2)>(rel);
    cs.p0 ^= 1; cs.p1 ^= 1;
  }
#undef HOOK
  cs.lead ^= 1;
  T4G(12);
  wg_wait<0>();
  fence_regs(acc);
  T4GD(13, __float_as_uint(acc[0]));
  mbar_arrive_cl<BAR(B_EMPTY + 3)>(rel);
  return ncode;
}

__device__ __forceinline__ void local_probs(bool first, const float (&S)[3][4], uint32_t (&pb)[4]) {
  const int lane = threadIdx.x & 31, g = lane >> 2, t = lane & 3;
  const bool c0 = 2 * t > g, c1 = 2 * t + 1 > g;
  float x0 = c0 ? S[0][0] : S[1][0], x1 = c1 ? S[0][1] : S[1][1], y0 = c0 ? S[1][2] : S[2][2], y1 = c1 ? S[1][3] : S[2][3];
  if (first && c0) x0 = -INFINITY;
  if (first && c1) x1 = -INFINITY;
  float m0 = fmaxf(x0, x1), m1 = fmaxf(y0, y1);
  m0 = fmaxf(m0, __shfl_xor_sync(0xffffffffu, m0, 1)); m1 = fmaxf(m1, __shfl_xor_sync(0xffffffffu, m1, 1));
  m0 = fmaxf(m0, __shfl_xor_sync(0xffffffffu, m0, 2)); m1 = fmaxf(m1, __shfl_xor_sync(0xffffffffu, m1, 2));
  constexpr float C = 0.17677669529663687f * 1.4426950408889634f;
  const float b0 = -m0 * C, b1 = -m1 * C;
  x0 = ex2(fmaf(x0, C, b0)); x1 = ex2(fmaf(x1, C, b0)); y0 = ex2(fmaf(y0, C, b1)); y1 = ex2(fmaf(y1, C, b1));
  const float l0 = rcp(quad_sum(x0 + x1)), l1 = rcp(quad_sum(y0 + y1));
  const uint32_t px = pack_bf16(x0 * l0, x1 * l0), py = pack_bf16(y0 * l1, y1 * l1);
  const uint32_t m = (c0 ? 0xffffu : 0u) | (c1 ? 0xffff0000u : 0u);
  pb[0] = px & m; pb[1] = px & ~m; pb[2] = py & m; pb[3] = py & ~m;
}
__device__ __forceinline__ void local_epilogue(const float (&acc)[96], uint32_t code, int w, Cons& cs) {
  const uint32_t lane = threadIdx.x & 31, wq = (threadIdx.x >> 5) & 3, cw = w * 4 + wq;
  const bool has_halo = (code & 15) != 0;
  const uint32_t hpar = cs.fpar >> 1;
  cs.fpar ^= has_halo ? 2 : 0;
  uint32_t kf[3][8], vt[3][8];
#pragma unroll
  for (int j = 0; j < 8; j++) { kf[2][j] = pack_bf16(acc[32 + 4 * j + 2], acc[32 + 4 * j + 3]); vt[2][j] = transpose8(pack_bf16(acc[64 + 4 * j + 2], acc[64 + 4 * j + 3])); }
  const uint32_t xa = cs.sb + OFF_STG + 8192 + w * 16384 + wq * 2048 + lane * 16;
  mbar_wait<BAR(B_STGE)>(cs.sb + w * 8, (cs.round & 1) ^ 1);
  sts128<0>(xa, &kf[2][0]); sts128<512>(xa, &kf[2][4]); sts128<1024>(xa, &vt[2][0]); sts128<1536>(xa, &vt[2][4]);
  if (cw == 3) bar_arrive(4, 160);
  uint32_t q[8][2];
#pragma unroll
  for (int j = 0; j < 8; j++) {
    q[j][0] = pack_bf16(acc[4 * j], acc[4 * j + 1]); q[j][1] = pack_bf16(acc[4 * j + 2], acc[4 * j + 3]);
    kf[1][j] = pack_bf16(acc[32 + 4 * j], acc[32 + 4 * j + 1]); vt[1][j] = transpose8(pack_bf16(acc[64 + 4 * j], acc[64 + 4 * j + 1]));
  }
  bar_sync(3 + w, 128 + 32 * w);
  uint32_t ra = xa - (wq == 0 ? 16384 - 3 * 2048 : 2048);
  if (cw == 0) {
    ra = has_halo ? cs.sb + OFF_HALO + lane * 16 : xa;
    if (has_halo) mbar_wait<BAR(B_HFULL)>(cs.sb, hpar);
  }
  lds128<0>(&kf[0][0], ra); lds128<512>(&kf[0][4], ra); lds128<1024>(&vt[0][0], ra); lds128<1536>(&vt[0][4], ra);
  float z;
  asm volatile("ld.shared.f32 %0, [%1+%2];" : "=f"(z) : "r"(cs.sb), "n"(OFF_FILLS + 4) : "memory");
  float S[2][3][4];
#pragma unroll
  for (int u = 0; u < 2; u++)
#pragma unroll
    for (int n = 0; n < 3; n++) mma16816z(S[u][n], q[4 * u][0], q[4 * u][1], q[4 * u + 1][0], q[4 * u + 1][1], kf[n][4 * u], kf[n][4 * u + 1], z);
#pragma unroll
  for (int u = 0; u < 2; u++)
#pragma unroll
    for (int n = 0; n < 3; n++) mma16816(S[u][n], q[4 * u + 2][0], q[4 * u + 2][1], q[4 * u + 3][0], q[4 * u + 3][1], kf[n][4 * u + 2], kf[n][4 * u + 3]);
  uint32_t pb[2][4];
#pragma unroll
  for (int u = 0; u < 2; u++) local_probs(cw == 0 && !has_halo, S[u], pb[u]);
  const uint32_t oa = cs.sb + w * 16384 + (wq * 16 + (lane & 7)) * 128 + (((lane >> 3) ^ (lane & 7)) << 4);
#pragma unroll
  for (int u = 0; u < 2; u++)
#pragma unroll
    for (int hf = 0; hf < 2; hf++) {
      float O[2][4];
#pragma unroll
      for (int mt = 0; mt < 2; mt++) {
        O[mt][0] = O[mt][1] = O[mt][2] = O[mt][3] = 0.f;
        mma16816(O[mt], vt[hf][4 * u + 2 * mt], vt[hf][4 * u + 2 * mt + 1], vt[hf + 1][4 * u + 2 * mt], vt[hf + 1][4 * u + 2 * mt + 1], pb[u][2 * hf], pb[u][2 * hf + 1]);
      }
      const uint32_t o0 = pack_bf16(O[0][0], O[0][1]), o1 = pack_bf16(O[0][2], O[0][3]), o2 = pack_bf16(O[1][0], O[1][1]), o3 = pack_bf16(O[1][2], O[1][3]);
      if (hf == 0) stmatrix_x4_trans<OFF_STG>(oa ^ (u * 64), o0, o1, o2, o3); else stmatrix_x4_trans<OFF_STG + 1024>(oa ^ (u * 64), o0, o1, o2, o3);
    }
  mbar_arrive_if<BAR(B_HEMPTY)>(cs.sb, has_halo && threadIdx.x == 128);
  stage_publish(w, cs);
}

constexpr float SCALE_LOG2 = 0.08838834764831845f * 1.4426950408889634f;
#define SUM_LO 8.673617379884035e-19f
#define SUM_HI 1152921504606846976.f
template <int J0> __device__ __forceinline__ void causal_mask(float (&S)[64], int r) {
#pragma unroll
  for (int j = 0; j < 8; j++) {
    if (8 * j > r) S[4 * (J0 + j) + 0] = -INFINITY;
    if (8 * j + 1 > r) S[4 * (J0 + j) + 1] = -INFINITY;
    if (8 * j - 8 > r) S[4 * (J0 + j) + 2] = -INFINITY;
    if (8 * j - 7 > r) S[4 * (J0 + j) + 3] = -INFINITY;
  }
}
__device__ __forceinline__ float v_ex2(float x) { float y; asm volatile("ex2.approx.ftz.f32 %0, %1;" : "=f"(y) : "f"(x)); return y; }
__device__ __forceinline__ float v_add(float a, float b) { float y; asm volatile("add.f32 %0, %1, %2;" : "=f"(y) : "f"(a), "f"(b)); return y; }
__device__ __forceinline__ float v_mul(float a, float b) { float y; asm volatile("mul.f32 %0, %1, %2;" : "=f"(y) : "f"(a), "f"(b)); return y; }
__device__ __forceinline__ uint32_t v_pack(float lo, float hi) { uint32_t r; asm volatile("cvt.rn.bf16x2.f32 %0, %1, %2;" : "=r"(r) : "f"(hi), "f"(lo)); return r; }
template <int MJ> __device__ __forceinline__ float exp_el(float x, int j, int e, int r) {
  float p = v_ex2(x);
  if (j >= MJ) asm volatile("{\n.reg .pred q;\nsetp.lt.s32 q, %1, %2;\n@q mov.b32 %0, 0f00000000;\n}\n" : "+f"(p) : "r"(r), "r"(8 * (j - MJ) + (e & 1) - 4 * (e & 2)));
  return p;
}
template <int J0, int J1, int MJ = 16> __device__ __forceinline__ void exp_inplace(float (&S)[64], float& l0, float& l1, int r = 0) {
#pragma unroll
  for (int j = J0; j < J1; j++) {
#pragma unroll
    for (int e = 0; e < 4; e++) S[4 * j + e] = exp_el<MJ>(S[4 * j + e], j, e, r);
    l0 = v_add(l0, S[4 * j + 0]); l1 = v_add(l1, S[4 * j + 2]); l0 = v_add(l0, S[4 * j + 1]); l1 = v_add(l1, S[4 * j + 3]);
  }
}
template <int JS, int MJ, bool OUT>
__device__ __forceinline__ void exp_pack(float (&S)[64], uint32_t (&P)[32], float& l0, float& l1, int r, const float (&O)[64], float a0, float a1, uint32_t (&pk)[32]) {
#pragma unroll
  for (int j = JS; j < 16; j++) {
    const float p0 = exp_el<MJ>(S[4 * j + 0], j, 0, r), p1 = exp_el<MJ>(S[4 * j + 1], j, 1, r), p2 = exp_el<MJ>(S[4 * j + 2], j, 2, r), p3 = exp_el<MJ>(S[4 * j + 3], j, 3, r);
#pragma unroll
    for (int k = (j - JS) * JS / (16 - JS); k < (j + 1 - JS) * JS / (16 - JS); k++) { P[2 * k] = v_pack(S[4 * k + 0], S[4 * k + 1]); P[2 * k + 1] = v_pack(S[4 * k + 2], S[4 * k + 3]); }
    if (OUT) {
#pragma unroll
      for (int k = (j - JS) * 16 / (16 - JS); k < (j + 1 - JS) * 16 / (16 - JS); k++) {
        pk[2 * k] = v_pack(v_mul(O[4 * k + 0], a0), v_mul(O[4 * k + 1], a0)); pk[2 * k + 1] = v_pack(v_mul(O[4 * k + 2], a1), v_mul(O[4 * k + 3], a1));
      }
    }
    l0 = v_add(l0, p0); l1 = v_add(l1, p2); l0 = v_add(l0, p1); l1 = v_add(l1, p3);
    P[2 * j] = v_pack(p0, p1); P[2 * j + 1] = v_pack(p2, p3);
  }
}
__device__ __forceinline__ void pin_after(float a, float b) {
  asm volatile("{\n.reg .pred p;\nsetp.eq.u32 p, %0, 0xffffffff;\n@p st.shared.b32 [%1], %1;\n}\n" ::"r"(__float_as_uint(a)), "r"(__float_as_uint(b)) : "memory");
}
template <bool HALF> __device__ __forceinline__ void issue_qk(float (&S)[64], uint32_t qlo, uint32_t klo) {
  wg_fence();
  if (HALF) wg_qk64_init(S, qlo, klo); else wg_qk_init(S, qlo, klo);
#pragma unroll
  for (int kk = 1; kk < 8; kk++) {
    const uint32_t off = ((kk >> 2) * 16384 + (kk & 3) * 32) >> 4;
    if (HALF) wg_qk64_acc(S, qlo + off, klo + off); else wg_qk_acc(S, qlo + off, klo + off);
  }
  wg_commit();
}
template <int NK> __device__ __forceinline__ void issue_pv(float (&O)[64], const uint32_t (&P)[32], uint32_t vlo, uint32_t accumulate) {
  wg_fence();
  wg_pv_sel(O, &P[0], vlo, accumulate);
#pragma unroll
  for (int kk = 1; kk < NK; kk++) wg_pv_acc(O, &P[4 * kk], vlo + kk * 128);
  wg_commit();
}
__device__ __forceinline__ uint32_t row_norm(float l0, float l1, float& a0, float& a1) {
  const float q0 = quad_sum(l0), q1 = quad_sum(l1);
  a0 = rcp(q0); a1 = rcp(q1);
  return __reduce_or_sync(0xffffffffu, (q0 >= SUM_LO && q0 <= SUM_HI && q1 >= SUM_LO && q1 <= SUM_HI) ? 0u : 1u);
}
__device__ __forceinline__ void slow_item(float (&O)[64], float& a0, float& a1, int head, int tile, uint32_t qbase, int w) {
  const int lane = threadIdx.x & 31, g = lane >> 2, t = lane & 3;
  const int rw = w * 64 + (int)__reduce_or_sync(0xffffffffu, (threadIdx.x >> 1) & 48);
  const int row0 = tile * 128 + rw;
  const uint32_t qa_ = qbase + (rw + g) * 128 + ((t ^ g) << 4);
  const __nv_bfloat16* kp = g_kv + ((size_t)head * SEQ + g) * 256 + 8 * t;
  const __nv_bfloat16* vp = g_kv + ((size_t)head * SEQ + 2 * t) * 256 + 128 + g;
  float m0 = -INFINITY, m1 = -INFINITY, l0 = 0.f, l1 = 0.f;
#pragma unroll
  for (int i = 0; i < 64; i++) O[i] = 0.f;
#pragma unroll 1
  for (int key0 = 0; key0 < row0 + 16; key0 += 16) {
    float c[2][4] = {{0.f, 0.f, 0.f, 0.f}, {0.f, 0.f, 0.f, 0.f}};
#pragma unroll 1
    for (int cc = 0; cc < 4; cc++) {
      uint32_t qa[4], qb[4];
      const uint32_t a = (qa_ ^ ((cc & 1) * 64)) + (cc >> 1) * 16384;
      lds128<0>(qa, a); lds128<1024>(qb, a);
#pragma unroll
      for (int n = 0; n < 2; n++) {
        const uint4 kf = ldg128(kp + (size_t)(key0 + 8 * n) * 256 + cc * 32);
        mma16816(c[n], qa[0], qb[0], qa[1], qb[1], kf.x, kf.y);
        mma16816(c[n], qa[2], qb[2], qa[3], qb[3], kf.z, kf.w);
      }
    }
#pragma unroll
    for (int n = 0; n < 2; n++)
#pragma unroll
      for (int e = 0; e < 4; e++)
        if (key0 + 8 * n + 2 * t + (e & 1) > row0 + g + (e >> 1) * 8) c[n][e] = -INFINITY;
    float x0 = fmaxf(fmaxf(c[0][0], c[0][1]), fmaxf(c[1][0], c[1][1])), x1 = fmaxf(fmaxf(c[0][2], c[0][3]), fmaxf(c[1][2], c[1][3]));
    x0 = fmaxf(x0, __shfl_xor_sync(0xffffffffu, x0, 1)); x1 = fmaxf(x1, __shfl_xor_sync(0xffffffffu, x1, 1));
    x0 = fmaxf(x0, __shfl_xor_sync(0xffffffffu, x0, 2)); x1 = fmaxf(x1, __shfl_xor_sync(0xffffffffu, x1, 2));
    const float n0 = fmaxf(m0, x0), n1 = fmaxf(m1, x1);
    const float r0 = ex2(m0 - n0), r1 = ex2(m1 - n1);
    m0 = n0; m1 = n1;
#pragma unroll
    for (int n = 0; n < 2; n++) { c[n][0] = ex2(c[n][0] - n0); c[n][1] = ex2(c[n][1] - n0); c[n][2] = ex2(c[n][2] - n1); c[n][3] = ex2(c[n][3] - n1); }
    l0 = l0 * r0 + ((c[0][0] + c[0][1]) + (c[1][0] + c[1][1]));
    l1 = l1 * r1 + ((c[0][2] + c[0][3]) + (c[1][2] + c[1][3]));
    const uint32_t p0 = pack_bf16(c[0][0], c[0][1]), p1 = pack_bf16(c[0][2], c[0][3]), p2 = pack_bf16(c[1][0], c[1][1]), p3 = pack_bf16(c[1][2], c[1][3]);
#pragma unroll
    for (int j = 0; j < 16; j++) {
      const __nv_bfloat16* v = vp + (size_t)key0 * 256 + j * 8;
      const uint32_t b0 = ldg16(v) | (ldg16(v + 256) << 16), b1 = ldg16(v + 8 * 256) | (ldg16(v + 9 * 256) << 16);
      float o[4] = {O[4 * j] * r0, O[4 * j + 1] * r0, O[4 * j + 2] * r1, O[4 * j + 3] * r1};
      mma16816(o, p0, p1, p2, p3, b0, b1);
      O[4 * j] = o[0]; O[4 * j + 1] = o[1]; O[4 * j + 2] = o[2]; O[4 * j + 3] = o[3];
    }
  }
  a0 = rcp(quad_sum(l0)); a1 = rcp(quad_sum(l1));
}
__device__ __forceinline__ void att_output(const float (&O)[64], float a0, float a1, uint32_t (&pk)[32]) {
#pragma unroll
  for (int k = 0; k < 16; k++) { pk[2 * k] = v_pack(v_mul(O[4 * k + 0], a0), v_mul(O[4 * k + 1], a0)); pk[2 * k + 1] = v_pack(v_mul(O[4 * k + 2], a1), v_mul(O[4 * k + 3], a1)); }
}
template <int J1> __device__ __forceinline__ void exp_stage(float (&S)[64], float& l0, float& l1, const uint32_t (&P)[32], int w, const Cons& cs) {
  const uint32_t lane = threadIdx.x & 31, wq = (threadIdx.x >> 5) & 3;
  const uint32_t a = cs.sb + w * 16384 + (wq * 16 + (lane & 15)) * 128 + (((lane >> 4) ^ (lane & 7)) << 4);
#define ES(c) \
  exp_inplace<c * J1 / 8, (c + 1) * J1 / 8>(S, l0, l1); \
  stmatrix_x4_after<OFF_STG + (c >> 2) * 8192>(a ^ ((c & 3) * 32), P[4 * c + 0], P[4 * c + 1], P[4 * c + 2], P[4 * c + 3], (c & 1) ? l1 : l0)
  ES(0); ES(1); ES(2); ES(3); ES(4); ES(5); ES(6); ES(7);
#undef ES
}
__device__ __forceinline__ void attention(uint32_t code, uint32_t rank, int idx, int w, Cons& cs, uint32_t (&P)[32], uint32_t (&pk)[32]) {
  const int lane = threadIdx.x & 31, wq = (threadIdx.x >> 5) & 3;
  constexpr int JS = JSPLIT, JE = JEDGE, JD = JDIAG;
  constexpr uint32_t SLOT = 32768 >> 4;
  const uint32_t sb = cs.sb;
  const int y = (code & 15) * 2 + rank;
  const int r = wq * 16 + (lane >> 2) - 2 * (lane & 3);
  float O[64], S[64];
  float l0 = 0.f, l1 = 0.f, a0 = 0.f, a1 = 0.f;
  uint32_t qd = dlo(OFF_A, 16) + w * 512;
  uint32_t kd = dlo(OFF_B, 16), vd = dlo(OFF_B + 98304, 16384);
  uint32_t c8 = 0, cb = sb;
  uint32_t xc = cs.p0, xp = cs.p1;
  uint32_t next = y ? 1 : 2, half = 0, accum = 0, pub = 1;
  uint32_t unsafe = 0, late;
  int ns = y - 1;
  auto look_ahead = [&]() {
    const uint32_t k_ready = mbar_test<BAR(B_FULL)>(cb, xc), q_ready = mbar_test<BAR(B_QFULL)>(sb, cs.fpar & 1);
    late = __reduce_or_sync(0xffffffffu, (k_ready | (q_ready << 1)) ^ 3) & (next == 2 ? 3 : 1);
  };
  {
    T4A(0, 0);
    bar_sync(3 - w, 128 + 128 * w);
    issue_qk<false>(S, qd, dlo(OFF_B + 32768, 16));
    bar_arrive(1 + (w ^ 1), 256);
    T4A(3, 0);
    wg_wait<0>();
    fence_regs(S);
    T4A(4, __float_as_uint(S[0]));
    mbar_arrive_cl<BAR(B_EMPTY + 1)>(cs.rel);
    if (y == 0) { causal_mask<0>(S, r + 64 * w); causal_mask<8>(S, r + 64 * w - 64); qd += SLOT; }
    exp_stage<JP>(S, l0, l1, pk, w, cs);
    T4A(5, __float_as_uint(l0));
    look_ahead();
#pragma unroll
    for (int i = 0; i < 64; i++) O[i] = 0.f;
    exp_pack<JP, 16, false>(S, P, l0, l1, r, O, a0, a1, pk);
    T4A(7, __float_as_uint(l0));
  }
  while (true) {
    if (late) {
      if (next == 2) {
        if (pub) { stage_publish(w, cs); pub = 0; }
        mbar_wait<BAR(B_QFULL)>(sb, cs.fpar & 1);
      }
      if (ns > 0 || next != 4) mbar_wait<BAR(B_FULL)>(cb, xc);
    }
    if (ns > 0) {
      while (true) {
        T4S(0, 0);
        bar_sync(1 + w, 256);
        issue_qk<false>(S, qd, kd);
        T4S(2, 0);
        if (pub) { stage_publish(w, cs); pub = 0; }
        mbar_wait<BAR(B_FULL + 2)>(cb ^ 8, xp);
        issue_pv<8>(O, P, vd, accum);
        bar_arrive(1 + (w ^ 1), 256);
        T4S(3, 0);
        ns--; accum = 1;
        kd ^= SLOT; vd ^= SLOT; c8 ^= 8; cb ^= 8;
        { const uint32_t t = xc; xc = xp ^ 1; xp = t; }
        wg_wait<1>();
        fence_regs(S);
        T4S(4, __float_as_uint(S[0]));
        mbar_arrive_cl<BAR(B_EMPTY)>(cs.rel, c8 ^ 8);
        exp_inplace<0, JS>(S, l0, l1);
        pin_after(l0, l1);
        T4S(5, __float_as_uint(l0));
        wg_wait<0>();
        fence_regs(O);
        fence_regs(P);
        mbar_arrive_cl<BAR(B_EMPTY + 2)>(cs.rel, c8);
        const bool k_ready = mbar_test<BAR(B_FULL)>(cb, xc);
        exp_pack<JS, 16, false>(S, P, l0, l1, 0, O, 0.f, 0.f, pk);
        const uint32_t lt = __reduce_or_sync(0xffffffffu, k_ready ? 0u : 1u);
        T4S(7, __float_as_uint(l0));
        if (lt != 0 || ns == 0) {
          if (lt != 0 && (ns != 0 || next != 4)) mbar_wait<BAR(B_FULL)>(cb, xc);
          if (ns == 0) break;
        }
      }
    }
    const uint32_t phase = next;
    auto advance = [&]() {
      accum = phase & 1;
      kd ^= SLOT; vd ^= SLOT; c8 ^= 8; cb ^= 8;
      { const uint32_t t = xc; xc = xp ^ 1; xp = t; }
      next = phase + 1 + (2 * y == phase);
      if (next == 2) qd += SLOT;
    };
    auto sums = [&]() {
      unsafe = row_norm(l0, l1, a0, a1);
      mbar_arrive_if<BAR(B_QEMPTY)>(sb, lane == 0 && !unsafe);
      l0 = l1 = 0.f;
    };
    if (phase == 2) { TRW(idx, 4); }
    T4A(0, 0);
    bar_sync(1 + w, 256);
    if (phase < 3) {
      if (w == 1) {
        issue_qk<false>(S, qd, kd);
        T4A(2, 0);
        if (pub) { stage_publish(w, cs); pub = 0; }
        if (phase == 2) sums();
        mbar_wait<BAR(B_FULL + 2)>(cb ^ 8, xp);
        issue_pv<8>(O, P, vd, accum);
        bar_arrive(1, 256);
        T4A(3, 0);
        advance();
        wg_wait<1>();
        fence_regs(S);
        T4A(4, __float_as_uint(S[0]));
        mbar_arrive_cl<BAR(B_EMPTY)>(cs.rel, c8 ^ 8);
        exp_inplace<0, JD, 8>(S, l0, l1, r);
        pin_after(l0, l1);
        T4A(5, __float_as_uint(l0));
        wg_wait<0>();
        fence_regs(O);
        fence_regs(P);
        mbar_arrive_cl<BAR(B_EMPTY + 2)>(cs.rel, c8);
        if (phase == 2) { look_ahead(); exp_pack<JD, 8, true>(S, P, l0, l1, r, O, a0, a1, pk); }
        else { look_ahead(); exp_pack<JD, 8, false>(S, P, l0, l1, r, O, a0, a1, pk); }
      } else {
        issue_qk<true>(S, qd, kd);
        T4A(2, 0);
        mbar_wait<BAR(B_FULL + 2)>(cb ^ 8, xp);
        if (half) issue_pv<4>(O, P, vd, accum); else issue_pv<8>(O, P, vd, accum);
        bar_arrive(2, 256);
        T4A(3, 0);
        if (pub) { stage_publish(w, cs); pub = 0; }
        advance();
        half = 1;
        wg_wait<1>();
        fence_regs<0, 32>(S);
        T4A(4, __float_as_uint(S[0]));
        mbar_arrive_cl<BAR(B_EMPTY)>(cs.rel, c8 ^ 8);
        if (phase == 2) sums();
        exp_inplace<0, 8, 0>(S, l0, l1, r);
        pin_after(l0, l1);
        T4A(5, __float_as_uint(l0));
        wg_wait<0>();
        fence_regs(O);
        fence_regs(P);
        mbar_arrive_cl<BAR(B_EMPTY + 2)>(cs.rel, c8);
        look_ahead();
#pragma unroll
        for (int k = 0; k < 8; k++) { P[2 * k] = v_pack(S[4 * k + 0], S[4 * k + 1]); P[2 * k + 1] = v_pack(S[4 * k + 2], S[4 * k + 3]); }
      }
    } else if (phase == 3) {
      issue_qk<false>(S, qd, kd);
      T4A(2, 0);
      mbar_wait<BAR(B_FULL + 2)>(cb ^ 8, xp);
      if (half) issue_pv<4>(O, P, vd, 0); else issue_pv<8>(O, P, vd, 0);
      bar_arrive(1 + (w ^ 1), 256);
      T4A(3, 0);
      advance();
      pub = 1; half = 0;
      ns = (y ^ 1) - 1;
      mbar_wait<BAR(B_STGE)>(sb + w * 8, (cs.round & 1) ^ 1);
      wg_wait<1>();
      fence_regs(S);
      T4A(4, __float_as_uint(S[0]));
      mbar_arrive_cl<BAR(B_EMPTY)>(cs.rel, c8 ^ 8);
      exp_stage<JE>(S, l0, l1, pk, w, cs);
      pin_after(l0, l1);
      T4A(5, __float_as_uint(l0));
      wg_wait<0>();
      fence_regs(O);
      fence_regs(P);
      mbar_arrive_cl<BAR(B_EMPTY + 2)>(cs.rel, c8);
      look_ahead();
      exp_pack<JE, 16, false>(S, P, l0, l1, r, O, a0, a1, pk);
    } else {
      mbar_wait<BAR(B_FULL + 2)>(cb ^ 8, xp);
      if (half) issue_pv<4>(O, P, vd, accum); else issue_pv<8>(O, P, vd, accum);
      if (w == 0) bar_arrive(2, 256);
      T4A(3, 0);
      if (pub) stage_publish(w, cs);
      unsafe = row_norm(l0, l1, a0, a1);
      mbar_arrive_if<BAR(B_QEMPTY + 1)>(sb, lane == 0 && !unsafe);
      wg_wait<0>();
      fence_regs(O);
      fence_regs(P);
      mbar_arrive_cl<BAR(B_EMPTY + 2)>(cs.rel, c8 ^ 8);
    }
    T4A(7, __float_as_uint(l0));
    if (!(phase & 1)) {
      if (UNLIKELY(unsafe)) {
        slow_item(S, a0, a1, ((code >> 4) & 31) * 2 + (phase >> 2), y ^ (phase >> 2), sb + OFF_A + (phase >> 2) * 32768, w);
        __syncwarp();
        mbar_arrive_if<BAR(B_QEMPTY)>(sb + (phase >> 2) * 8, lane == 0);
        att_output(S, a0, a1, pk);
      } else if (phase == 4 || w == 0) {
        att_output(O, a0, a1, pk);
      }
      T4A(8, pk[31] ^ pk[15]);
      if (phase == 4) break;
      if (next == 4) { stage_write(pk, w, cs); pub = 1; }
    }
  }
  cs.p1 = xp ^ 1; cs.p0 = xc;
  cs.fpar ^= 1;
}

struct Src { const CUtensorMap *ma, *mb; int a0, a1, b0, b1, b2; uint32_t hb; };
__device__ __forceinline__ Src gemm_src(const Params& p, uint32_t code, uint32_t rank, uint32_t h) {
  const int kind = code >> 9, x = (code >> 4) & 31, m = code & 15;
  Src s;
  s.ma = &p.maps[M_AX + kind];
  s.mb = &p.maps[(kind == K_KV && h) ? M_WUV : M_WQKV + kind];
  if (kind == K_QL) { s.a0 = rank * 1024; s.a1 = m * 128; s.b0 = x * 64; s.b1 = h * 32; s.b2 = 0; s.hb = 12288; }
  else { s.a0 = 0; s.a1 = (2 * m + rank) * 128; s.b0 = 0; s.b1 = 0; s.b2 = kind == K_KV ? x * 2 : x * 4 + h * 2; s.hb = 16384; }
  return s;
}
__global__ void __cluster_dims__(2, 1, 1) __launch_bounds__(384, 1) mega_kernel(const __grid_constant__ Params p) {
  extern __shared__ __align__(1024) uint8_t smem_raw[];
  const uint32_t sb = smem_u32(smem_raw);
  const uint32_t bid = blockIdx.x, rank = bid & 1;
  const uint32_t code0 = p.sched[bid >> 1][0];
  const uint32_t epoch = g_flags.epoch[bid];
  auto early_load = [&](int s0) {
    const Src u = gemm_src(p, code0, rank, 0), v = gemm_src(p, code0, rank, 1);
#pragma unroll
    for (int i = 0; i < 2; i++) {
      const int s = s0 + i;
      const uint32_t bar = sb + BAR(B_FULL) + s * 8;
      mbar_expect_tx<0>(bar, 16384 + 2 * u.hb);
      tma_load_2d(sb + OFF_A + s * 16384, u.ma, u.a0 + s * 64, u.a1, bar);
      tma_load_3d(sb + OFF_B + s * 32768, u.mb, u.b0, u.b1 + s * 64, u.b2, bar);
      tma_load_3d(sb + OFF_B + s * 32768 + u.hb, v.mb, v.b0, v.b1 + s * 64, v.b2, bar);
    }
  };
#define BI(b) mbar_init<BAR(b)>(sb, bar_count(b))
  if (threadIdx.x == 0) {
    BI(0); BI(1); BI(2); BI(3);
    asm volatile("fence.mbarrier_init.release.cluster;" ::: "memory");
    early_load(0);
  }
  if (threadIdx.x == 32 || threadIdx.x == 64 || threadIdx.x == 96) {
    if (threadIdx.x == 32) { BI(4); BI(5); BI(6); BI(7); BI(8); BI(9); }
    else if (threadIdx.x == 64) { BI(10); BI(11); BI(12); BI(13); BI(14); BI(15); }
    else {
      BI(16); BI(17); BI(18); BI(19); BI(20);
      asm volatile("st.shared.v2.u32 [%0+%2], {%1, %1};" ::"r"(sb), "r"(0), "n"(OFF_FILLS) : "memory");
      if ((sb & 0xffffffu) != SB) __trap();
    }
    asm volatile("fence.mbarrier_init.release.cluster;" ::: "memory");
  }
#undef BI
  static_assert(B_COUNT == 21, "barrier set-up");
  if (threadIdx.x >= 128 && threadIdx.x < 128 + MAX_ITEMS / 4) {
    const int i = threadIdx.x - 128;
    const uint2 v = *reinterpret_cast<const uint2*>(&p.sched[bid >> 1][4 * i]);
    asm volatile("st.shared.v2.u32 [%0+%3], {%1, %2};" ::"r"(sb + i * 8), "r"(v.x), "r"(v.y), "n"(OFF_LIST) : "memory");
  }
  if (threadIdx.x >= 256 && threadIdx.x < 320) asm volatile("st.shared.u32 [%0+%2], %1;" ::"r"(sb + (threadIdx.x - 256) * 4), "r"(0), "n"(OFF_MASK) : "memory");
  bar_sync(0, 384);
  cluster_arrive_relaxed();
  const int wg = __shfl_sync(0xffffffffu, threadIdx.x >> 7, 0);
  if (wg == 0) {
    reg_dealloc<REG_PROD>();
    if (threadIdx.x == 0) early_load(2);
    __syncwarp();
    cluster_wait();
    const int warp = threadIdx.x >> 5;
    const int lane = threadIdx.x & 31;
    auto need = [&](uint32_t& have, int i, int b) {
      if (!((have >> b) & 1)) {
        uint32_t n = 0;
        while (have = lds_acquire<OFF_MASK>(sb + i * 4), !((have >> b) & 1)) { __nanosleep(32); if (++n > (1u << 22)) __trap(); }
        fence_async_glob();
      }
    };
    if (warp == 0) {
      uint32_t e0 = 0, e1 = 0;
      uint32_t qe = 0, after_att = 0, fills = 0;
      for (int idx = 0;; idx++) {
        const uint32_t code = item(sb, idx);
        const int kind = code >> 9, x = (code >> 4) & 31, m = code & 15, y = 2 * m + rank;
        if (kind == K_END) break;
        {
          const Src u = gemm_src(p, code, rank, rank);
          const int nk = kind == K_KV ? 8 : kind == K_OB ? 64 : 16;
          uint32_t have = kind >= K_OA ? 0u : 0xffffffffu;
#pragma unroll 1
          for (int k = idx == 0 ? 4 : 0; k < nk; k++) {
            const uint32_t s = k & 3;
            need(have, (kind == K_OA ? F_QL : F_CTX) + y, kind == K_OA ? k : k >> 1);
            mbar_wait<BAR(B_EMPTY)>(sb + s * 8, (s & 1) ? e1 : e0);
            if (after_att && !(k & 1)) {
              mbar_wait<BAR(B_QEMPTY)>(sb + k * 4, qe);
              if (k == 2) { after_att = 0; qe ^= 1; }
            }
            if (lane == 0) {
              const uint32_t bar = sb + BAR(B_FULL) + s * 8;
              mbar_expect_tx<0>(bar, 16384 + 2 * u.hb);
              tma_load_3d_mc(sb + OFF_B + s * 32768 + rank * u.hb, u.mb, u.b0, u.b1 + k * 64, u.b2, bar, 3);
              tma_load_2d(sb + OFF_A + s * 16384, u.ma, u.a0 + k * 64, u.a1, bar);
              asm volatile("st.volatile.shared.u32 [%0+%2], %1;" ::"r"(sb), "r"(++fills), "n"(OFF_FILLS) : "memory");
            }
            if (s == 3) { e0 ^= 1; e1 ^= 1; }
          }
        }
        if (kind == K_QF) {
          uint32_t have = 0, xc = e1, xp = e0 ^ 1;
#pragma unroll 1
          for (int j = 0; j < 8 * m + 8; j++) {
            const int i = j >> 1, v = j & 1;
            if (v ? i == 0 : i == 4 * m + 3) continue;
            const int ib = i - v;
            if (i == 2 * m + 1 + rank && !v) have = 0;
            const int h = 2 * x + (ib >= 2 * m + 1 + (int)rank), blk = ib <= 2 * m + 1 ? ib : 4 * m + 2 - ib;
            const int row = h * SEQ + blk * 128;
            if (!v) need(have, F_KV + h, blk);
            const uint32_t b = 2 * v + ((ib + 1) & 1);
            mbar_wait<BAR(B_EMPTY)>(sb + b * 8, v ? xp : xc);
            if (lane == 0) {
              const uint32_t bar = sb + BAR(B_FULL) + b * 8, dst = sb + OFF_B + b * 32768;
              mbar_expect_tx<0>(bar, 32768);
              const bool own = ib == 2 * m + 1;
              tma_load_2d_mc(dst + rank * 16384, &p.maps[M_KV_LD], (2 * v + rank) * 64, row, bar, own ? 1 + rank : 3);
              if (own) tma_load_2d(dst + (rank ^ 1) * 16384, &p.maps[M_KV_LD], (2 * v + (rank ^ 1)) * 64, row, bar);
            }
            if (v || i == 0) { const uint32_t t = xc; xc = xp ^ 1; xp = t; }
          }
          e0 ^= 1;
          after_att = 1;
        }
      }
    } else if (warp == 2) {
      const uint32_t f0 = 0xffffu, f1 = lane < 16 ? 0xffffffffu : 0xffffu, flip = 0u - (epoch & 1);
      uint32_t s0 = 0, s1 = 0, tries = 0;
      while (!__all_sync(0xffffffffu, s0 == f0 && s1 == f1)) {
        const uint32_t v0 = (ld_acquire(&g_flags.m[lane]) ^ flip) & f0, v1 = (ld_acquire(&g_flags.m[32 + lane]) ^ flip) & f1;
        if (v0 != s0) { s0 = v0; sts_release<OFF_MASK>(sb + lane * 4, v0); }
        if (v1 != s1) { s1 = v1; sts_release<OFF_MASK + 128>(sb + lane * 4, v1); }
        __nanosleep(WATCH_NS);
        if (++tries > (1u << 20)) __trap();
      }
    } else if (warp == 3) {
      uint32_t hp = 1;
      for (int idx = 0;; idx++) {
        const uint32_t code = item(sb, idx);
        const int kind = code >> 9, x = (code >> 4) & 31, y = 2 * (code & 15) + rank;
        if (kind == K_END) break;
        if (kind != K_QL || y < 2) continue;
        uint32_t n = 0;
        while (!mbar_test<BAR(B_HEMPTY)>(sb, hp)) { __nanosleep(500); if (++n > (1u << 20)) __trap(); }
        hp ^= 1;
        n = 0;
        while (!((lds_acquire<OFF_MASK>(sb + (F_QL + y - 2) * 4) >> x) & 1)) { __nanosleep(100); if (++n > (1u << 22)) __trap(); }
        fence_async_glob();
        if (lane == 0) { mbar_expect_tx<BAR(B_HFULL)>(sb, 2048); bulk_load(sb + OFF_HALO, g_halo + ((y - 2) * 16 + x) * 2048, 2048, sb + BAR(B_HFULL)); }
      }
    } else {
      if (lane == 0) {
        uint32_t round = 0, fpar = 0;
        const uint32_t rb = mapa(sb, rank ^ 1);
        const uint64_t pol_first = policy_evict_first(), pol_normal = policy_evict_normal();
        auto pace = [&]() {
          uint32_t c0, c, t0, t;
          asm volatile("ld.volatile.shared.u32 %0, [%1+%2];" : "=r"(c0) : "r"(sb), "n"(OFF_FILLS) : "memory");
          asm volatile("mov.u32 %0, %clock;" : "=r"(t0));
          do {
            asm volatile("ld.volatile.shared.u32 %0, [%1+%2];" : "=r"(c) : "r"(sb), "n"(OFF_FILLS) : "memory");
            asm volatile("mov.u32 %0, %clock;" : "=r"(t));
          } while (c == c0 && t - t0 < PACE_MAX);
        };
        for (int idx = 0;; idx++) {
          const uint32_t code = item1(sb, idx);
          const int kind = code >> 9, x = (code >> 4) & 31, m = code & 15, y = 2 * m + rank;
          if (kind == K_END) break;
          const bool last = (item1(sb, idx + 1) >> 9) == K_END;
          if (kind == K_QF) {
            mbar_expect_tx<BAR(B_QFULL)>(sb, 32768);
            mbar_wait<BAR(B_QX)>(sb, fpar);
            for (int v = 0; v < 2; v++) {
              mbar_wait<BAR(B_STGF)>(sb + v * 8, round & 1);
              bulk_send(rb + OFF_A + 32768 + v * 8192, sb + OFF_STG + v * 16384, 8192, rb + BAR(B_QFULL));
              bulk_send(rb + OFF_A + 49152 + v * 8192, sb + OFF_STG + v * 16384 + 8192, 8192, rb + BAR(B_QFULL));
            }
            mbar_wait<BAR(B_QFULL)>(sb, fpar);
            mbar_arrive_cl<BAR(B_STGE)>(rb);
            mbar_arrive_cl<BAR(B_STGE + 1)>(rb);
            round++; fpar ^= 1;
          }
          const CUtensorMap* mc = &p.maps[M_OA_ST + kind];
          const uint64_t pol = (((HINTS & 1) && kind >= K_OA) || ((HINTS & 2) && kind == K_QF) || ((HINTS & 4) && kind == K_QL) || ((HINTS & 8) && kind == K_KV)) ? pol_first : pol_normal;
          int row = kind == K_KV ? x * SEQ + y * 128 : kind == K_OA ? m * 128 : y * 128;
          int cg = kind == K_QL ? x : kind == K_QF ? x * 4 : kind == K_KV ? 0 : kind == K_OA ? rank * 32 + x * 4 : 16 + x * 4;
          const int nr = kind == K_QL ? 1 : 2;
#pragma unroll 1
          for (int r = 0; r < nr; r++) {
            mbar_wait<BAR(B_STGF)>(sb, round & 1);
            if (last && kind >= K_KV) {
              tma_store_3d(mc, sb + OFF_STG, 0, row, cg, pol);
              mbar_wait<BAR(B_FIN)>(sb, 0);
              tma_store_3d(mc, sb + OFF_B, 0, row, cg + 2, pol);
              mbar_wait<BAR(B_STGF + 1)>(sb, round & 1);
              tma_store_3d(mc, sb + OFF_STG + 16384, 0, row + 64, cg, pol);
              mbar_wait<BAR(B_FIN + 1)>(sb, 0);
              tma_store_3d(mc, sb + OFF_B + 16384, 0, row + 64, cg + 2, pol);
              bulk_commit();
              r = 1;
            } else {
              const bool paced = !last && (kind != K_QF || r == 1);
              if (paced) pace();
              tma_store_3d(mc, sb + OFF_STG, 0, row, cg, pol);
              bulk_commit();
              mbar_wait<BAR(B_STGF + 1)>(sb, round & 1);
              if (paced) pace();
              tma_store_3d(mc, sb + OFF_STG + 16384, 0, row + 64, cg, pol);
              if (kind == K_QL) bulk_store(g_halo + (y * 16 + x) * 2048, sb + OFF_STG + 16384 + 8192 + 3 * 2048, 2048);
              bulk_commit();
              bulk_wait_read<1>();
              mbar_arrive<BAR(B_STGE)>(sb);
              bulk_wait_read<0>();
              mbar_arrive<BAR(B_STGE + 1)>(sb);
              round++;
            }
            if (kind == K_QF || (kind <= K_KV && r == nr - 1)) {
              bulk_wait_all();
              flag_toggle(&g_flags.m[kind == K_QL ? F_QL + y : kind == K_KV ? F_KV + x : F_CTX + (y ^ r)], 1u << (kind == K_QL ? x : kind == K_KV ? y : 2 * x + r));
              TRC(idx, 12 + r);
            }
            cg += 2;
            if (kind == K_QF) row ^= 128;
          }
        }
        bulk_wait_all();
        g_flags.epoch[bid] = epoch + 1;
      }
      __syncwarp();
      cluster_arrive();
      cluster_wait();
    }
  } else {
    reg_alloc<REG_CONS>();
    cluster_wait();
    const int w = wg - 1;
    Cons cs;
    cs.sb = sb;
    cs.rel = (threadIdx.x & 127) == 0 ? sb : (threadIdx.x & 127) == 1 ? mapa(sb, rank ^ 1) : 0;
    cs.p0 = cs.p1 = cs.lead = cs.round = cs.fpar = 0;
    uint32_t pkA[32], pkB[32], pend = 0;
#pragma unroll
    for (int i = 0; i < 32; i++) pkA[i] = pkB[i] = 0;
    uint32_t code = item(sb, 0);
    int idx = 0;
    do {
      TRW(idx, 0);
      const int kind = code >> 9;
      uint32_t ncode;
      if (kind == K_QL) {
        float acc[96];
        ncode = gemm_tile(acc, 4, idx, w, cs, pend, pkA, pkB);
        TRW(idx, 2);
        local_epilogue(acc, code, w, cs);
        pend = 0;
      } else {
        float acc[128];
        ncode = gemm_tile(acc, kind == K_KV ? 2 : kind == K_OB ? 16 : 4, idx, w, cs, pend, pkA, pkB);
        TRW(idx, 2);
        T4A(11, __float_as_uint(acc[0]));
        if (kind == K_QF) {
          mbar_arrive_cl<BAR(B_QX)>((threadIdx.x & 1) ? cs.rel : 0);
          mbar_wait<BAR(B_STGE)>(sb + w * 8, (cs.round & 1) ^ 1);
          const uint32_t lane = threadIdx.x & 31, wq = (threadIdx.x >> 5) & 3;
          const uint32_t a = sb + w * 8192 + (wq * 16 + (lane & 15)) * 128 + (((lane >> 4) ^ (lane & 7)) << 4);
#define QW(c) \
          pkB[4 * c + 0] = v_pack(acc[8 * c + 0], acc[8 * c + 1]); pkB[4 * c + 1] = v_pack(acc[8 * c + 2], acc[8 * c + 3]); \
          pkB[4 * c + 2] = v_pack(acc[8 * c + 4], acc[8 * c + 5]); pkB[4 * c + 3] = v_pack(acc[8 * c + 6], acc[8 * c + 7]); \
          stmatrix_x4<OFF_A + (c >> 2) * 16384>(a ^ ((c & 3) * 32), pkB[4 * c + 0], pkB[4 * c + 1], pkB[4 * c + 2], pkB[4 * c + 3])
          QW(0); QW(1); QW(2); QW(3); QW(4); QW(5); QW(6); QW(7);
#undef QW
#pragma unroll
          for (int i = 0; i < 32; i++) pkA[i] = v_pack(acc[64 + 2 * i], acc[64 + 2 * i + 1]);
          T4A(12, pkA[31]);
          mbar_wait<BAR(B_FULL + 1)>(sb, cs.p1);
          fence_async_smem();
          T4A(13, 0);
          attention(code, rank, idx, w, cs, pkB, pkA);
          pend = 1;
        } else {
          if (kind == K_KV) {
#pragma unroll
            for (int i = 0; i < 64; i++) acc[i] *= SCALE_LOG2;
          }
#pragma unroll
          for (int i = 0; i < 32; i++) pkA[i] = pack_bf16(acc[2 * i], acc[2 * i + 1]);
#pragma unroll
          for (int i = 0; i < 32; i++) pkB[i] = pack_bf16(acc[64 + 2 * i], acc[64 + 2 * i + 1]);
          T4GD(14, pkB[31] ^ pkA[31] ^ pkA[15] ^ pkB[15]);
          pend = 3;
        }
      }
      code = ncode;
      idx++;
    } while ((code >> 9) != K_END);
    TRW(idx, 0);
    if (pend & 1) { stage_write(pkA, w, cs); stage_publish(w, cs); }
    if (pend & 2) {
      mbar_wait<BAR(B_EMPTY)>(sb, cs.p0 ^ 1);
      tile_write<OFF_B, 8192>(pkB, sb + w * 16384);
      fence_async_smem();
      __syncwarp();
      mbar_arrive_if<BAR(B_FIN)>(sb + w * 8, (threadIdx.x & 31) == 0);
    }
    cluster_arrive();
  }
}

typedef CUresult (*EncodeFn)(CUtensorMap*, CUtensorMapDataType, cuuint32_t, void*, const cuuint64_t*, const cuuint64_t*, const cuuint32_t*,
                             const cuuint32_t*, CUtensorMapInterleave, CUtensorMapSwizzle, CUtensorMapL2promotion, CUtensorMapFloatOOBfill);

void make_map_2d(EncodeFn enc, CUtensorMap* tm, const void* ptr, uint64_t cols, uint64_t rows) {
  cuuint64_t dims[2] = {cols, rows};
  cuuint64_t str[1] = {cols * 2};
  cuuint32_t box[2] = {64, 128};
  cuuint32_t es[2] = {1, 1};
  enc(tm, CU_TENSOR_MAP_DATA_TYPE_BFLOAT16, 2, const_cast<void*>(ptr), dims, str, box, es, CU_TENSOR_MAP_INTERLEAVE_NONE, CU_TENSOR_MAP_SWIZZLE_128B,
      CU_TENSOR_MAP_L2_PROMOTION_L2_256B, CU_TENSOR_MAP_FLOAT_OOB_FILL_NONE);
}
void make_map_3d(EncodeFn enc, CUtensorMap* tm, const void* ptr, uint64_t cols, uint64_t rows, uint64_t part, uint32_t br, uint32_t bg) {
  cuuint64_t dims[3] = {part, rows, cols / part};
  cuuint64_t str[2] = {cols * 2, part * 2};
  cuuint32_t box[3] = {64, br, bg};
  cuuint32_t es[3] = {1, 1, 1};
  enc(tm, CU_TENSOR_MAP_DATA_TYPE_BFLOAT16, 3, const_cast<void*>(ptr), dims, str, box, es, CU_TENSOR_MAP_INTERLEAVE_NONE, CU_TENSOR_MAP_SWIZZLE_128B,
      CU_TENSOR_MAP_L2_PROMOTION_L2_256B, CU_TENSOR_MAP_FLOAT_OOB_FILL_NONE);
}

static const uint16_t h_sched[NPAIR][MAX_ITEMS] = {
  {0,1170,577,1312,1222,1265,1348,1333,1504,1443,1431,1463,1524,2048,3584,3584,3584,3584,3584,3584,3584,3584,3584,3584},
  {1024,514,1248,647,2103,3584,3584,3584,3584,3584,3584,3584,3584,3584,3584,3584,3584,3584,3584,3584,3584,3584,3584,3584},
  {16,1187,1095,598,690,738,1570,3584,3584,3584,3584,3584,3584,3584,3584,3584,3584,3584,3584,3584,3584,3584,3584,3584},
  {1056,518,1330,1381,1426,1414,1509,54,2050,3584,3584,3584,3584,3584,3584,3584,3584,3584,3584,3584,3584,3584,3584,3584},
  {32,1046,597,656,1477,1510,1525,2055,3584,3584,3584,3584,3584,3584,3584,3584,3584,3584,3584,3584,3584,3584,3584,3584},
  {48,544,131,5,1264,1287,1329,693,230,183,1573,3584,3584,3584,3584,3584,3584,3584,3584,3584,3584,3584,3584,3584},
  {64,561,52,165,1347,1319,1351,1505,1444,722,214,119,1571,3584,3584,3584,3584,3584,3584,3584,3584,3584,3584,3584},
  {1088,1093,580,1317,1270,1360,1442,725,151,1541,3584,3584,3584,3584,3584,3584,3584,3584,3584,3584,3584,3584,3584,3584},
  {1120,519,1410,1412,689,102,166,39,1536,3584,3584,3584,3584,3584,3584,3584,3584,3584,3584,3584,3584,3584,3584,3584},
  {1040,512,35,100,1314,1376,695,752,1543,3584,3584,3584,3584,3584,3584,3584,3584,3584,3584,3584,3584,3584,3584,3584},
  {1072,1125,1142,1047,1174,593,1255,1334,711,167,1574,3584,3584,3584,3584,3584,3584,3584,3584,3584,3584,3584,3584,3584},
  {1025,530,1280,614,1520,2096,3584,3584,3584,3584,3584,3584,3584,3584,3584,3584,3584,3584,3584,3584,3584,3584,3584,3584},
  {1057,513,147,1220,608,674,1521,2099,3584,3584,3584,3584,3584,3584,3584,3584,3584,3584,3584,3584,3584,3584,3584,3584},
  {1089,534,660,2052,3584,3584,3584,3584,3584,3584,3584,3584,3584,3584,3584,3584,3584,3584,3584,3584,3584,3584,3584,3584},
  {1121,517,661,755,1575,3584,3584,3584,3584,3584,3584,3584,3584,3584,3584,3584,3584,3584,3584,3584,3584,3584,3584,3584},
  {1041,516,213,658,741,1586,3584,3584,3584,3584,3584,3584,3584,3584,3584,3584,3584,3584,3584,3584,3584,3584,3584,3584},
  {80,177,130,179,21,1223,1297,1349,1411,1399,704,2053,3584,3584,3584,3584,3584,3584,3584,3584,3584,3584,3584,3584},
  {96,193,146,195,37,626,1507,721,150,23,231,3584,3584,3584,3584,3584,3584,3584,3584,3584,3584,3584,3584,3584},
  {1073,1,50,51,148,610,1424,706,753,1542,3584,3584,3584,3584,3584,3584,3584,3584,3584,3584,3584,3584,3584,3584},
  {112,547,1251,1285,1303,1301,1367,1413,742,1540,3584,3584,3584,3584,3584,3584,3584,3584,3584,3584,3584,3584,3584,3584},
  {128,209,162,1202,116,197,1378,694,736,1572,3584,3584,3584,3584,3584,3584,3584,3584,3584,3584,3584,3584,3584,3584},
  {1105,17,66,67,164,1344,1286,644,2086,3584,3584,3584,3584,3584,3584,3584,3584,3584,3584,3584,3584,3584,3584,3584},
  {144,1078,1127,1173,115,244,229,659,1523,2102,3584,3584,3584,3584,3584,3584,3584,3584,3584,3584,3584,3584,3584,3584},
  {1104,33,1171,1204,1175,1218,69,1239,1271,1269,1395,709,87,1585,3584,3584,3584,3584,3584,3584,3584,3584,3584,3584},
  {160,1110,1157,1158,594,1298,1331,1441,1474,1445,1461,1459,2082,3584,3584,3584,3584,3584,3584,3584,3584,3584,3584,3584},
  {1136,49,578,611,705,118,246,199,1590,3584,3584,3584,3584,3584,3584,3584,3584,3584,3584,3584,3584,3584,3584,3584},
  {1026,529,595,1350,673,1488,2100,3584,3584,3584,3584,3584,3584,3584,3584,3584,3584,3584,3584,3584,3584,3584,3584,3584},
  {1058,1155,1172,1079,1205,1216,132,1234,645,2085,3584,3584,3584,3584,3584,3584,3584,3584,3584,3584,3584,3584,3584,3584},
  {1090,1186,1031,1111,3,68,1221,1345,1267,1335,1361,688,1492,2066,3584,3584,3584,3584,3584,3584,3584,3584,3584,3584},
  {1122,65,596,678,737,1539,3584,3584,3584,3584,3584,3584,3584,3584,3584,3584,3584,3584,3584,3584,3584,3584,3584,3584},
  {176,562,1281,1233,1316,642,1478,740,1587,3584,3584,3584,3584,3584,3584,3584,3584,3584,3584,3584,3584,3584,3584,3584},
  {1152,535,691,2098,3584,3584,3584,3584,3584,3584,3584,3584,3584,3584,3584,3584,3584,3584,3584,3584,3584,3584,3584,3584},
  {1184,81,82,83,180,609,1366,759,1558,3584,3584,3584,3584,3584,3584,3584,3584,3584,3584,3584,3584,3584,3584,3584},
  {1042,1045,1063,1143,19,84,181,22,1332,692,720,1552,3584,3584,3584,3584,3584,3584,3584,3584,3584,3584,3584,3584},
  {192,560,1201,615,756,1557,3584,3584,3584,3584,3584,3584,3584,3584,3584,3584,3584,3584,3584,3584,3584,3584,3584,3584},
  {1074,97,1188,1189,1190,1206,1232,613,1494,2070,3584,3584,3584,3584,3584,3584,3584,3584,3584,3584,3584,3584,3584,3584},
  {1106,1077,576,243,85,1266,1328,1380,1472,1425,1476,1447,1527,2051,3584,3584,3584,3584,3584,3584,3584,3584,3584,3584},
  {1168,1109,581,640,1475,1429,724,1584,3584,3584,3584,3584,3584,3584,3584,3584,3584,3584,3584,3584,3584,3584,3584,3584},
  {1200,1141,582,1364,1473,1397,1458,70,2049,3584,3584,3584,3584,3584,3584,3584,3584,3584,3584,3584,3584,3584,3584,3584},
  {1137,515,631,2065,3584,3584,3584,3584,3584,3584,3584,3584,3584,3584,3584,3584,3584,3584,3584,3584,3584,3584,3584,3584},
  {1027,113,98,1203,1207,228,245,1268,1440,710,135,1556,3584,3584,3584,3584,3584,3584,3584,3584,3584,3584,3584,3584},
  {1059,550,676,2068,3584,3584,3584,3584,3584,3584,3584,3584,3584,3584,3584,3584,3584,3584,3584,3584,3584,3584,3584,3584},
  {1091,1030,2,210,4,101,1238,643,1490,2067,3584,3584,3584,3584,3584,3584,3584,3584,3584,3584,3584,3584,3584,3584},
  {1123,1062,18,226,20,117,627,1462,1493,2083,3584,3584,3584,3584,3584,3584,3584,3584,3584,3584,3584,3584,3584,3584},
  {1153,551,1300,1383,726,247,3584,3584,3584,3584,3584,3584,3584,3584,3584,3584,3584,3584,3584,3584,3584,3584,3584,3584},
  {1043,545,163,1250,663,134,7,215,1559,3584,3584,3584,3584,3584,3584,3584,3584,3584,3584,3584,3584,3584,3584,3584},
  {1075,528,1159,1191,212,1315,625,1396,1430,38,2054,3584,3584,3584,3584,3584,3584,3584,3584,3584,3584,3584,3584,3584},
  {1138,1094,592,1217,1249,149,624,727,1568,3584,3584,3584,3584,3584,3584,3584,3584,3584,3584,3584,3584,3584,3584,3584},
  {1028,1126,583,1394,1506,1446,1460,86,754,1589,3584,3584,3584,3584,3584,3584,3584,3584,3584,3584,3584,3584,3584,3584},
  {1060,532,630,2081,3584,3584,3584,3584,3584,3584,3584,3584,3584,3584,3584,3584,3584,3584,3584,3584,3584,3584,3584,3584},
  {1092,546,1219,1313,1236,1296,1302,677,198,103,1538,3584,3584,3584,3584,3584,3584,3584,3584,3584,3584,3584,3584,3584},
  {1124,533,628,1522,2064,3584,3584,3584,3584,3584,3584,3584,3584,3584,3584,3584,3584,3584,3584,3584,3584,3584,3584,3584},
  {1154,548,646,2084,3584,3584,3584,3584,3584,3584,3584,3584,3584,3584,3584,3584,3584,3584,3584,3584,3584,3584,3584,3584},
  {1185,564,662,2071,3584,3584,3584,3584,3584,3584,3584,3584,3584,3584,3584,3584,3584,3584,3584,3584,3584,3584,3584,3584},
  {1044,129,599,743,1555,3584,3584,3584,3584,3584,3584,3584,3584,3584,3584,3584,3584,3584,3584,3584,3584,3584,3584,3584},
  {208,225,178,211,1282,1252,1346,641,1457,1428,1526,2101,3584,3584,3584,3584,3584,3584,3584,3584,3584,3584,3584,3584},
  {224,241,194,227,53,1253,1237,1409,1382,1365,708,55,1553,3584,3584,3584,3584,3584,3584,3584,3584,3584,3584,3584},
  {1076,567,707,2097,3584,3584,3584,3584,3584,3584,3584,3584,3584,3584,3584,3584,3584,3584,3584,3584,3584,3584,3584,3584},
  {1108,566,675,1489,2087,3584,3584,3584,3584,3584,3584,3584,3584,3584,3584,3584,3584,3584,3584,3584,3584,3584,3584,3584},
  {1140,549,679,182,71,1569,3584,3584,3584,3584,3584,3584,3584,3584,3584,3584,3584,3584,3584,3584,3584,3584,3584,3584},
  {1107,1156,34,242,36,133,6,657,1456,1495,739,1554,3584,3584,3584,3584,3584,3584,3584,3584,3584,3584,3584,3584},
  {1139,145,579,1254,1408,1363,1392,1398,1508,1479,1491,2080,3584,3584,3584,3584,3584,3584,3584,3584,3584,3584,3584,3584},
  {1169,565,1377,1379,1362,672,1511,723,1537,3584,3584,3584,3584,3584,3584,3584,3584,3584,3584,3584,3584,3584,3584,3584},
  {240,563,1283,1235,1318,1299,1427,1393,1415,757,1588,3584,3584,3584,3584,3584,3584,3584,3584,3584,3584,3584,3584,3584},
  {1029,531,612,758,1591,3584,3584,3584,3584,3584,3584,3584,3584,3584,3584,3584,3584,3584,3584,3584,3584,3584,3584,3584},
  {1061,161,114,99,196,1284,629,2069,3584,3584,3584,3584,3584,3584,3584,3584,3584,3584,3584,3584,3584,3584,3584,3584},
};

struct HostState { bool init; Params p; void* out; const void* in[9]; };
HostState g_hs;

void build_state(void* const* d_in, void* d_out) {
  void* fn = nullptr;
  cudaDriverEntryPointQueryResult qr;
  cudaGetDriverEntryPoint("cuTensorMapEncodeTiled", &fn, cudaEnableDefault, &qr);
  EncodeFn enc = (EncodeFn)fn;
  void *kv, *ctx, *oA;
  cudaGetSymbolAddress(&kv, g_kv);
  cudaGetSymbolAddress(&ctx, g_ctx);
  cudaGetSymbolAddress(&oA, g_oA);
  Params& p = g_hs.p;
  make_map_2d(enc, &p.maps[M_AX], d_in[0], 2048, SEQ / 2);
  make_map_2d(enc, &p.maps[M_BX], d_in[3], 1024, SEQ);
  make_map_2d(enc, &p.maps[M_CKV], d_in[4], 512, SEQ);
  make_map_2d(enc, &p.maps[M_OA], oA, 1024, SEQ);
  make_map_2d(enc, &p.maps[M_CTX], ctx, 4096, SEQ);
  make_map_3d(enc, &p.maps[M_WQKV], d_in[1], 3072, 1024, 1024, 32, 3);
  make_map_3d(enc, &p.maps[M_WQ], d_in[5], 4096, 1024, 64, 64, 2);
  make_map_3d(enc, &p.maps[M_WUK], d_in[6], 4096, 512, 64, 64, 2);
  make_map_3d(enc, &p.maps[M_WUV], d_in[7], 4096, 512, 64, 64, 2);
  make_map_3d(enc, &p.maps[M_WOA], d_in[2], 1024, 1024, 64, 64, 2);
  make_map_3d(enc, &p.maps[M_WOB], d_in[8], 1024, 4096, 64, 64, 2);
  make_map_2d(enc, &p.maps[M_KV_LD], kv, 256, 32 * SEQ);
  make_map_3d(enc, &p.maps[M_OA_ST], oA, 1024, SEQ, 64, 64, 1);
  make_map_3d(enc, &p.maps[M_CTX_ST], ctx, 4096, SEQ, 64, 64, 2);
  make_map_3d(enc, &p.maps[M_KV_ST], kv, 256, 32 * SEQ, 64, 64, 2);
  make_map_3d(enc, &p.maps[M_OUTA_ST], d_out, 4096, SEQ / 2, 64, 64, 2);
  make_map_3d(enc, &p.maps[M_OUTB_ST], d_out, 2048, SEQ, 64, 64, 2);
  for (int c = 0; c < NPAIR; c++)
    for (int i = 0; i < MAX_ITEMS; i++) p.sched[c][i] = h_sched[c][i];
  cudaFuncSetAttribute(mega_kernel, cudaFuncAttributeMaxDynamicSharedMemorySize, SMEM_BYTES);
}

}

extern "C" void kernel_launch(void* const* d_in, const int* in_sizes, int n_in, void* d_out, int out_size) {
  (void)in_sizes; (void)n_in; (void)out_size;
  bool same = g_hs.init && g_hs.out == d_out;
  for (int i = 0; i < 9 && same; i++) same = (g_hs.in[i] == d_in[i]);
  if (!same) {
    build_state(d_in, d_out);
    g_hs.init = true; g_hs.out = d_out;
    for (int i = 0; i < 9; i++) g_hs.in[i] = d_in[i];
  }
  mega_kernel<<<NCTA, 384, SMEM_BYTES, cudaStreamPerThread>>>(g_hs.p);
}
```

```cpp
#include <cuda_runtime.h>
#include <cuda_bf16.h>
#include <cuda.h>
#include <stdint.h>

namespace {

constexpr int SEQ = 2048;
constexpr int NCTA = 132, NPAIR = 66;
constexpr int MAX_ITEMS = 20;

__device__ __align__(1024) __nv_bfloat16 g_kv[32 * SEQ * 256];
__device__ __align__(1024) __nv_bfloat16 g_ctx[SEQ * 4096];
__device__ __align__(1024) __nv_bfloat16 g_oA[SEQ * 1024];
__device__ __align__(1024) uint8_t g_halo[16 * 16 * 2048];
struct Flags { uint32_t m[64]; uint32_t epoch[NCTA]; };
__device__ __align__(128) Flags g_flags;
enum { F_KV = 0, F_CTX = 32, F_QL = 48 };

enum { K_QL = 0, K_QF = 1, K_KV = 2, K_OA = 3, K_OB = 4, K_END = 7 };
enum { M_AX = 0, M_BX, M_CKV, M_OA, M_CTX, M_WQKV, M_WQ, M_WUK, M_WOA, M_WOB, M_WUV, M_KV_LD, M_OA_ST, M_CTX_ST, M_KV_ST, M_OUTA_ST, M_OUTB_ST, M_COUNT };

struct Params {
  CUtensorMap maps[M_COUNT];
  alignas(16) uint32_t sched[NPAIR][MAX_ITEMS];
};

#define TRC(idx, slot)
#define TRW(idx, slot)
#define T4Q(dep)
#define T4X(dep)
#define T4K()

constexpr uint32_t SB = 1024;
constexpr uint32_t OFF_A = 0;
constexpr uint32_t OFF_B = 65536;
constexpr uint32_t OFF_STG = 196608;
constexpr uint32_t OFF_HALO = 229376;
constexpr uint32_t OFF_BAR = 231424;
constexpr uint32_t OFF_MASK = OFF_BAR + 256;
constexpr uint32_t OFF_LIST = OFF_BAR + 512;
constexpr uint32_t OFF_FILLS = OFF_BAR + 608;
constexpr uint32_t SMEM_BYTES = OFF_BAR + 640;
enum { B_FULL = 0, B_EMPTY = 4, B_QEMPTY = 8, B_STGE = 10, B_STGF = 12, B_FIN = 14, B_QFULL = 16, B_QX = 17, B_LEAD = 18, B_HFULL = 19, B_HEMPTY = 20, B_COUNT = 21 };
__host__ __device__ constexpr uint32_t BAR(int b) { return OFF_BAR + b * 8; }
__host__ __device__ constexpr int bar_count(int b) { return b < B_EMPTY ? 1 : b < B_QEMPTY ? 4 : b < B_STGE ? 8 : b < B_STGF ? 1 : b < B_QFULL ? 4 : b == B_QX ? 2 : 1; }
#define RCONS 232
constexpr int REG_CONS = RCONS, REG_PROD = (64512 - RCONS * 256) / 128 / 8 * 8;
#define KVSLOT(h) (h)
#define PACE_MAX 1100
#define WATCH_NS 250
#define HINTS 3
#define JSPLIT 14
#define JEDGE 14
#define LSH 0
#define LPUB 1
#define SBU 1
#define LHS 1
#define LPUBP 0
#define LEADF 3
#define EARLYN 3
#define HLATE 3
#define LASTUSE 3
#define EREL 1
#define JP 8
#define YIELD0 0
#define YIELD2 0
#define JDIAG2 10
#define SUMPOS 1
#define JDIAG 12
#define LEADN 2
#define LEADL LEADN
#define STGA 3
#define STGB 8
#define STGAL 4
#define STGBL 12
#define PUBD 1

__device__ __forceinline__ uint32_t smem_u32(const void* p) { return (uint32_t)__cvta_generic_to_shared(p); }
__device__ __forceinline__ void wg_fence() { asm volatile("wgmma.fence.sync.aligned;" ::: "memory"); }
__device__ __forceinline__ void wg_commit() { asm volatile("wgmma.commit_group.sync.aligned;" ::: "memory"); }
template <int N> __device__ __forceinline__ void wg_wait() { asm volatile("wgmma.wait_group.sync.aligned %0;" ::"n"(N) : "memory"); }
__host__ __device__ constexpr uint32_t dlo(uint32_t off, uint32_t lbo) { return ((SB + off) >> 4) | ((lbo >> 4) << 16); }
template <uint32_t O> __device__ __forceinline__ void mbar_init(uint32_t a, uint32_t cnt) { asm volatile("mbarrier.init.shared::cta.b64 [%0+%2], %1;" ::"r"(a), "r"(cnt), "n"(O) : "memory"); }
template <uint32_t O> __device__ __forceinline__ void mbar_expect_tx(uint32_t a, uint32_t bytes) { asm volatile("mbarrier.arrive.expect_tx.shared::cta.b64 _, [%0+%2], %1;" ::"r"(a), "r"(bytes), "n"(O) : "memory"); }
template <uint32_t O> __device__ __forceinline__ void mbar_arrive_if(uint32_t a, bool pred) {
  asm volatile("{\n.reg .pred p;\nsetp.ne.u32 p, %1, 0;\n@p mbarrier.arrive.shared::cta.b64 _, [%0+%2];\n}\n" ::"r"(a), "r"((uint32_t)pred), "n"(O) : "memory");
}
template <uint32_t O> __device__ __forceinline__ void mbar_arrive_cl(uint32_t a, uint32_t off = 0) {
  asm volatile("{\n.reg .pred p;\nsetp.ne.u32 p, %2, 0;\n@p mbarrier.arrive.shared::cluster.b64 _, [%0+%1];\n}\n" ::"r"(a + off), "n"(O), "r"(a) : "memory");
}
template <uint32_t O> __device__ __forceinline__ bool mbar_test(uint32_t a, uint32_t parity) {
  uint32_t ok;
  asm volatile("{\n.reg .pred p;\nmbarrier.test_wait.parity.shared::cta.b64 p, [%1+%3], %2;\nselp.u32 %0, 1, 0, p;\n}\n" : "=r"(ok) : "r"(a), "r"(parity), "n"(O) : "memory");
  return ok;
}
template <uint32_t O> __device__ __forceinline__ void mbar_wait(uint32_t a, uint32_t parity) {
  asm volatile("{\n.reg .pred p, q;\n.reg .u32 n;\nmov.u32 n, 0;\nWAIT_%=:\nadd.u32 n, n, 1;\nmbarrier.try_wait.parity.shared::cta.b64 p, [%0+%2], %1;\n"
               "setp.lt.u32 q, n, 4194304;\nand.pred q, q, !p;\n@q bra WAIT_%=;\n@!p st.shared.u32 [%0+1], n;\n}\n" ::"r"(a), "r"(parity), "n"(O) : "memory");
}
template <uint32_t O> __device__ __forceinline__ void mbar_wait_long(uint32_t a, uint32_t parity) {
  asm volatile("{\n.reg .pred p, q;\n.reg .u32 n;\nmov.u32 n, 0;\nWAIT_%=:\nadd.u32 n, n, 1;\nmbarrier.try_wait.parity.shared::cta.b64 p, [%0+%2], %1, 4000;\n"
               "setp.lt.u32 q, n, 1048576;\nand.pred q, q, !p;\n@q bra WAIT_%=;\n@!p st.shared.u32 [%0+1], n;\n}\n" ::"r"(a), "r"(parity), "n"(O) : "memory");
}
__device__ __forceinline__ void tma_load_2d(uint32_t dst, const CUtensorMap* tm, int c0, int c1, uint32_t bar) {
  asm volatile("cp.async.bulk.tensor.2d.shared::cluster.global.mbarrier::complete_tx::bytes [%0], [%1, {%3, %4}], [%2];" ::"r"(dst), "l"(tm), "r"(bar), "r"(c0), "r"(c1) : "memory");
}
__device__ __forceinline__ void tma_load_3d(uint32_t dst, const CUtensorMap* tm, int c0, int c1, int c2, uint32_t bar) {
  asm volatile("cp.async.bulk.tensor.3d.shared::cluster.global.mbarrier::complete_tx::bytes [%0], [%1, {%3, %4, %5}], [%2];" ::"r"(dst), "l"(tm), "r"(bar), "r"(c0), "r"(c1), "r"(c2) : "memory");
}
#define FILL_HEAD "{\n.reg .pred p, q;\n.reg .u32 n;\nmov.u32 n, 0;\nWAIT_%=:\nadd.u32 n, n, 1;\nmbarrier.try_wait.parity.shared::cta.b64 p, [%0+%1], %3;\n" \
                  "setp.lt.u32 q, n, 4194304;\nand.pred q, q, !p;\n@q bra WAIT_%=;\n@!p st.shared.u32 [%0+1], n;\nelect.sync _|p, 0xffffffff;\n" \
                  "@p mbarrier.arrive.expect_tx.shared::cta.b64 _, [%2], %4;\n"
__device__ __forceinline__ void fill_gemm(uint32_t bb, uint32_t parity, uint32_t bytes, uint32_t dstb, const CUtensorMap* mb, int b0, int b1, int b2, uint32_t dsta, const CUtensorMap* ma, int a0, int a1, uint64_t pb, uint64_t pa) {
  asm volatile(FILL_HEAD
               "@p cp.async.bulk.tensor.3d.shared::cluster.global.mbarrier::complete_tx::bytes.multicast::cluster.L2::cache_hint [%5], [%6, {%7, %8, %9}], [%2], %14, %15;\n"
               "@p cp.async.bulk.tensor.2d.shared::cluster.global.mbarrier::complete_tx::bytes.L2::cache_hint [%10], [%11, {%12, %13}], [%2], %16;\n}\n"
               ::"r"(bb), "n"(BAR(B_EMPTY)), "r"(bb + BAR(B_FULL)), "r"(parity), "r"(bytes), "r"(dstb), "l"(mb), "r"(b0), "r"(b1), "r"(b2), "r"(dsta), "l"(ma), "r"(a0), "r"(a1), "h"((uint16_t)3), "l"(pb), "l"(pa) : "memory");
}
__device__ __forceinline__ void fill_kv(uint32_t bb, uint32_t parity, uint32_t dst, const CUtensorMap* m, int c0, int c1, uint16_t mask, uint64_t pol) {
  asm volatile(FILL_HEAD
               "@p cp.async.bulk.tensor.2d.shared::cluster.global.mbarrier::complete_tx::bytes.multicast::cluster.L2::cache_hint [%5], [%6, {%7, %8}], [%2], %9, %10;\n}\n"
               ::"r"(bb), "n"(BAR(B_EMPTY)), "r"(bb + BAR(B_FULL)), "r"(parity), "r"(32768), "r"(dst), "l"(m), "r"(c0), "r"(c1), "h"(mask), "l"(pol) : "memory");
}
__device__ __forceinline__ void tma_load_2d_h(uint32_t dst, const CUtensorMap* tm, int c0, int c1, uint32_t bar, uint64_t pol) {
  asm volatile("{\n.reg .pred p;\nelect.sync _|p, 0xffffffff;\n@p cp.async.bulk.tensor.2d.shared::cluster.global.mbarrier::complete_tx::bytes.L2::cache_hint [%0], [%1, {%3, %4}], [%2], %5;\n}\n" ::"r"(dst), "l"(tm), "r"(bar), "r"(c0), "r"(c1), "l"(pol) : "memory");
}
__device__ __forceinline__ void tma_store_3d(const CUtensorMap* tm, uint32_t src, int c0, int c1, int c2, uint64_t pol) {
  asm volatile("{\n.reg .pred p;\nelect.sync _|p, 0xffffffff;\n@p cp.async.bulk.tensor.3d.global.shared::cta.bulk_group.L2::cache_hint [%0, {%2, %3, %4}], [%1], %5;\n}\n" ::"l"(tm), "r"(src), "r"(c0), "r"(c1), "r"(c2), "l"(pol) : "memory");
}
__device__ __forceinline__ void bulk_load(uint32_t dst, const void* src, uint32_t bytes, uint32_t bar) {
  asm volatile("{\n.reg .pred p;\nelect.sync _|p, 0xffffffff;\n@p cp.async.bulk.shared::cluster.global.mbarrier::complete_tx::bytes [%0], [%1], %2, [%3];\n}\n" ::"r"(dst), "l"(src), "r"(bytes), "r"(bar) : "memory");
}
__device__ __forceinline__ void bulk_store(void* dst, uint32_t src, uint32_t bytes) {
  asm volatile("{\n.reg .pred p;\nelect.sync _|p, 0xffffffff;\n@p cp.async.bulk.global.shared::cta.bulk_group [%0], [%1], %2;\n}\n" ::"l"(dst), "r"(src), "r"(bytes) : "memory");
}
__device__ __forceinline__ void bulk_send(uint32_t dst, uint32_t src, uint32_t bytes, uint32_t bar) {
  asm volatile("{\n.reg .pred p;\nelect.sync _|p, 0xffffffff;\n@p cp.async.bulk.shared::cluster.shared::cta.mbarrier::complete_tx::bytes [%0], [%1], %2, [%3];\n}\n" ::"r"(dst), "r"(src), "r"(bytes), "r"(bar) : "memory");
}
__device__ __forceinline__ uint64_t policy_evict_first() { uint64_t p; asm volatile("createpolicy.fractional.L2::evict_first.b64 %0, 1.0;" : "=l"(p)); return p; }
constexpr uint64_t POL_NORMAL = 0x1000000000000000ull;
__device__ __forceinline__ uint32_t mapa(uint32_t addr, uint32_t rank) { uint32_t r; asm("mapa.shared::cluster.u32 %0, %1, %2;" : "=r"(r) : "r"(addr), "r"(rank)); return r; }
__device__ __forceinline__ void cluster_arrive_relaxed() { asm volatile("barrier.cluster.arrive.relaxed.aligned;" ::: "memory"); }
__device__ __forceinline__ void cluster_arrive() { asm volatile("barrier.cluster.arrive.release.aligned;" ::: "memory"); }
__device__ __forceinline__ void cluster_wait() { asm volatile("barrier.cluster.wait.acquire.aligned;" ::: "memory"); }
__device__ __forceinline__ void bulk_commit() { asm volatile("cp.async.bulk.commit_group;" ::: "memory"); }
template <int N> __device__ __forceinline__ void bulk_wait_read() { asm volatile("cp.async.bulk.wait_group.read %0;" ::"n"(N) : "memory"); }
__device__ __forceinline__ void bulk_wait_all() { asm volatile("cp.async.bulk.wait_group 0;" ::: "memory"); }
__device__ __forceinline__ void fence_async_smem() { asm volatile("fence.proxy.async.shared::cta;" ::: "memory"); }
__device__ __forceinline__ void fence_async_glob() { asm volatile("fence.proxy.async.global;" ::: "memory"); }
__device__ __forceinline__ void flag_toggle(uint32_t* p, uint32_t v) { asm volatile("{\n.reg .pred p;\nelect.sync _|p, 0xffffffff;\n@p red.release.gpu.global.xor.b32 [%0], %1;\n}\n" ::"l"(p), "r"(v) : "memory"); }
template <uint32_t O> __device__ __forceinline__ uint32_t lds_acquire(uint32_t a) { uint32_t v; asm volatile("ld.acquire.cta.shared::cta.u32 %0, [%1+%2];" : "=r"(v) : "r"(a), "n"(O) : "memory"); return v; }
__device__ __forceinline__ uint32_t item_full(uint32_t sb, int idx) {
  uint32_t c;
  asm volatile("ld.shared.u32 %0, [%1+%2];" : "=r"(c) : "r"(sb + idx * 4), "n"(OFF_LIST));
  return __reduce_or_sync(0xffffffffu, c);
}
__device__ __forceinline__ uint32_t item(uint32_t sb, int idx) { return item_full(sb, idx) & 4095; }
template <int N> __device__ __forceinline__ void reg_alloc() { asm volatile("setmaxnreg.inc.sync.aligned.u32 %0;" ::"n"(N)); }
template <int N> __device__ __forceinline__ void reg_dealloc() { asm volatile("setmaxnreg.dec.sync.aligned.u32 %0;" ::"n"(N)); }
template <int I0, int I1, int N> __device__ __forceinline__ void fence_regs(float (&d)[N]) {
#pragma unroll
  for (int i = I0; i < I1; i++) asm volatile("" : "+f"(d[i])::"memory");
}
template <int N> __device__ __forceinline__ void fence_regs(float (&d)[N]) { fence_regs<0, N, N>(d); }
template <int N> __device__ __forceinline__ void fence_regs(uint32_t (&d)[N]) {
#pragma unroll
  for (int i = 0; i < N; i++) asm volatile("" : "+r"(d[i])::"memory");
}
__device__ __forceinline__ uint32_t pack_bf16(float lo, float hi) { uint32_t r; asm("cvt.rn.bf16x2.f32 %0, %1, %2;" : "=r"(r) : "f"(hi), "f"(lo)); return r; }
__device__ __forceinline__ uint32_t v_pack(float lo, float hi) { uint32_t r; asm volatile("cvt.rn.bf16x2.f32 %0, %1, %2;" : "=r"(r) : "f"(hi), "f"(lo)); return r; }
template <uint32_t O> __device__ __forceinline__ void stmatrix_x4(uint32_t a, uint32_t r0, uint32_t r1, uint32_t r2, uint32_t r3) {
  asm volatile("stmatrix.sync.aligned.m8n8.x4.shared.b16 [%0+%5], {%1, %2, %3, %4};" ::"r"(a), "r"(r0), "r"(r1), "r"(r2), "r"(r3), "n"(O) : "memory");
}
template <uint32_t O> __device__ __forceinline__ void stmatrix_x4_after(uint32_t a, uint32_t r0, uint32_t r1, uint32_t r2, uint32_t r3, float dep) {
  asm volatile("{\n.reg .pred q;\n.reg .u32 a;\nsetp.ne.u32 q, %6, 0xffffffff;\nselp.u32 a, %0, 0, q;\nstmatrix.sync.aligned.m8n8.x4.shared.b16 [a+%5], {%1, %2, %3, %4};\n}\n"
               ::"r"(a), "r"(r0), "r"(r1), "r"(r2), "r"(r3), "n"(O), "r"(__float_as_uint(dep)) : "memory");
}
template <uint32_t O> __device__ __forceinline__ void stmatrix_x4_trans(uint32_t a, uint32_t r0, uint32_t r1, uint32_t r2, uint32_t r3) {
  asm volatile("stmatrix.sync.aligned.m8n8.x4.trans.shared.b16 [%0+%5], {%1, %2, %3, %4};" ::"r"(a), "r"(r0), "r"(r1), "r"(r2), "r"(r3), "n"(O) : "memory");
}
template <uint32_t O> __device__ __forceinline__ void sts128(uint32_t a, const uint32_t* r) { asm volatile("st.shared.v4.u32 [%0+%5], {%1, %2, %3, %4};" ::"r"(a), "r"(r[0]), "r"(r[1]), "r"(r[2]), "r"(r[3]), "n"(O) : "memory"); }
template <uint32_t O> __device__ __forceinline__ void lds128(uint32_t* r, uint32_t a) { asm volatile("ld.shared.v4.u32 {%0, %1, %2, %3}, [%4+%5];" : "=r"(r[0]), "=r"(r[1]), "=r"(r[2]), "=r"(r[3]) : "r"(a), "n"(O) : "memory"); }
__device__ __forceinline__ uint32_t transpose8(uint32_t a) { uint32_t d; asm volatile("movmatrix.sync.aligned.m8n8.trans.b16 %0, %1;" : "=r"(d) : "r"(a)); return d; }
__device__ __forceinline__ float ex2(float x) { float y; asm("ex2.approx.ftz.f32 %0, %1;" : "=f"(y) : "f"(x)); return y; }
__device__ __forceinline__ float rcp(float x) { float y; asm("rcp.approx.ftz.f32 %0, %1;" : "=f"(y) : "f"(x)); return y; }
__device__ __forceinline__ void bar_sync(int id, int n) { asm volatile("bar.sync %0, %1;" ::"r"(id), "r"(n) : "memory"); }
__device__ __forceinline__ void bar_arrive(int id, int n) { asm volatile("bar.arrive %0, %1;" ::"r"(id), "r"(n) : "memory"); }
__device__ __forceinline__ void mma16816(float (&c)[4], uint32_t a0, uint32_t a1, uint32_t a2, uint32_t a3, uint32_t b0, uint32_t b1) {
  asm("mma.sync.aligned.m16n8k16.row.col.f32.bf16.bf16.f32 {%0, %1, %2, %3}, {%4, %5, %6, %7}, {%8, %9}, {%0, %1, %2, %3};"
      : "+f"(c[0]), "+f"(c[1]), "+f"(c[2]), "+f"(c[3]) : "r"(a0), "r"(a1), "r"(a2), "r"(a3), "r"(b0), "r"(b1));
}
__device__ __forceinline__ void mma16816z(float (&c)[4], uint32_t a0, uint32_t a1, uint32_t a2, uint32_t a3, uint32_t b0, uint32_t b1, float z) {
  asm("mma.sync.aligned.m16n8k16.row.col.f32.bf16.bf16.f32 {%0, %1, %2, %3}, {%4, %5, %6, %7}, {%8, %9}, {%10, %10, %10, %10};"
      : "=f"(c[0]), "=f"(c[1]), "=f"(c[2]), "=f"(c[3]) : "r"(a0), "r"(a1), "r"(a2), "r"(a3), "r"(b0), "r"(b1), "f"(z));
}
__device__ __forceinline__ uint4 ldg128(const void* p) { uint4 v; asm volatile("ld.global.cg.v4.u32 {%0, %1, %2, %3}, [%4];" : "=r"(v.x), "=r"(v.y), "=r"(v.z), "=r"(v.w) : "l"(p) : "memory"); return v; }
__device__ __forceinline__ uint32_t ldg16(const void* p) { uint16_t v; asm volatile("ld.global.cg.u16 %0, [%1];" : "=h"(v) : "l"(p) : "memory"); return v; }
__device__ __forceinline__ float quad_sum(float v) {
  v += __shfl_xor_sync(0xffffffffu, v, 1);
  v += __shfl_xor_sync(0xffffffffu, v, 2);
  return v;
}
__device__ __forceinline__ bool elect_one() { uint32_t p; asm volatile("{\n.reg .pred p;\nelect.sync _|p, 0xffffffff;\nselp.u32 %0, 1, 0, p;\n}\n" : "=r"(p)); return p; }
#define UNLIKELY(x) __builtin_expect(!!(x), 0)

__device__ __forceinline__ void wg_gemm_init(float (&d)[128], uint32_t alo, uint32_t blo) {
  asm volatile("{\n.reg .pred p;\n.reg .b64 da, db;\nmov.b64 da, {%128, 0x40000040};\nmov.b64 db, {%129, 0x40000040};\nsetp.ne.b32 p, 0, 0;\n"
    "wgmma.mma_async.sync.aligned.m64n256k16.f32.bf16.bf16 {"
    "%0, %1, %2, %3, %4, %5, %6, %7, %8, %9, %10, %11, %12, %13, %14, %15, %16, %17, %18, %19, %20, %21, %22, %23, %24, %25, %26, %27, %28, %29, %30, %31, "
    "%32, %33, %34, %35, %36, %37, %38, %39, %40, %41, %42, %43, %44, %45, %46, %47, %48, %49, %50, %51, %52, %53, %54, %55, %56, %57, %58, %59, %60, %61, %62, %63, "
    "%64, %65, %66, %67, %68, %69, %70, %71, %72, %73, %74, %75, %76, %77, %78, %79, %80, %81, %82, %83, %84, %85, %86, %87, %88, %89, %90, %91, %92, %93, %94, %95, "
    "%96, %97, %98, %99, %100, %101, %102, %103, %104, %105, %106, %107, %108, %109, %110, %111, %112, %113, %114, %115, %116, %117, %118, %119, %120, %121, %122, %123, %124, %125, %126, %127}, "
    "da, db, p, 1, 1, 0, 1;\n}\n"
    : "=f"(d[0]), "=f"(d[1]), "=f"(d[2]), "=f"(d[3]), "=f"(d[4]), "=f"(d[5]), "=f"(d[6]), "=f"(d[7]), "=f"(d[8]), "=f"(d[9]), "=f"(d[10]), "=f"(d[11]), "=f"(d[12]), "=f"(d[13]), "=f"(d[14]), "=f"(d[15]),
      "=f"(d[16]), "=f"(d[17]), "=f"(d[18]), "=f"(d[19]), "=f"(d[20]), "=f"(d[21]), "=f"(d[22]), "=f"(d[23]), "=f"(d[24]), "=f"(d[25]), "=f"(d[26]), "=f"(d[27]), "=f"(d[28]), "=f"(d[29]), "=f"(d[30]), "=f"(d[31]),
      "=f"(d[32]), "=f"(d[33]), "=f"(d[34]), "=f"(d[35]), "=f"(d[36]), "=f"(d[37]), "=f"(d[38]), "=f"(d[39]), "=f"(d[40]), "=f"(d[41]), "=f"(d[42]), "=f"(d[43]), "=f"(d[44]), "=f"(d[45]), "=f"(d[46]), "=f"(d[47]),
      "=f"(d[48]), "=f"(d[49]), "=f"(d[50]), "=f"(d[51]), "=f"(d[52]), "=f"(d[53]), "=f"(d[54]), "=f"(d[55]), "=f"(d[56]), "=f"(d[57]), "=f"(d[58]), "=f"(d[59]), "=f"(d[60]), "=f"(d[61]), "=f"(d[62]), "=f"(d[63]),
      "=f"(d[64]), "=f"(d[65]), "=f"(d[66]), "=f"(d[67]), "=f"(d[68]), "=f"(d[69]), "=f"(d[70]), "=f"(d[71]), "=f"(d[72]), "=f"(d[73]), "=f"(d[74]), "=f"(d[75]), "=f"(d[76]), "=f"(d[77]), "=f"(d[78]), "=f"(d[79]),
      "=f"(d[80]), "=f"(d[81]), "=f"(d[82]), "=f"(d[83]), "=f"(d[84]), "=f"(d[85]), "=f"(d[86]), "=f"(d[87]), "=f"(d[88]), "=f"(d[89]), "=f"(d[90]), "=f"(d[91]), "=f"(d[92]), "=f"(d[93]), "=f"(d[94]), "=f"(d[95]),
      "=f"(d[96]), "=f"(d[97]), "=f"(d[98]), "=f"(d[99]), "=f"(d[100]), "=f"(d[101]), "=f"(d[102]), "=f"(d[103]), "=f"(d[104]), "=f"(d[105]), "=f"(d[106]), "=f"(d[107]), "=f"(d[108]), "=f"(d[109]), "=f"(d[110]), "=f"(d[111]),
      "=f"(d[112]), "=f"(d[113]), "=f"(d[114]), "=f"(d[115]), "=f"(d[116]), "=f"(d[117]), "=f"(d[118]), "=f"(d[119]), "=f"(d[120]), "=f"(d[121]), "=f"(d[122]), "=f"(d[123]), "=f"(d[124]), "=f"(d[125]), "=f"(d[126]), "=f"(d[127])
    : "r"(alo), "r"(blo));
}
__device__ __forceinline__ void wg_gemm_acc(float (&d)[128], uint32_t alo, uint32_t blo) {
  asm volatile("{\n.reg .pred p;\n.reg .b64 da, db;\nmov.b64 da, {%128, 0x40000040};\nmov.b64 db, {%129, 0x40000040};\nsetp.eq.b32 p, 0, 0;\n"
    "wgmma.mma_async.sync.aligned.m64n256k16.f32.bf16.bf16 {"
    "%0, %1, %2, %3, %4, %5, %6, %7, %8, %9, %10, %11, %12, %13, %14, %15, %16, %17, %18, %19, %20, %21, %22, %23, %24, %25, %26, %27, %28, %29, %30, %31, "
    "%32, %33, %34, %35, %36, %37, %38, %39, %40, %41, %42, %43, %44, %45, %46, %47, %48, %49, %50, %51, %52, %53, %54, %55, %56, %57, %58, %59, %60, %61, %62, %63, "
    "%64, %65, %66, %67, %68, %69, %70, %71, %72, %73, %74, %75, %76, %77, %78, %79, %80, %81, %82, %83, %84, %85, %86, %87, %88, %89, %90, %91, %92, %93, %94, %95, "
    "%96, %97, %98, %99, %100, %101, %102, %103, %104, %105, %106, %107, %108, %109, %110, %111, %112, %113, %114, %115, %116, %117, %118, %119, %120, %121, %122, %123, %124, %125, %126, %127}, "
    "da, db, p, 1, 1, 0, 1;\n}\n"
    : "+f"(d[0]), "+f"(d[1]), "+f"(d[2]), "+f"(d[3]), "+f"(d[4]), "+f"(d[5]), "+f"(d[6]), "+f"(d[7]), "+f"(d[8]), "+f"(d[9]), "+f"(d[10]), "+f"(d[11]), "+f"(d[12]), "+f"(d[13]), "+f"(d[14]), "+f"(d[15]),
      "+f"(d[16]), "+f"(d[17]), "+f"(d[18]), "+f"(d[19]), "+f"(d[20]), "+f"(d[21]), "+f"(d[22]), "+f"(d[23]), "+f"(d[24]), "+f"(d[25]), "+f"(d[26]), "+f"(d[27]), "+f"(d[28]), "+f"(d[29]), "+f"(d[30]), "+f"(d[31]),
      "+f"(d[32]), "+f"(d[33]), "+f"(d[34]), "+f"(d[35]), "+f"(d[36]), "+f"(d[37]), "+f"(d[38]), "+f"(d[39]), "+f"(d[40]), "+f"(d[41]), "+f"(d[42]), "+f"(d[43]), "+f"(d[44]), "+f"(d[45]), "+f"(d[46]), "+f"(d[47]),
      "+f"(d[48]), "+f"(d[49]), "+f"(d[50]), "+f"(d[51]), "+f"(d[52]), "+f"(d[53]), "+f"(d[54]), "+f"(d[55]), "+f"(d[56]), "+f"(d[57]), "+f"(d[58]), "+f"(d[59]), "+f"(d[60]), "+f"(d[61]), "+f"(d[62]), "+f"(d[63]),
      "+f"(d[64]), "+f"(d[65]), "+f"(d[66]), "+f"(d[67]), "+f"(d[68]), "+f"(d[69]), "+f"(d[70]), "+f"(d[71]), "+f"(d[72]), "+f"(d[73]), "+f"(d[74]), "+f"(d[75]), "+f"(d[76]), "+f"(d[77]), "+f"(d[78]), "+f"(d[79]),
      "+f"(d[80]), "+f"(d[81]), "+f"(d[82]), "+f"(d[83]), "+f"(d[84]), "+f"(d[85]), "+f"(d[86]), "+f"(d[87]), "+f"(d[88]), "+f"(d[89]), "+f"(d[90]), "+f"(d[91]), "+f"(d[92]), "+f"(d[93]), "+f"(d[94]), "+f"(d[95]),
      "+f"(d[96]), "+f"(d[97]), "+f"(d[98]), "+f"(d[99]), "+f"(d[100]), "+f"(d[101]), "+f"(d[102]), "+f"(d[103]), "+f"(d[104]), "+f"(d[105]), "+f"(d[106]), "+f"(d[107]), "+f"(d[108]), "+f"(d[109]), "+f"(d[110]), "+f"(d[111]),
      "+f"(d[112]), "+f"(d[113]), "+f"(d[114]), "+f"(d[115]), "+f"(d[116]), "+f"(d[117]), "+f"(d[118]), "+f"(d[119]), "+f"(d[120]), "+f"(d[121]), "+f"(d[122]), "+f"(d[123]), "+f"(d[124]), "+f"(d[125]), "+f"(d[126]), "+f"(d[127])
    : "r"(alo), "r"(blo));
}
__device__ __forceinline__ void wg_gemm_init(float (&d)[96], uint32_t alo, uint32_t blo) {
  asm volatile("{\n.reg .pred p;\n.reg .b64 da, db;\nmov.b64 da, {%96, 0x40000040};\nmov.b64 db, {%97, 0x40000040};\nsetp.ne.b32 p, 0, 0;\n"
    "wgmma.mma_async.sync.aligned.m64n192k16.f32.bf16.bf16 {"
    "%0, %1, %2, %3, %4, %5, %6, %7, %8, %9, %10, %11, %12, %13, %14, %15, %16, %17, %18, %19, %20, %21, %22, %23, %24, %25, %26, %27, %28, %29, %30, %31, "
    "%32, %33, %34, %35, %36, %37, %38, %39, %40, %41, %42, %43, %44, %45, %46, %47, %48, %49, %50, %51, %52, %53, %54, %55, %56, %57, %58, %59, %60, %61, %62, %63, "
    "%64, %65, %66, %67, %68, %69, %70, %71, %72, %73, %74, %75, %76, %77, %78, %79, %80, %81, %82, %83, %84, %85, %86, %87, %88, %89, %90, %91, %92, %93, %94, %95}, "
    "da, db, p, 1, 1, 0, 1;\n}\n"
    : "=f"(d[0]), "=f"(d[1]), "=f"(d[2]), "=f"(d[3]), "=f"(d[4]), "=f"(d[5]), "=f"(d[6]), "=f"(d[7]), "=f"(d[8]), "=f"(d[9]), "=f"(d[10]), "=f"(d[11]), "=f"(d[12]), "=f"(d[13]), "=f"(d[14]), "=f"(d[15]),
      "=f"(d[16]), "=f"(d[17]), "=f"(d[18]), "=f"(d[19]), "=f"(d[20]), "=f"(d[21]), "=f"(d[22]), "=f"(d[23]), "=f"(d[24]), "=f"(d[25]), "=f"(d[26]), "=f"(d[27]), "=f"(d[28]), "=f"(d[29]), "=f"(d[30]), "=f"(d[31]),
      "=f"(d[32]), "=f"(d[33]), "=f"(d[34]), "=f"(d[35]), "=f"(d[36]), "=f"(d[37]), "=f"(d[38]), "=f"(d[39]), "=f"(d[40]), "=f"(d[41]), "=f"(d[42]), "=f"(d[43]), "=f"(d[44]), "=f"(d[45]), "=f"(d[46]), "=f"(d[47]),
      "=f"(d[48]), "=f"(d[49]), "=f"(d[50]), "=f"(d[51]), "=f"(d[52]), "=f"(d[53]), "=f"(d[54]), "=f"(d[55]), "=f"(d[56]), "=f"(d[57]), "=f"(d[58]), "=f"(d[59]), "=f"(d[60]), "=f"(d[61]), "=f"(d[62]), "=f"(d[63]),
      "=f"(d[64]), "=f"(d[65]), "=f"(d[66]), "=f"(d[67]), "=f"(d[68]), "=f"(d[69]), "=f"(d[70]), "=f"(d[71]), "=f"(d[72]), "=f"(d[73]), "=f"(d[74]), "=f"(d[75]), "=f"(d[76]), "=f"(d[77]), "=f"(d[78]), "=f"(d[79]),
      "=f"(d[80]), "=f"(d[81]), "=f"(d[82]), "=f"(d[83]), "=f"(d[84]), "=f"(d[85]), "=f"(d[86]), "=f"(d[87]), "=f"(d[88]), "=f"(d[89]), "=f"(d[90]), "=f"(d[91]), "=f"(d[92]), "=f"(d[93]), "=f"(d[94]), "=f"(d[95])
    : "r"(alo), "r"(blo));
}
__device__ __forceinline__ void wg_gemm_acc(float (&d)[96], uint32_t alo, uint32_t blo) {
  asm volatile("{\n.reg .pred p;\n.reg .b64 da, db;\nmov.b64 da, {%96, 0x40000040};\nmov.b64 db, {%97, 0x40000040};\nsetp.eq.b32 p, 0, 0;\n"
    "wgmma.mma_async.sync.aligned.m64n192k16.f32.bf16.bf16 {"
    "%0, %1, %2, %3, %4, %5, %6, %7, %8, %9, %10, %11, %12, %13, %14, %15, %16, %17, %18, %19, %20, %21, %22, %23, %24, %25, %26, %27, %28, %29, %30, %31, "
    "%32, %33, %34, %35, %36, %37, %38, %39, %40, %41, %42, %43, %44, %45, %46, %47, %48, %49, %50, %51, %52, %53, %54, %55, %56, %57, %58, %59, %60, %61, %62, %63, "
    "%64, %65, %66, %67, %68, %69, %70, %71, %72, %73, %74, %75, %76, %77, %78, %79, %80, %81, %82, %83, %84, %85, %86, %87, %88, %89, %90, %91, %92, %93, %94, %95}, "
    "da, db, p, 1, 1, 0, 1;\n}\n"
    : "+f"(d[0]), "+f"(d[1]), "+f"(d[2]), "+f"(d[3]), "+f"(d[4]), "+f"(d[5]), "+f"(d[6]), "+f"(d[7]), "+f"(d[8]), "+f"(d[9]), "+f"(d[10]), "+f"(d[11]), "+f"(d[12]), "+f"(d[13]), "+f"(d[14]), "+f"(d[15]),
      "+f"(d[16]), "+f"(d[17]), "+f"(d[18]), "+f"(d[19]), "+f"(d[20]), "+f"(d[21]), "+f"(d[22]), "+f"(d[23]), "+f"(d[24]), "+f"(d[25]), "+f"(d[26]), "+f"(d[27]), "+f"(d[28]), "+f"(d[29]), "+f"(d[30]), "+f"(d[31]),
      "+f"(d[32]), "+f"(d[33]), "+f"(d[34]), "+f"(d[35]), "+f"(d[36]), "+f"(d[37]), "+f"(d[38]), "+f"(d[39]), "+f"(d[40]), "+f"(d[41]), "+f"(d[42]), "+f"(d[43]), "+f"(d[44]), "+f"(d[45]), "+f"(d[46]), "+f"(d[47]),
      "+f"(d[48]), "+f"(d[49]), "+f"(d[50]), "+f"(d[51]), "+f"(d[52]), "+f"(d[53]), "+f"(d[54]), "+f"(d[55]), "+f"(d[56]), "+f"(d[57]), "+f"(d[58]), "+f"(d[59]), "+f"(d[60]), "+f"(d[61]), "+f"(d[62]), "+f"(d[63]),
      "+f"(d[64]), "+f"(d[65]), "+f"(d[66]), "+f"(d[67]), "+f"(d[68]), "+f"(d[69]), "+f"(d[70]), "+f"(d[71]), "+f"(d[72]), "+f"(d[73]), "+f"(d[74]), "+f"(d[75]), "+f"(d[76]), "+f"(d[77]), "+f"(d[78]), "+f"(d[79]),
      "+f"(d[80]), "+f"(d[81]), "+f"(d[82]), "+f"(d[83]), "+f"(d[84]), "+f"(d[85]), "+f"(d[86]), "+f"(d[87]), "+f"(d[88]), "+f"(d[89]), "+f"(d[90]), "+f"(d[91]), "+f"(d[92]), "+f"(d[93]), "+f"(d[94]), "+f"(d[95])
    : "r"(alo), "r"(blo));
}
__device__ __forceinline__ void wg_qk_init(float (&d)[64], uint32_t alo, uint32_t blo) {
  asm volatile("{\n.reg .pred p;\n.reg .b64 da, db;\nmov.b64 da, {%64, 0x40000040};\nmov.b64 db, {%65, 0x40000040};\nsetp.ne.b32 p, 0, 0;\n"
    "wgmma.mma_async.sync.aligned.m64n128k16.f32.bf16.bf16 {"
    "%0, %1, %2, %3, %4, %5, %6, %7, %8, %9, %10, %11, %12, %13, %14, %15, %16, %17, %18, %19, %20, %21, %22, %23, %24, %25, %26, %27, %28, %29, %30, %31, "
    "%32, %33, %34, %35, %36, %37, %38, %39, %40, %41, %42, %43, %44, %45, %46, %47, %48, %49, %50, %51, %52, %53, %54, %55, %56, %57, %58, %59, %60, %61, %62, %63}, "
    "da, db, p, 1, 1, 0, 0;\n}\n"
    : "=f"(d[0]), "=f"(d[1]), "=f"(d[2]), "=f"(d[3]), "=f"(d[4]), "=f"(d[5]), "=f"(d[6]), "=f"(d[7]), "=f"(d[8]), "=f"(d[9]), "=f"(d[10]), "=f"(d[11]), "=f"(d[12]), "=f"(d[13]), "=f"(d[14]), "=f"(d[15]),
      "=f"(d[16]), "=f"(d[17]), "=f"(d[18]), "=f"(d[19]), "=f"(d[20]), "=f"(d[21]), "=f"(d[22]), "=f"(d[23]), "=f"(d[24]), "=f"(d[25]), "=f"(d[26]), "=f"(d[27]), "=f"(d[28]), "=f"(d[29]), "=f"(d[30]), "=f"(d[31]),
      "=f"(d[32]), "=f"(d[33]), "=f"(d[34]), "=f"(d[35]), "=f"(d[36]), "=f"(d[37]), "=f"(d[38]), "=f"(d[39]), "=f"(d[40]), "=f"(d[41]), "=f"(d[42]), "=f"(d[43]), "=f"(d[44]), "=f"(d[45]), "=f"(d[46]), "=f"(d[47]),
      "=f"(d[48]), "=f"(d[49]), "=f"(d[50]), "=f"(d[51]), "=f"(d[52]), "=f"(d[53]), "=f"(d[54]), "=f"(d[55]), "=f"(d[56]), "=f"(d[57]), "=f"(d[58]), "=f"(d[59]), "=f"(d[60]), "=f"(d[61]), "=f"(d[62]), "=f"(d[63])
    : "r"(alo), "r"(blo));
}
__device__ __forceinline__ void wg_qk_acc(float (&d)[64], uint32_t alo, uint32_t blo) {
  asm volatile("{\n.reg .pred p;\n.reg .b64 da, db;\nmov.b64 da, {%64, 0x40000040};\nmov.b64 db, {%65, 0x40000040};\nsetp.eq.b32 p, 0, 0;\n"
    "wgmma.mma_async.sync.aligned.m64n128k16.f32.bf16.bf16 {"
    "%0, %1, %2, %3, %4, %5, %6, %7, %8, %9, %10, %11, %12, %13, %14, %15, %16, %17, %18, %19, %20, %21, %22, %23, %24, %25, %26, %27, %28, %29, %30, %31, "
    "%32, %33, %34, %35, %36, %37, %38, %39, %40, %41, %42, %43, %44, %45, %46, %47, %48, %49, %50, %51, %52, %53, %54, %55, %56, %57, %58, %59, %60, %61, %62, %63}, "
    "da, db, p, 1, 1, 0, 0;\n}\n"
    : "+f"(d[0]), "+f"(d[1]), "+f"(d[2]), "+f"(d[3]), "+f"(d[4]), "+f"(d[5]), "+f"(d[6]), "+f"(d[7]), "+f"(d[8]), "+f"(d[9]), "+f"(d[10]), "+f"(d[11]), "+f"(d[12]), "+f"(d[13]), "+f"(d[14]), "+f"(d[15]),
      "+f"(d[16]), "+f"(d[17]), "+f"(d[18]), "+f"(d[19]), "+f"(d[20]), "+f"(d[21]), "+f"(d[22]), "+f"(d[23]), "+f"(d[24]), "+f"(d[25]), "+f"(d[26]), "+f"(d[27]), "+f"(d[28]), "+f"(d[29]), "+f"(d[30]), "+f"(d[31]),
      "+f"(d[32]), "+f"(d[33]), "+f"(d[34]), "+f"(d[35]), "+f"(d[36]), "+f"(d[37]), "+f"(d[38]), "+f"(d[39]), "+f"(d[40]), "+f"(d[41]), "+f"(d[42]), "+f"(d[43]), "+f"(d[44]), "+f"(d[45]), "+f"(d[46]), "+f"(d[47]),
      "+f"(d[48]), "+f"(d[49]), "+f"(d[50]), "+f"(d[51]), "+f"(d[52]), "+f"(d[53]), "+f"(d[54]), "+f"(d[55]), "+f"(d[56]), "+f"(d[57]), "+f"(d[58]), "+f"(d[59]), "+f"(d[60]), "+f"(d[61]), "+f"(d[62]), "+f"(d[63])
    : "r"(alo), "r"(blo));
}
__device__ __forceinline__ void wg_qk64_init(float (&d)[64], uint32_t alo, uint32_t blo) {
  asm volatile("{\n.reg .pred p;\n.reg .b64 da, db;\nmov.b64 da, {%32, 0x40000040};\nmov.b64 db, {%33, 0x40000040};\nsetp.ne.b32 p, 0, 0;\n"
    "wgmma.mma_async.sync.aligned.m64n64k16.f32.bf16.bf16 {"
    "%0, %1, %2, %3, %4, %5, %6, %7, %8, %9, %10, %11, %12, %13, %14, %15, %16, %17, %18, %19, %20, %21, %22, %23, %24, %25, %26, %27, %28, %29, %30, %31}, "
    "da, db, p, 1, 1, 0, 0;\n}\n"
    : "=f"(d[0]), "=f"(d[1]), "=f"(d[2]), "=f"(d[3]), "=f"(d[4]), "=f"(d[5]), "=f"(d[6]), "=f"(d[7]), "=f"(d[8]), "=f"(d[9]), "=f"(d[10]), "=f"(d[11]), "=f"(d[12]), "=f"(d[13]), "=f"(d[14]), "=f"(d[15]),
      "=f"(d[16]), "=f"(d[17]), "=f"(d[18]), "=f"(d[19]), "=f"(d[20]), "=f"(d[21]), "=f"(d[22]), "=f"(d[23]), "=f"(d[24]), "=f"(d[25]), "=f"(d[26]), "=f"(d[27]), "=f"(d[28]), "=f"(d[29]), "=f"(d[30]), "=f"(d[31])
    : "r"(alo), "r"(blo));
}
__device__ __forceinline__ void wg_qk64_acc(float (&d)[64], uint32_t alo, uint32_t blo) {
  asm volatile("{\n.reg .pred p;\n.reg .b64 da, db;\nmov.b64 da, {%32, 0x40000040};\nmov.b64 db, {%33, 0x40000040};\nsetp.eq.b32 p, 0, 0;\n"
    "wgmma.mma_async.sync.aligned.m64n64k16.f32.bf16.bf16 {"
    "%0, %1, %2, %3, %4, %5, %6, %7, %8, %9, %10, %11, %12, %13, %14, %15, %16, %17, %18, %19, %20, %21, %22, %23, %24, %25, %26, %27, %28, %29, %30, %31}, "
    "da, db, p, 1, 1, 0, 0;\n}\n"
    : "+f"(d[0]), "+f"(d[1]), "+f"(d[2]), "+f"(d[3]), "+f"(d[4]), "+f"(d[5]), "+f"(d[6]), "+f"(d[7]), "+f"(d[8]), "+f"(d[9]), "+f"(d[10]), "+f"(d[11]), "+f"(d[12]), "+f"(d[13]), "+f"(d[14]), "+f"(d[15]),
      "+f"(d[16]), "+f"(d[17]), "+f"(d[18]), "+f"(d[19]), "+f"(d[20]), "+f"(d[21]), "+f"(d[22]), "+f"(d[23]), "+f"(d[24]), "+f"(d[25]), "+f"(d[26]), "+f"(d[27]), "+f"(d[28]), "+f"(d[29]), "+f"(d[30]), "+f"(d[31])
    : "r"(alo), "r"(blo));
}
__device__ __forceinline__ void wg_pv_init(float (&d)[64], const uint32_t* a, uint32_t blo) {
  asm volatile("{\n.reg .pred p;\n.reg .b64 da, db;\nmov.b64 db, {%68, 0x40000040};\nsetp.ne.b32 p, 0, 0;\n"
    "wgmma.mma_async.sync.aligned.m64n128k16.f32.bf16.bf16 {"
    "%0, %1, %2, %3, %4, %5, %6, %7, %8, %9, %10, %11, %12, %13, %14, %15, %16, %17, %18, %19, %20, %21, %22, %23, %24, %25, %26, %27, %28, %29, %30, %31, "
    "%32, %33, %34, %35, %36, %37, %38, %39, %40, %41, %42, %43, %44, %45, %46, %47, %48, %49, %50, %51, %52, %53, %54, %55, %56, %57, %58, %59, %60, %61, %62, %63}, "
    "{%64, %65, %66, %67}, db, p, 1, 1, 1;\n}\n"
    : "=f"(d[0]), "=f"(d[1]), "=f"(d[2]), "=f"(d[3]), "=f"(d[4]), "=f"(d[5]), "=f"(d[6]), "=f"(d[7]), "=f"(d[8]), "=f"(d[9]), "=f"(d[10]), "=f"(d[11]), "=f"(d[12]), "=f"(d[13]), "=f"(d[14]), "=f"(d[15]),
      "=f"(d[16]), "=f"(d[17]), "=f"(d[18]), "=f"(d[19]), "=f"(d[20]), "=f"(d[21]), "=f"(d[22]), "=f"(d[23]), "=f"(d[24]), "=f"(d[25]), "=f"(d[26]), "=f"(d[27]), "=f"(d[28]), "=f"(d[29]), "=f"(d[30]), "=f"(d[31]),
      "=f"(d[32]), "=f"(d[33]), "=f"(d[34]), "=f"(d[35]), "=f"(d[36]), "=f"(d[37]), "=f"(d[38]), "=f"(d[39]), "=f"(d[40]), "=f"(d[41]), "=f"(d[42]), "=f"(d[43]), "=f"(d[44]), "=f"(d[45]), "=f"(d[46]), "=f"(d[47]),
      "=f"(d[48]), "=f"(d[49]), "=f"(d[50]), "=f"(d[51]), "=f"(d[52]), "=f"(d[53]), "=f"(d[54]), "=f"(d[55]), "=f"(d[56]), "=f"(d[57]), "=f"(d[58]), "=f"(d[59]), "=f"(d[60]), "=f"(d[61]), "=f"(d[62]), "=f"(d[63])
    : "r"(a[0]), "r"(a[1]), "r"(a[2]), "r"(a[3]), "r"(blo));
}
__device__ __forceinline__ void wg_pv_acc(float (&d)[64], const uint32_t* a, uint32_t blo) {
  asm volatile("{\n.reg .pred p;\n.reg .b64 da, db;\nmov.b64 db, {%68, 0x40000040};\nsetp.eq.b32 p, 0, 0;\n"
    "wgmma.mma_async.sync.aligned.m64n128k16.f32.bf16.bf16 {"
    "%0, %1, %2, %3, %4, %5, %6, %7, %8, %9, %10, %11, %12, %13, %14, %15, %16, %17, %18, %19, %20, %21, %22, %23, %24, %25, %26, %27, %28, %29, %30, %31, "
    "%32, %33, %34, %35, %36, %37, %38, %39, %40, %41, %42, %43, %44, %45, %46, %47, %48, %49, %50, %51, %52, %53, %54, %55, %56, %57, %58, %59, %60, %61, %62, %63}, "
    "{%64, %65, %66, %67}, db, p, 1, 1, 1;\n}\n"
    : "+f"(d[0]), "+f"(d[1]), "+f"(d[2]), "+f"(d[3]), "+f"(d[4]), "+f"(d[5]), "+f"(d[6]), "+f"(d[7]), "+f"(d[8]), "+f"(d[9]), "+f"(d[10]), "+f"(d[11]), "+f"(d[12]), "+f"(d[13]), "+f"(d[14]), "+f"(d[15]),
      "+f"(d[16]), "+f"(d[17]), "+f"(d[18]), "+f"(d[19]), "+f"(d[20]), "+f"(d[21]), "+f"(d[22]), "+f"(d[23]), "+f"(d[24]), "+f"(d[25]), "+f"(d[26]), "+f"(d[27]), "+f"(d[28]), "+f"(d[29]), "+f"(d[30]), "+f"(d[31]),
      "+f"(d[32]), "+f"(d[33]), "+f"(d[34]), "+f"(d[35]), "+f"(d[36]), "+f"(d[37]), "+f"(d[38]), "+f"(d[39]), "+f"(d[40]), "+f"(d[41]), "+f"(d[42]), "+f"(d[43]), "+f"(d[44]), "+f"(d[45]), "+f"(d[46]), "+f"(d[47]),
      "+f"(d[48]), "+f"(d[49]), "+f"(d[50]), "+f"(d[51]), "+f"(d[52]), "+f"(d[53]), "+f"(d[54]), "+f"(d[55]), "+f"(d[56]), "+f"(d[57]), "+f"(d[58]), "+f"(d[59]), "+f"(d[60]), "+f"(d[61]), "+f"(d[62]), "+f"(d[63])
    : "r"(a[0]), "r"(a[1]), "r"(a[2]), "r"(a[3]), "r"(blo));
}

struct Cons {
  uint32_t sb;
  uint32_t rel;
  uint32_t p0, p1;
  uint32_t lead, round, fpar;
};

template <uint32_t OFF, uint32_t GROUP> __device__ __forceinline__ void tile_write(const uint32_t (&pk)[32], uint32_t base) {
  const uint32_t lane = threadIdx.x & 31, wq = (threadIdx.x >> 5) & 3;
  const uint32_t a = base + (wq * 16 + (lane & 15)) * 128 + (((lane >> 4) ^ (lane & 7)) << 4);
#define TW(j) stmatrix_x4<OFF + (j >> 2) * GROUP>(a ^ ((j & 3) * 32), pk[4 * j + 0], pk[4 * j + 1], pk[4 * j + 2], pk[4 * j + 3])
  TW(0); TW(1); TW(2); TW(3); TW(4); TW(5); TW(6); TW(7);
#undef TW
}
template <uint32_t OFF, uint32_t GROUP, int A0> __device__ __forceinline__ void tile_pack_write(const float (&acc)[128], uint32_t (&pk)[32], uint32_t base) {
  const uint32_t lane = threadIdx.x & 31, wq = (threadIdx.x >> 5) & 3;
  const uint32_t a = base + (wq * 16 + (lane & 15)) * 128 + (((lane >> 4) ^ (lane & 7)) << 4);
#define TW(j) \
  pk[4 * j + 0] = v_pack(acc[A0 + 8 * j + 0], acc[A0 + 8 * j + 1]); pk[4 * j + 1] = v_pack(acc[A0 + 8 * j + 2], acc[A0 + 8 * j + 3]); \
  pk[4 * j + 2] = v_pack(acc[A0 + 8 * j + 4], acc[A0 + 8 * j + 5]); pk[4 * j + 3] = v_pack(acc[A0 + 8 * j + 6], acc[A0 + 8 * j + 7]); \
  stmatrix_x4<OFF + (j >> 2) * GROUP>(a ^ ((j & 3) * 32), pk[4 * j + 0], pk[4 * j + 1], pk[4 * j + 2], pk[4 * j + 3])
  TW(0); TW(1); TW(2); TW(3); TW(4); TW(5); TW(6); TW(7);
#undef TW
}
__device__ __forceinline__ void stage_write(const uint32_t (&pk)[32], int w, const Cons& cs) {
  mbar_wait<BAR(B_STGE)>(cs.sb + w * 8, (cs.round & 1) ^ 1);
  tile_write<OFF_STG, 8192>(pk, cs.sb + w * 16384);
}
__device__ __forceinline__ void stage_publish(int w, Cons& cs) {
  fence_async_smem();
  __syncwarp();
  mbar_arrive_if<BAR(B_STGF)>(cs.sb + w * 8, (threadIdx.x & 31) == 0);
  cs.round++;
}

template <int ST, bool INIT, int NA> __device__ __forceinline__ void g_issue(float (&acc)[NA], uint32_t wa) {
  constexpr uint32_t A = dlo(OFF_A + ST * 16384, 16), B = dlo(OFF_B + ST * 32768, NA == 128 ? 8192 : 4096);
  wg_fence();
  if (INIT) wg_gemm_init(acc, A + wa, B); else wg_gemm_acc(acc, A + wa, B);
#pragma unroll
  for (int kk = 1; kk < 4; kk++) wg_gemm_acc(acc, A + wa + kk * 2, B + (NA == 128 ? kk * 128 : (kk >> 1) * 768 + (kk & 1) * 128));
  wg_commit();
}
template <int NA>
__device__ __forceinline__ uint32_t gemm_tile(float (&acc)[NA], int nk4, int idx, int w, Cons& cs, uint32_t pend, const uint32_t (&pkA)[32], const uint32_t (&pkB)[32]) {
  const uint32_t wa = w * 512, sb = cs.sb, rel = cs.rel;
  constexpr int SA = NA == 128 ? STGA : STGAL, SBB = NA == 128 ? STGB : STGBL;
#define HOOK(n) \
  if (n == LPUBP && (pend & 8)) stage_publish(w, cs); \
  if (LHS && n == 0 && (pend & 16) && w == 0) bar_sync(5, 256); \
  if (n == SA && (pend & 1)) stage_write(pkA, w, cs); \
  if (n == SA + PUBD && (pend & 1)) { stage_publish(w, cs); pend &= 6; } \
  if (n == SBB && (pend & 2)) { stage_write(pkB, w, cs); pend = 4; } \
  if (n == SBB + PUBD && (pend & 4)) { stage_publish(w, cs); pend = 0; }
  mbar_wait<BAR(B_FULL + 0)>(sb, cs.p0);
  g_issue<0, true>(acc, wa);
  HOOK(0);
  mbar_wait<BAR(B_FULL + 1)>(sb, cs.p1);
  g_issue<1, false>(acc, wa);
  HOOK(2);
  wg_wait<1>(); T4K();
  mbar_arrive_cl<BAR(B_EMPTY + 0)>(rel);
  HOOK(3);
  mbar_wait<BAR(B_FULL + 2)>(sb, cs.p0);
  g_issue<2, false>(acc, wa);
  HOOK(4);
  wg_wait<1>(); T4K();
  mbar_arrive_cl<BAR(B_EMPTY + 1)>(rel);
  HOOK(5);
  mbar_wait<BAR(B_FULL + 3)>(sb, cs.p1);
  g_issue<3, false>(acc, wa);
  HOOK(6);
  const uint32_t ncode = item(sb, idx + 1);
  wg_wait<1>(); T4K();
  mbar_arrive_cl<BAR(B_EMPTY + 2)>(rel);
  HOOK(7);
  cs.p0 ^= 1; cs.p1 ^= 1;
  const bool final_tile = (ncode >> 9) == K_END;
  constexpr int LD = NA == 128 ? LEADN : LEADL;
#pragma unroll 1
  for (int q = 1; q < nk4; q++) {
    const bool tail = q == nk4 - 1;
    mbar_wait<BAR(B_FULL + 0)>(sb, cs.p0);
    g_issue<0, false>(acc, wa);
    HOOK(8);
    wg_wait<1>(); T4K();
    mbar_arrive_cl<BAR(B_EMPTY + 3)>(rel);
    HOOK(9);
    mbar_wait<BAR(B_FULL + 1)>(sb, cs.p1);
    uint32_t rel0 = rel;
    if (LEADF == 3 && NA == 128 && final_tile && tail && w == 1) {
      wg_wait<0>();
      mbar_arrive_cl<BAR(B_EMPTY + 0)>(rel);
      rel0 = 0;
      mbar_wait<BAR(B_LEAD)>(sb, cs.lead);
    }
    g_issue<1, false>(acc, wa);
    HOOK(10);
    wg_wait<1>(); T4K();
    mbar_arrive_cl<BAR(B_EMPTY + 0)>(rel0);
    HOOK(11);
    mbar_wait<BAR(B_FULL + 2)>(sb, cs.p0);
    uint32_t rel1 = rel;
    if (LD == 2 && tail && w == 1 && !(LEADF == 3 && NA == 128 && final_tile)) {
      if (EREL) { wg_wait<0>(); mbar_arrive_cl<BAR(B_EMPTY + 1)>(rel); rel1 = 0; }
      mbar_wait<BAR(B_LEAD)>(sb, cs.lead);
    }
    g_issue<2, false>(acc, wa);
    HOOK(12);
    wg_wait<1>(); T4K();
    mbar_arrive_cl<BAR(B_EMPTY + 1)>(rel1);
    HOOK(13);
    mbar_wait<BAR(B_FULL + 3)>(sb, cs.p1);
    if (LD == 1 && tail && w == 1) mbar_wait<BAR(B_LEAD)>(sb, cs.lead);
    g_issue<3, false>(acc, wa);
    mbar_arrive_if<BAR(B_LEAD)>(sb, tail && threadIdx.x == 128);
    HOOK(14);
    wg_wait<1>(); T4K();
    mbar_arrive_cl<BAR(B_EMPTY + 2)>(rel);
    cs.p0 ^= 1; cs.p1 ^= 1;
  }
#undef HOOK
  cs.lead ^= 1;
  wg_wait<0>();
  fence_regs(acc);
  T4Q(__float_as_uint(acc[0]));
  mbar_arrive_cl<BAR(B_EMPTY + 3)>(rel);
  return ncode;
}

__device__ __forceinline__ void local_probs(bool first, const float (&S)[3][4], uint32_t (&pb)[4]) {
  const int lane = threadIdx.x & 31, g = lane >> 2, t = lane & 3;
  const bool c0 = 2 * t > g, c1 = 2 * t + 1 > g;
  float x0 = c0 ? S[0][0] : S[1][0], x1 = c1 ? S[0][1] : S[1][1], y0 = c0 ? S[1][2] : S[2][2], y1 = c1 ? S[1][3] : S[2][3];
  if (first && c0) x0 = -INFINITY;
  if (first && c1) x1 = -INFINITY;
  float m0 = fmaxf(x0, x1), m1 = fmaxf(y0, y1);
  if (LSH & 1) {
    m0 = fmaxf(fmaxf(m0, __shfl_xor_sync(0xffffffffu, m0, 1)), fmaxf(__shfl_xor_sync(0xffffffffu, m0, 2), __shfl_xor_sync(0xffffffffu, m0, 3)));
    m1 = fmaxf(fmaxf(m1, __shfl_xor_sync(0xffffffffu, m1, 1)), fmaxf(__shfl_xor_sync(0xffffffffu, m1, 2), __shfl_xor_sync(0xffffffffu, m1, 3)));
  } else {
    m0 = fmaxf(m0, __shfl_xor_sync(0xffffffffu, m0, 1)); m1 = fmaxf(m1, __shfl_xor_sync(0xffffffffu, m1, 1));
    m0 = fmaxf(m0, __shfl_xor_sync(0xffffffffu, m0, 2)); m1 = fmaxf(m1, __shfl_xor_sync(0xffffffffu, m1, 2));
  }
  constexpr float C = 0.17677669529663687f * 1.4426950408889634f;
  const float b0 = -m0 * C, b1 = -m1 * C;
  x0 = ex2(fmaf(x0, C, b0)); x1 = ex2(fmaf(x1, C, b0)); y0 = ex2(fmaf(y0, C, b1)); y1 = ex2(fmaf(y1, C, b1));
  auto qs = [](float v) { return (LSH & 2) ? (v + __shfl_xor_sync(0xffffffffu, v, 1)) + (__shfl_xor_sync(0xffffffffu, v, 2) + __shfl_xor_sync(0xffffffffu, v, 3)) : quad_sum(v); };
  const float l0 = rcp(qs(x0 + x1)), l1 = rcp(qs(y0 + y1));
  const uint32_t px = pack_bf16(x0 * l0, x1 * l0), py = pack_bf16(y0 * l1, y1 * l1);
  const uint32_t m = (c0 ? 0xffffu : 0u) | (c1 ? 0xffff0000u : 0u);
  pb[0] = px & m; pb[1] = px & ~m; pb[2] = py & m; pb[3] = py & ~m;
}
__device__ __forceinline__ void local_epilogue(const float (&acc)[96], uint32_t code, int w, Cons& cs) {
  const uint32_t lane = threadIdx.x & 31, wq = (threadIdx.x >> 5) & 3, cw = w * 4 + wq;
  const bool has_halo = (code & 15) != 0;
  const uint32_t hpar = cs.fpar >> 1;
  cs.fpar ^= has_halo ? 2 : 0;
  uint32_t kf[3][8], vt[3][8];
#pragma unroll
  for (int j = 0; j < 8; j++) { kf[2][j] = pack_bf16(acc[32 + 4 * j + 2], acc[32 + 4 * j + 3]); vt[2][j] = transpose8(pack_bf16(acc[64 + 4 * j + 2], acc[64 + 4 * j + 3])); }
  const uint32_t xa = cs.sb + OFF_STG + 8192 + w * 16384 + wq * 2048 + lane * 16;
  mbar_wait<BAR(B_STGE)>(cs.sb + w * 8, (cs.round & 1) ^ 1);
  sts128<0>(xa, &kf[2][0]); sts128<512>(xa, &kf[2][4]); sts128<1024>(xa, &vt[2][0]); sts128<1536>(xa, &vt[2][4]);
  if (cw == 3) bar_arrive(4, 160);
  uint32_t q[8][2];
#pragma unroll
  for (int j = 0; j < 8; j++) {
    q[j][0] = pack_bf16(acc[4 * j], acc[4 * j + 1]); q[j][1] = pack_bf16(acc[4 * j + 2], acc[4 * j + 3]);
    kf[1][j] = pack_bf16(acc[32 + 4 * j], acc[32 + 4 * j + 1]); vt[1][j] = transpose8(pack_bf16(acc[64 + 4 * j], acc[64 + 4 * j + 1]));
  }
  bar_sync(3 + w, 128 + 32 * w);
  uint32_t ra = xa - (wq == 0 ? 16384 - 3 * 2048 : 2048);
  if (cw == 0) {
    ra = has_halo ? cs.sb + OFF_HALO + lane * 16 : xa;
    if (has_halo) mbar_wait<BAR(B_HFULL)>(cs.sb, hpar);
  }
  lds128<0>(&kf[0][0], ra); lds128<512>(&kf[0][4], ra); lds128<1024>(&vt[0][0], ra); lds128<1536>(&vt[0][4], ra);
  float z;
  asm volatile("ld.shared.f32 %0, [%1+%2];" : "=f"(z) : "r"(cs.sb), "n"(OFF_FILLS + 4) : "memory");
  float S[2][3][4];
#pragma unroll
  for (int u = 0; u < 2; u++)
#pragma unroll
    for (int n = 0; n < 3; n++) mma16816z(S[u][n], q[4 * u][0], q[4 * u][1], q[4 * u + 1][0], q[4 * u + 1][1], kf[n][4 * u], kf[n][4 * u + 1], z);
#pragma unroll
  for (int u = 0; u < 2; u++)
#pragma unroll
    for (int n = 0; n < 3; n++) mma16816(S[u][n], q[4 * u + 2][0], q[4 * u + 2][1], q[4 * u + 3][0], q[4 * u + 3][1], kf[n][4 * u + 2], kf[n][4 * u + 3]);
  uint32_t pb[2][4];
#pragma unroll
  for (int u = 0; u < 2; u++) local_probs(cw == 0 && !has_halo, S[u], pb[u]);
  const uint32_t oa = cs.sb + w * 16384 + (wq * 16 + (lane & 7)) * 128 + (((lane >> 3) ^ (lane & 7)) << 4);
#pragma unroll
  for (int u = 0; u < 2; u++)
#pragma unroll
    for (int hf = 0; hf < 2; hf++) {
      float O[2][4];
#pragma unroll
      for (int mt = 0; mt < 2; mt++) {
        O[mt][0] = O[mt][1] = O[mt][2] = O[mt][3] = 0.f;
        mma16816(O[mt], vt[hf][4 * u + 2 * mt], vt[hf][4 * u + 2 * mt + 1], vt[hf + 1][4 * u + 2 * mt], vt[hf + 1][4 * u + 2 * mt + 1], pb[u][2 * hf], pb[u][2 * hf + 1]);
      }
      const uint32_t o0 = pack_bf16(O[0][0], O[0][1]), o1 = pack_bf16(O[0][2], O[0][3]), o2 = pack_bf16(O[1][0], O[1][1]), o3 = pack_bf16(O[1][2], O[1][3]);
      if (hf == 0) stmatrix_x4_trans<OFF_STG>(oa ^ (u * 64), o0, o1, o2, o3); else stmatrix_x4_trans<OFF_STG + 1024>(oa ^ (u * 64), o0, o1, o2, o3);
    }
  mbar_arrive_if<BAR(B_HEMPTY)>(cs.sb, has_halo && threadIdx.x == 128);
}

constexpr float SCALE_LOG2 = 0.08838834764831845f * 1.4426950408889634f;
#define SUM_LO 8.673617379884035e-19f
#define SUM_HI 1152921504606846976.f
template <int J0> __device__ __forceinline__ void causal_mask(float (&S)[64], int r) {
#pragma unroll
  for (int j = 0; j < 8; j++) {
    if (8 * j > r) S[4 * (J0 + j) + 0] = -INFINITY;
    if (8 * j + 1 > r) S[4 * (J0 + j) + 1] = -INFINITY;
    if (8 * j - 8 > r) S[4 * (J0 + j) + 2] = -INFINITY;
    if (8 * j - 7 > r) S[4 * (J0 + j) + 3] = -INFINITY;
  }
}
__device__ __forceinline__ float v_ex2(float x) { float y; asm volatile("ex2.approx.ftz.f32 %0, %1;" : "=f"(y) : "f"(x)); return y; }
__device__ __forceinline__ float v_add(float a, float b) { float y; asm volatile("add.f32 %0, %1, %2;" : "=f"(y) : "f"(a), "f"(b)); return y; }
__device__ __forceinline__ float v_mul(float a, float b) { float y; asm volatile("mul.f32 %0, %1, %2;" : "=f"(y) : "f"(a), "f"(b)); return y; }
template <int MJ> __device__ __forceinline__ float exp_el(float x, int j, int e, int r) {
  float p = v_ex2(x);
  if (j >= MJ) asm volatile("{\n.reg .pred q;\nsetp.lt.s32 q, %1, %2;\n@q mov.b32 %0, 0f00000000;\n}\n" : "+f"(p) : "r"(r), "r"(8 * (j - MJ) + (e & 1) - 4 * (e & 2)));
  return p;
}
template <int J0, int J1, int MJ = 16> __device__ __forceinline__ void exp_inplace(float (&S)[64], float& l0, float& l1, int r = 0) {
#pragma unroll
  for (int j = J0; j < J1; j++) {
#pragma unroll
    for (int e = 0; e < 4; e++) S[4 * j + e] = exp_el<MJ>(S[4 * j + e], j, e, r);
    l0 = v_add(l0, S[4 * j + 0]); l1 = v_add(l1, S[4 * j + 2]); l0 = v_add(l0, S[4 * j + 1]); l1 = v_add(l1, S[4 * j + 3]);
  }
}
template <int JS, int MJ, bool OUT>
__device__ __forceinline__ void exp_pack(float (&S)[64], uint32_t (&P)[32], float& l0, float& l1, int r, const float (&O)[64], float a0, float a1, uint32_t (&pk)[32]) {
#pragma unroll
  for (int j = JS; j < 16; j++) {
    const float p0 = exp_el<MJ>(S[4 * j + 0], j, 0, r), p1 = exp_el<MJ>(S[4 * j + 1], j, 1, r), p2 = exp_el<MJ>(S[4 * j + 2], j, 2, r), p3 = exp_el<MJ>(S[4 * j + 3], j, 3, r);
#pragma unroll
    for (int k = (j - JS) * JS / (16 - JS); k < (j + 1 - JS) * JS / (16 - JS); k++) { P[2 * k] = v_pack(S[4 * k + 0], S[4 * k + 1]); P[2 * k + 1] = v_pack(S[4 * k + 2], S[4 * k + 3]); }
    if (OUT) {
#pragma unroll
      for (int k = (j - JS) * 16 / (16 - JS); k < (j + 1 - JS) * 16 / (16 - JS); k++) {
        pk[2 * k] = v_pack(v_mul(O[4 * k + 0], a0), v_mul(O[4 * k + 1], a0)); pk[2 * k + 1] = v_pack(v_mul(O[4 * k + 2], a1), v_mul(O[4 * k + 3], a1));
      }
    }
    l0 = v_add(l0, p0); l1 = v_add(l1, p2); l0 = v_add(l0, p1); l1 = v_add(l1, p3);
    P[2 * j] = v_pack(p0, p1); P[2 * j + 1] = v_pack(p2, p3);
  }
}
__device__ __forceinline__ void pin_after(float a, float b) {
  asm volatile("{\n.reg .pred p;\nsetp.eq.u32 p, %0, 0xffffffff;\n@p st.shared.b32 [%1], %1;\n}\n" ::"r"(__float_as_uint(a)), "r"(__float_as_uint(b)) : "memory");
}
template <bool HALF> __device__ __forceinline__ void issue_qk(float (&S)[64], uint32_t qlo, uint32_t klo) {
  wg_fence();
  if (HALF) wg_qk64_init(S, qlo, klo); else wg_qk_init(S, qlo, klo);
#pragma unroll
  for (int kk = 1; kk < 8; kk++) {
    const uint32_t off = ((kk >> 2) * 16384 + (kk & 3) * 32) >> 4;
    if (HALF) wg_qk64_acc(S, qlo + off, klo + off); else wg_qk_acc(S, qlo + off, klo + off);
  }
  wg_commit();
}
template <int NK, int ACC> __device__ __forceinline__ void issue_pv(float (&O)[64], const uint32_t (&P)[32], uint32_t vlo) {
  wg_fence();
  if (ACC) wg_pv_acc(O, &P[0], vlo); else wg_pv_init(O, &P[0], vlo);
#pragma unroll
  for (int kk = 1; kk < NK; kk++) wg_pv_acc(O, &P[4 * kk], vlo + kk * 128);
  wg_commit();
}
__device__ __forceinline__ uint32_t row_norm(float l0, float l1, float& a0, float& a1) {
  const float q0 = quad_sum(l0), q1 = quad_sum(l1);
  a0 = rcp(q0); a1 = rcp(q1);
  return __reduce_or_sync(0xffffffffu, (q0 >= SUM_LO && q0 <= SUM_HI && q1 >= SUM_LO && q1 <= SUM_HI) ? 0u : 1u);
}
__device__ __forceinline__ void slow_item(float (&O)[64], float& a0, float& a1, int head, int tile, uint32_t qbase, int w) {
  const int lane = threadIdx.x & 31, g = lane >> 2, t = lane & 3;
  const int rw = w * 64 + (int)__reduce_or_sync(0xffffffffu, (threadIdx.x >> 1) & 48);
  const int row0 = tile * 128 + rw;
  const uint32_t qa_ = qbase + (rw + g) * 128 + ((t ^ g) << 4);
  const __nv_bfloat16* kp = g_kv + ((size_t)head * SEQ + g) * 256 + 8 * t;
  const __nv_bfloat16* vp = g_kv + ((size_t)head * SEQ + 2 * t) * 256 + 128 + g;
  float m0 = -INFINITY, m1 = -INFINITY, l0 = 0.f, l1 = 0.f;
#pragma unroll
  for (int i = 0; i < 64; i++) O[i] = 0.f;
#pragma unroll 1
  for (int key0 = 0; key0 < row0 + 16; key0 += 16) {
    float c[2][4] = {{0.f, 0.f, 0.f, 0.f}, {0.f, 0.f, 0.f, 0.f}};
#pragma unroll 1
    for (int cc = 0; cc < 4; cc++) {
      uint32_t qa[4], qb[4];
      const uint32_t a = (qa_ ^ ((cc & 1) * 64)) + (cc >> 1) * 16384;
      lds128<0>(qa, a); lds128<1024>(qb, a);
#pragma unroll
      for (int n = 0; n < 2; n++) {
        const uint4 kf = ldg128(kp + (size_t)(key0 + 8 * n) * 256 + cc * 32);
        mma16816(c[n], qa[0], qb[0], qa[1], qb[1], kf.x, kf.y);
        mma16816(c[n], qa[2], qb[2], qa[3], qb[3], kf.z, kf.w);
      }
    }
#pragma unroll
    for (int n = 0; n < 2; n++)
#pragma unroll
      for (int e = 0; e < 4; e++)
        if (key0 + 8 * n + 2 * t + (e & 1) > row0 + g + (e >> 1) * 8) c[n][e] = -INFINITY;
    float x0 = fmaxf(fmaxf(c[0][0], c[0][1]), fmaxf(c[1][0], c[1][1])), x1 = fmaxf(fmaxf(c[0][2], c[0][3]), fmaxf(c[1][2], c[1][3]));
    x0 = fmaxf(x0, __shfl_xor_sync(0xffffffffu, x0, 1)); x1 = fmaxf(x1, __shfl_xor_sync(0xffffffffu, x1, 1));
    x0 = fmaxf(x0, __shfl_xor_sync(0xffffffffu, x0, 2)); x1 = fmaxf(x1, __shfl_xor_sync(0xffffffffu, x1, 2));
    const float n0 = fmaxf(m0, x0), n1 = fmaxf(m1, x1);
    const float r0 = ex2(m0 - n0), r1 = ex2(m1 - n1);
    m0 = n0; m1 = n1;
#pragma unroll
    for (int n = 0; n < 2; n++) { c[n][0] = ex2(c[n][0] - n0); c[n][1] = ex2(c[n][1] - n0); c[n][2] = ex2(c[n][2] - n1); c[n][3] = ex2(c[n][3] - n1); }
    l0 = l0 * r0 + ((c[0][0] + c[0][1]) + (c[1][0] + c[1][1]));
    l1 = l1 * r1 + ((c[0][2] + c[0][3]) + (c[1][2] + c[1][3]));
    const uint32_t p0 = pack_bf16(c[0][0], c[0][1]), p1 = pack_bf16(c[0][2], c[0][3]), p2 = pack_bf16(c[1][0], c[1][1]), p3 = pack_bf16(c[1][2], c[1][3]);
#pragma unroll
    for (int j = 0; j < 16; j++) {
      const __nv_bfloat16* v = vp + (size_t)key0 * 256 + j * 8;
      const uint32_t b0 = ldg16(v) | (ldg16(v + 256) << 16), b1 = ldg16(v + 8 * 256) | (ldg16(v + 9 * 256) << 16);
      float o[4] = {O[4 * j] * r0, O[4 * j + 1] * r0, O[4 * j + 2] * r1, O[4 * j + 3] * r1};
      mma16816(o, p0, p1, p2, p3, b0, b1);
      O[4 * j] = o[0]; O[4 * j + 1] = o[1]; O[4 * j + 2] = o[2]; O[4 * j + 3] = o[3];
    }
  }
  a0 = rcp(quad_sum(l0)); a1 = rcp(quad_sum(l1));
}
__device__ __forceinline__ void att_output(const float (&O)[64], float a0, float a1, uint32_t (&pk)[32]) {
#pragma unroll
  for (int k = 0; k < 16; k++) { pk[2 * k] = v_pack(v_mul(O[4 * k + 0], a0), v_mul(O[4 * k + 1], a0)); pk[2 * k + 1] = v_pack(v_mul(O[4 * k + 2], a1), v_mul(O[4 * k + 3], a1)); }
}
template <int J1> __device__ __forceinline__ void exp_stage(float (&S)[64], float& l0, float& l1, const uint32_t (&P)[32], int w, const Cons& cs) {
  const uint32_t lane = threadIdx.x & 31, wq = (threadIdx.x >> 5) & 3;
  const uint32_t a = cs.sb + w * 16384 + (wq * 16 + (lane & 15)) * 128 + (((lane >> 4) ^ (lane & 7)) << 4);
#define ES(c) \
  exp_inplace<c * J1 / 8, (c + 1) * J1 / 8>(S, l0, l1); \
  stmatrix_x4_after<OFF_STG + (c >> 2) * 8192>(a ^ ((c & 3) * 32), P[4 * c + 0], P[4 * c + 1], P[4 * c + 2], P[4 * c + 3], (c & 1) ? l1 : l0)
  ES(0); ES(1); ES(2); ES(3); ES(4); ES(5); ES(6); ES(7);
#undef ES
}
struct Att { uint32_t qd, kd, vd, c8, cb, xc, xp, pub; };
__device__ __forceinline__ void att_advance(Att& t) {
  constexpr uint32_t SLOT = 32768 >> 4;
  t.kd ^= SLOT; t.vd ^= SLOT; t.c8 ^= 8; t.cb ^= 8;
  const uint32_t x = t.xc; t.xc = t.xp ^ 1; t.xp = x;
}
template <bool SECOND>
__device__ __forceinline__ uint32_t diag_step(float (&S)[64], float (&O)[64], uint32_t (&P)[32], uint32_t (&pk)[32], float& l0, float& l1, uint32_t& unsafe, Att& t, int r, int w, Cons& cs) {
  constexpr int JD = SECOND ? JDIAG2 : JDIAG;
  const uint32_t sb = cs.sb;
  float a0 = 0.f, a1 = 0.f;
  uint32_t ready;
  auto sums = [&]() {
    unsafe = row_norm(l0, l1, a0, a1);
    mbar_arrive_if<BAR(B_QEMPTY)>(sb, (threadIdx.x & 31) == 0 && !unsafe);
    l0 = l1 = 0.f;
  };
  auto look_ahead = [&]() { ready = mbar_test<BAR(B_FULL)>(t.cb, t.xc); if (!SECOND) ready &= mbar_test<BAR(B_QFULL)>(sb, cs.fpar & 1); };
  if (w == 1) {
    bar_sync(2, 256);
    issue_qk<false>(S, t.qd, t.kd);
    if (YIELD2 && SECOND) bar_arrive(5, 256);
    if (!SECOND && t.pub) { stage_publish(w, cs); t.pub = 0; }
    if (SECOND && SUMPOS == 0) sums();
    mbar_wait<BAR(B_FULL + 2)>(t.cb ^ 8, t.xp);
    issue_pv<8, 1>(O, P, t.vd);
    bar_arrive(1, 256);
    att_advance(t);
    wg_wait<1>();
    fence_regs(S);
    T4Q(__float_as_uint(S[0]));
    mbar_arrive_cl<BAR(B_EMPTY)>(cs.rel, t.c8 ^ 8);
    if (SECOND && SUMPOS == 1) sums();
    exp_inplace<0, JD, 8>(S, l0, l1, r);
    pin_after(l0, l1);
    wg_wait<0>();
    fence_regs(O);
    fence_regs(P);
    mbar_arrive_cl<BAR(B_EMPTY + 2)>(cs.rel, t.c8);
    look_ahead();
    exp_pack<JD, 8, SECOND>(S, P, l0, l1, r, O, a0, a1, pk);
  } else {
    bar_sync(1, 256);
    issue_qk<true>(S, t.qd, t.kd);
    mbar_wait<BAR(B_FULL + 2)>(t.cb ^ 8, t.xp);
    issue_pv<SECOND ? 4 : 8, 1>(O, P, t.vd);
    bar_arrive(2, 256);
    if (!SECOND && t.pub) { stage_publish(w, cs); t.pub = 0; }
    att_advance(t);
    if (SECOND) {
      sums();
      if (YIELD2) bar_sync(5, 256);
    }
    wg_wait<1>();
    fence_regs<0, 32>(S);
    T4Q(__float_as_uint(S[0]));
    mbar_arrive_cl<BAR(B_EMPTY)>(cs.rel, t.c8 ^ 8);
    exp_inplace<0, 8, 0>(S, l0, l1, r);
    pin_after(l0, l1);
    wg_wait<0>();
    fence_regs(O);
    fence_regs(P);
    mbar_arrive_cl<BAR(B_EMPTY + 2)>(cs.rel, t.c8);
    look_ahead();
#pragma unroll
    for (int k = 0; k < 8; k++) { P[2 * k] = v_pack(S[4 * k + 0], S[4 * k + 1]); P[2 * k + 1] = v_pack(S[4 * k + 2], S[4 * k + 3]); }
    if (SECOND) att_output(O, a0, a1, pk);
  }
  return __reduce_or_sync(0xffffffffu, ready ^ 1);
}
__device__ __forceinline__ void attention(uint32_t code, uint32_t rank, int idx, int w, Cons& cs, uint32_t (&P)[32], uint32_t (&pk)[32]) {
  const int lane = threadIdx.x & 31, wq = (threadIdx.x >> 5) & 3;
  constexpr int JS = JSPLIT, JE = JEDGE;
  const uint32_t sb = cs.sb;
  const int y = (code & 15) * 2 + rank;
  const int r = wq * 16 + (lane >> 2) - 2 * (lane & 3);
  float O[64], S[64];
  float l0 = 0.f, l1 = 0.f;
  Att t = {dlo(OFF_A, 16) + w * 512, dlo(OFF_B, 16), dlo(OFF_B + 98304, 16384), 0, sb, cs.p0, cs.p1, 0};
  uint32_t unsafe = 0, late;
  int ns;
  auto stage_step = [&](bool signal) {
    att_advance(t);
    t.pub = 1;
    wg_wait<1>();
    fence_regs(S);
    T4Q(__float_as_uint(S[0]));
    mbar_arrive_cl<BAR(B_EMPTY)>(cs.rel, t.c8 ^ 8);
    exp_stage<JE>(S, l0, l1, pk, w, cs);
    pin_after(l0, l1);
    if (signal) bar_arrive(5, 256);
    wg_wait<0>();
    fence_regs(O);
    fence_regs(P);
    mbar_arrive_cl<BAR(B_EMPTY + 2)>(cs.rel, t.c8);
    const uint32_t ready = mbar_test<BAR(B_FULL)>(t.cb, t.xc);
    exp_pack<JE, 16, false>(S, P, l0, l1, r, O, 0.f, 0.f, pk);
    late = __reduce_or_sync(0xffffffffu, ready ^ 1);
  };
  bar_sync(3 - w, 128 + 128 * w);
  if (y >= 2) {
    issue_qk<false>(O, t.qd, dlo(OFF_B + 32768, 16));
    mbar_wait<BAR(B_FULL)>(sb, t.xc);
    issue_qk<false>(S, t.qd, dlo(OFF_B, 16));
    bar_arrive(1 + (w ^ 1), 256);
    T4X(0);
    wg_wait<1>();
    fence_regs(O);
    T4Q(0);
    mbar_arrive_cl<BAR(B_EMPTY + 1)>(cs.rel);
    exp_inplace<0, JP>(O, l0, l1);
    pin_after(l0, l1);
    const uint32_t rd = mbar_test<BAR(B_FULL + 3)>(sb, t.xp) & mbar_test<BAR(B_STGE)>(sb + w * 8, (cs.round & 1) ^ 1);
    exp_pack<JP, 16, false>(O, P, l0, l1, r, O, 0.f, 0.f, pk);
    if (UNLIKELY(__reduce_or_sync(0xffffffffu, rd ^ 1))) {
      mbar_wait<BAR(B_FULL + 3)>(sb, t.xp);
      mbar_wait<BAR(B_STGE)>(sb + w * 8, (cs.round & 1) ^ 1);
    }
    bar_sync(1 + w, 256);
    issue_pv<8, 0>(O, P, t.vd);
    bar_arrive(1 + (w ^ 1), 256);
    if (YIELD0 && w == 1) bar_sync(5, 256);
    stage_step(YIELD0 && w == 0);
    ns = y - 2;
  } else {
    issue_qk<false>(S, t.qd, dlo(OFF_B + 32768, 16));
    bar_arrive(1 + (w ^ 1), 256);
    T4X(0);
    stage_write(pk, w, cs);
    stage_publish(w, cs);
    wg_wait<0>();
    fence_regs(S);
    T4Q(__float_as_uint(S[0]));
    mbar_arrive_cl<BAR(B_EMPTY + 1)>(cs.rel);
    causal_mask<0>(S, r + 64 * w + 128 * y);
    causal_mask<8>(S, r + 64 * w + 128 * y - 64);
    exp_pack<0, 16, false>(S, P, l0, l1, r, S, 0.f, 0.f, pk);
#pragma unroll
    for (int i = 0; i < 64; i++) O[i] = 0.f;
    late = 1;
    ns = 0;
  }
#pragma unroll 1
  for (uint32_t head = 0;; head++) {
    while (ns > 0) {
      if (UNLIKELY(late)) mbar_wait<BAR(B_FULL)>(t.cb, t.xc);
      bar_sync(1 + w, 256);
      issue_qk<false>(S, t.qd, t.kd);
      if (t.pub) { stage_publish(w, cs); t.pub = 0; }
      mbar_wait<BAR(B_FULL + 2)>(t.cb ^ 8, t.xp);
      issue_pv<8, 1>(O, P, t.vd);
      bar_arrive(1 + (w ^ 1), 256);
      ns--;
      att_advance(t);
      wg_wait<1>();
      fence_regs(S);
      T4Q(__float_as_uint(S[0]));
      mbar_arrive_cl<BAR(B_EMPTY)>(cs.rel, t.c8 ^ 8);
      exp_inplace<0, JS>(S, l0, l1);
      pin_after(l0, l1);
      wg_wait<0>();
      fence_regs(O);
      fence_regs(P);
      mbar_arrive_cl<BAR(B_EMPTY + 2)>(cs.rel, t.c8);
      const uint32_t rd = mbar_test<BAR(B_FULL)>(t.cb, t.xc);
      exp_pack<JS, 16, false>(S, P, l0, l1, 0, O, 0.f, 0.f, pk);
      late = __reduce_or_sync(0xffffffffu, rd ^ 1);
    }
    if (head == 0) {
      if (y != 0) {
        if (UNLIKELY(late)) mbar_wait<BAR(B_FULL)>(t.cb, t.xc);
        late = diag_step<false>(S, O, P, pk, l0, l1, unsafe, t, r, w, cs);
      }
      t.qd += 32768 >> 4;
      TRW(idx, 4);
      if (UNLIKELY(late)) { mbar_wait<BAR(B_QFULL)>(sb, cs.fpar & 1); mbar_wait<BAR(B_FULL)>(t.cb, t.xc); }
      late = diag_step<true>(S, O, P, pk, l0, l1, unsafe, t, r, w, cs);
    } else {
      bar_sync(1 + w, 256);
      mbar_wait<BAR(B_FULL + 2)>(t.cb ^ 8, t.xp);
      if (y != 1 || w) issue_pv<8, 1>(O, P, t.vd); else issue_pv<4, 1>(O, P, t.vd);
      if (w == 0) bar_arrive(2, 256);
      if (t.pub) stage_publish(w, cs);
      float a0, a1;
      unsafe = row_norm(l0, l1, a0, a1);
      mbar_arrive_if<BAR(B_QEMPTY + 1)>(sb, lane == 0 && !unsafe);
      wg_wait<0>();
      fence_regs(O);
      fence_regs(P);
      mbar_arrive_cl<BAR(B_EMPTY + 2)>(cs.rel, t.c8 ^ 8);
      att_output(O, a0, a1, pk);
    }
    if (UNLIKELY(unsafe)) {
      float a0, a1;
      slow_item(S, a0, a1, ((code >> 4) & 31) * 2 + head, y ^ head, sb + OFF_A + head * 32768, w);
      __syncwarp();
      mbar_arrive_if<BAR(B_QEMPTY)>(sb + head * 8, lane == 0);
      att_output(S, a0, a1, pk);
    }
    if (head) break;
    if (y != 1) {
      if (UNLIKELY(late)) mbar_wait<BAR(B_FULL)>(t.cb, t.xc);
      bar_sync(1 + w, 256);
      issue_qk<false>(S, t.qd, t.kd);
      mbar_wait<BAR(B_STGE)>(sb + w * 8, (cs.round & 1) ^ 1);
      mbar_wait<BAR(B_FULL + 2)>(t.cb ^ 8, t.xp);
      if (w == 0) issue_pv<4, 0>(O, P, t.vd); else issue_pv<8, 0>(O, P, t.vd);
      bar_arrive(1 + (w ^ 1), 256);
      stage_step(false);
      ns = (y ^ 1) - 1;
    } else {
      stage_write(pk, w, cs);
      t.pub = 1;
#pragma unroll
      for (int i = 0; i < 64; i++) O[i] = 0.f;
    }
  }
  cs.p1 = t.xp ^ 1; cs.p0 = t.xc;
  cs.fpar ^= 1;
}

struct Src { const CUtensorMap *ma, *mb; int a0, a1, b0, b1, b2; uint32_t hb; };
__device__ __forceinline__ Src gemm_src(const Params& p, uint32_t code, uint32_t rank, uint32_t h) {
  const int kind = code >> 9, x = (code >> 4) & 31, m = code & 15;
  Src s;
  s.ma = &p.maps[M_AX + kind];
  s.mb = &p.maps[(kind == K_KV && h) ? M_WUV : M_WQKV + kind];
  if (kind == K_QL) { s.a0 = rank * 1024; s.a1 = m * 128; s.b0 = x * 64; s.b1 = h * 32; s.b2 = 0; s.hb = 12288; }
  else { s.a0 = 0; s.a1 = (2 * m + rank) * 128; s.b0 = 0; s.b1 = 0; s.b2 = kind == K_KV ? x * 2 : x * 4 + h * 2; s.hb = 16384; }
  return s;
}
__global__ void __cluster_dims__(2, 1, 1) __launch_bounds__(384, 1) mega_kernel(const __grid_constant__ Params p) {
  extern __shared__ __align__(1024) uint8_t smem_raw[];
  const uint32_t sb = smem_u32(smem_raw), sb0 = sb;
#define TS(slot)
  const uint32_t bid = blockIdx.x, rank = bid & 1;
  const int warp = __shfl_sync(0xffffffffu, threadIdx.x >> 5, 0);
  auto early_load = [&](uint32_t code0, int s0, int s1) {
    const Src u = gemm_src(p, code0, rank, 0), v = gemm_src(p, code0, rank, 1);
#pragma unroll
    for (int s = s0; s < s1; s++) {
      const uint32_t bar = sb + BAR(B_FULL) + s * 8;
      if (elect_one()) {
        mbar_expect_tx<0>(bar, 16384 + 2 * u.hb);
        tma_load_2d(sb + OFF_A + s * 16384, u.ma, u.a0 + s * 64, u.a1, bar);
        tma_load_3d(sb + OFF_B + s * 32768, u.mb, u.b0, u.b1 + s * 64, u.b2, bar);
        tma_load_3d(sb + OFF_B + s * 32768 + u.hb, v.mb, v.b0, v.b1 + s * 64, v.b2, bar);
      }
    }
  };
#define BI(b) mbar_init<BAR(b)>(sb, bar_count(b))
  if (warp == 0) {
    const uint32_t c0 = p.sched[bid >> 1][threadIdx.x & 1];
    if (elect_one()) {
      BI(0); BI(1); BI(2); BI(3);
      asm volatile("fence.mbarrier_init.release.cluster;" ::: "memory");
    }
    __syncwarp();
    if (threadIdx.x == 0) TS(0);
    early_load(__shfl_sync(0xffffffffu, c0, 0) & 4095, 0, EARLYN);
    if (threadIdx.x == 0) TS(1);
  }
  if (threadIdx.x == 32 || threadIdx.x == 64 || threadIdx.x == 96) {
    if (threadIdx.x == 32) { BI(4); BI(5); BI(6); BI(7); BI(8); BI(9); }
    else if (threadIdx.x == 64) { BI(10); BI(11); BI(12); BI(13); BI(14); BI(15); }
    else {
      BI(16); BI(17); BI(18); BI(19); BI(20);
      asm volatile("st.shared.v2.u32 [%0+%2], {%1, %1};" ::"r"(sb), "r"(0), "n"(OFF_FILLS) : "memory");
      if ((sb & 0xffffffu) != SB) __trap();
    }
    asm volatile("fence.mbarrier_init.release.cluster;" ::: "memory");
  }
#undef BI
  static_assert(B_COUNT == 21, "barrier set-up");
  if (threadIdx.x >= 128 && threadIdx.x < 128 + MAX_ITEMS) {
    const int i = threadIdx.x - 128;
    asm volatile("st.shared.u32 [%0+%2], %1;" ::"r"(sb + i * 4), "r"(p.sched[bid >> 1][i]), "n"(OFF_LIST) : "memory");
  }
  if (threadIdx.x >= 256 && threadIdx.x < 320) asm volatile("st.shared.u32 [%0+%2], %1;" ::"r"(sb + (threadIdx.x - 256) * 4), "r"(0), "n"(OFF_MASK) : "memory");
  bar_sync(0, 384);
  cluster_arrive_relaxed();
  const int wg = warp >> 2;
  if (wg == 0) {
    reg_dealloc<REG_PROD>();
    if (EARLYN < 4 && warp == 0) early_load(item(sb, 0), EARLYN, 4);
    cluster_wait();
    const int lane = threadIdx.x & 31;
    auto need = [&](uint32_t& have, int i, int b) {
      if (!((have >> b) & 1)) {
        uint32_t n = 0;
        while (have = __reduce_or_sync(0xffffffffu, lds_acquire<OFF_MASK>(sb + i * 4)), !((have >> b) & 1)) { __nanosleep(32); if (++n > (1u << 22)) __trap(); }
        fence_async_glob();
      }
    };
    if (warp == 0) {
      uint32_t e0 = 0, e1 = 0;
      uint32_t qe = 0, after_att = 0, fills = 0;
      const uint64_t pol_first = policy_evict_first(), pol_normal = POL_NORMAL;
      for (int idx = 0;; idx++) {
        const uint32_t full = item_full(sb, idx), code = full & 4095;
        const int kind = code >> 9, x = (code >> 4) & 31, m = code & 15, y = 2 * m + rank;
        if (kind == K_END) break;
        const uint32_t last = full & (((LASTUSE & (kind >= K_OA ? 4 : 1)) ? 0x3000u : 0u) | ((LASTUSE & 2) ? 0xffff0000u : 0u));
        {
          const Src u = gemm_src(p, code, rank, rank);
          const uint64_t pa = (last & 0x1000) ? pol_first : pol_normal, pb = (last & 0x2000) ? pol_first : pol_normal;
          const int nk = kind == K_KV ? 8 : kind == K_OB ? 64 : 16;
          uint32_t have = kind >= K_OA ? 0u : 0xffffffffu;
#pragma unroll 1
          for (int k = idx == 0 ? 4 : 0; k < nk; k++) {
            const uint32_t s = k & 3;
            int kk = k;
            if (k >= 64 - 4 * HLATE) { const int j = (k >> 1) - (32 - 2 * HLATE); kk = (32 - 2 * HLATE + (j < HLATE ? 2 * j : 2 * (j - HLATE) + 1)) * 2 + (k & 1); }
            need(have, (kind == K_OA ? F_QL : F_CTX) + y, kind == K_OA ? k : kk >> 1);
            if (after_att && !(k & 1)) {
              mbar_wait<BAR(B_QEMPTY)>(sb + k * 4, qe);
              if (k == 2) { after_att = 0; qe ^= 1; }
            }
            fill_gemm(sb + s * 8, (s & 1) ? e1 : e0, 16384 + 2 * u.hb, sb + OFF_B + s * 32768 + rank * u.hb, u.mb, u.b0, u.b1 + kk * 64, u.b2, sb + OFF_A + s * 16384, u.ma, u.a0 + kk * 64, u.a1, pb, pa);
            asm volatile("st.volatile.shared.u32 [%0+%2], %1;" ::"r"(sb), "r"(++fills), "n"(OFF_FILLS) : "memory");
            if (s == 3) { e0 ^= 1; e1 ^= 1; }
          }
        }
        if (kind == K_QF) {
          uint32_t have = 0, xc = e1, xp = e0 ^ 1;
#pragma unroll 1
          for (int j = 0; j < 8 * m + 8; j++) {
            const int i = j >> 1, v = j & 1;
            if (v ? i == 0 : i == 4 * m + 3) continue;
            const int ib = i - v;
            if (i == 2 * m + 1 + rank && !v) have = 0;
            const int h = 2 * x + (ib >= 2 * m + 1 + (int)rank), blk = ib <= 2 * m + 1 ? ib : 4 * m + 2 - ib;
            const int row = KVSLOT(h) * SEQ + blk * 128;
            if (!v) need(have, F_KV + h, blk);
            const uint32_t b = 2 * v + ((ib + 1) & 1);
            const uint32_t dst = sb + OFF_B + b * 32768;
            const bool own = ib == 2 * m + 1;
            const uint64_t pol = ((last >> (16 + (h & 1) * 8 + (blk >> 1))) & 1) ? pol_first : pol_normal;
            fill_kv(sb + b * 8, v ? xp : xc, dst + rank * 16384, &p.maps[M_KV_LD], (2 * v + rank) * 64, row, own ? 1 + rank : 3, pol);
            if (own) tma_load_2d_h(dst + (rank ^ 1) * 16384, &p.maps[M_KV_LD], (2 * v + (rank ^ 1)) * 64, row, sb + BAR(B_FULL) + b * 8, pol);
            if (v || i == 0) { const uint32_t t = xc; xc = xp ^ 1; xp = t; }
          }
          e0 ^= 1;
          after_att = 1;
        }
      }
    } else if (warp == 2) {
      const uint32_t epoch = g_flags.epoch[bid];
      const uint64_t full = (lane >> 3) == 2 ? ~0ull : 0x0000ffff0000ffffull, flip = 0ull - (epoch & 1);
      uint64_t seen = 0;
      uint32_t tries = 0;
      while (!__all_sync(0xffffffffu, seen == full)) {
        uint64_t v;
        asm volatile("ld.acquire.gpu.global.u64 %0, [%1];" : "=l"(v) : "l"(&g_flags.m[2 * lane]) : "memory");
        v = (v ^ flip) & full;
        if (v != seen) { seen = v; asm volatile("st.release.cta.shared::cta.u64 [%0+%2], %1;" ::"r"(sb + lane * 8), "l"(v), "n"(OFF_MASK) : "memory"); }
        __nanosleep(WATCH_NS);
        if (++tries > (1u << 20)) __trap();
      }
      if (lane == 0) g_flags.epoch[bid] = epoch + 1;
    } else if (warp == 3) {
      uint32_t hp = 1;
      for (int idx = 0;; idx++) {
        const uint32_t code = item(sb, idx);
        const int kind = code >> 9, x = (code >> 4) & 31, y = 2 * (code & 15) + rank;
        if (kind == K_END) break;
        if (kind != K_QL || y < 2) continue;
        mbar_wait_long<BAR(B_HEMPTY)>(sb, hp);
        hp ^= 1;
        uint32_t n = 0;
        while (!((lds_acquire<OFF_MASK>(sb + (F_QL + y - 2) * 4) >> x) & 1)) { __nanosleep(100); if (++n > (1u << 22)) __trap(); }
        fence_async_glob();
        if (elect_one()) mbar_expect_tx<BAR(B_HFULL)>(sb, 2048);
        bulk_load(sb + OFF_HALO, g_halo + ((y - 2) * 16 + x) * 2048, 2048, sb + BAR(B_HFULL));
      }
    } else {
      {
        uint32_t round = 0, fpar = 0;
        const uint32_t rb = mapa(sb, rank ^ 1);
        const uint64_t pol_first = policy_evict_first(), pol_normal = POL_NORMAL;
        auto pace = [&]() {
          uint32_t c0, c, t0, t;
          asm volatile("ld.volatile.shared.u32 %0, [%1+%2];" : "=r"(c0) : "r"(sb), "n"(OFF_FILLS) : "memory");
          asm volatile("mov.u32 %0, %clock;" : "=r"(t0));
          do {
            asm volatile("ld.volatile.shared.u32 %0, [%1+%2];" : "=r"(c) : "r"(sb), "n"(OFF_FILLS) : "memory");
            asm volatile("mov.u32 %0, %clock;" : "=r"(t));
          } while (__all_sync(0xffffffffu, c == c0 && t - t0 < PACE_MAX));
        };
        for (int idx = 0;; idx++) {
          const uint32_t code = item(sb, idx);
          const int kind = code >> 9, x = (code >> 4) & 31, m = code & 15, y = 2 * m + rank;
          if (kind == K_END) break;
          const bool last = (item(sb, idx + 1) >> 9) == K_END;
          if (kind == K_QF) {
            if (elect_one()) mbar_expect_tx<BAR(B_QFULL)>(sb, 32768);
            mbar_wait_long<BAR(B_QX)>(sb, fpar);
#pragma unroll 1
            for (int v = 0; v < 2; v++) {
              mbar_wait<BAR(B_STGF)>(sb + v * 8, round & 1);
              bulk_send(rb + OFF_A + 32768 + v * 8192, sb + OFF_STG + v * 16384, 8192, rb + BAR(B_QFULL));
              bulk_send(rb + OFF_A + 49152 + v * 8192, sb + OFF_STG + v * 16384 + 8192, 8192, rb + BAR(B_QFULL));
            }
            mbar_wait<BAR(B_QFULL)>(sb, fpar);
            mbar_arrive_cl<BAR(B_STGE)>(lane < 2 ? rb : 0, lane * 8);
            round++; fpar ^= 1;
          }
          const CUtensorMap* mc = &p.maps[M_OA_ST + kind];
          const uint64_t pol = (((HINTS & 1) && kind >= K_OA) || ((HINTS & 2) && kind == K_QF) || ((HINTS & 4) && kind == K_QL) || ((HINTS & 8) && kind == K_KV)) ? pol_first : pol_normal;
          int row = kind == K_KV ? KVSLOT(x) * SEQ + y * 128 : kind == K_OA ? m * 128 : y * 128;
          int cg = kind == K_QL ? x : kind == K_QF ? x * 4 : kind == K_KV ? 0 : kind == K_OA ? rank * 32 + x * 4 : 16 + x * 4;
          const int nr = kind == K_QL ? 1 : 2;
#pragma unroll 1
          for (int r = 0; r < nr; r++) {
            mbar_wait_long<BAR(B_STGF)>(sb, round & 1);
            if (last && kind >= K_KV) {
              TRC(idx + 1, 6);
              tma_store_3d(mc, sb + OFF_STG, 0, row, cg, pol);
              mbar_wait<BAR(B_FIN)>(sb, 0);
              TRC(idx + 1, 7);
              tma_store_3d(mc, sb + OFF_B, 0, row, cg + 2, pol);
              mbar_wait<BAR(B_STGF + 1)>(sb, round & 1);
              TRC(idx + 1, 8);
              tma_store_3d(mc, sb + OFF_STG + 16384, 0, row + 64, cg, pol);
              mbar_wait<BAR(B_FIN + 1)>(sb, 0);
              TRC(idx + 1, 9);
              tma_store_3d(mc, sb + OFF_B + 16384, 0, row + 64, cg + 2, pol);
              bulk_commit();
              r = 1;
            } else {
              const bool paced = !last && (kind >= K_KV || r == 1);
              if (paced) pace();
              tma_store_3d(mc, sb + OFF_STG, 0, row, cg, pol);
              bulk_commit();
              mbar_wait<BAR(B_STGF + 1)>(sb, round & 1);
              if (paced) pace();
              tma_store_3d(mc, sb + OFF_STG + 16384, 0, row + 64, cg, pol);
              if (kind == K_QL) bulk_store(g_halo + (y * 16 + x) * 2048, sb + OFF_STG + 16384 + 8192 + 3 * 2048, 2048);
              bulk_commit();
              bulk_wait_read<1>();
              mbar_arrive_if<BAR(B_STGE)>(sb, lane == 0);
              bulk_wait_read<0>();
              mbar_arrive_if<BAR(B_STGE + 1)>(sb, lane == 0);
              round++;
            }
            if (kind == K_QF || (kind <= K_KV && r == nr - 1)) {
              bulk_wait_all();
              flag_toggle(&g_flags.m[kind == K_QL ? F_QL + y : kind == K_KV ? F_KV + x : F_CTX + (y ^ r)], 1u << (kind == K_QL ? x : kind == K_KV ? y : 2 * x + r));
              TRC(idx, 12 + r);
            }
            cg += 2;
            if (kind == K_QF) row ^= 128;
          }
        }
        bulk_wait_all();
      }
      cluster_arrive_relaxed();
      cluster_wait();
    }
  } else {
    reg_alloc<REG_CONS>();
    cluster_wait();
    const int w = wg - 1;
    Cons cs;
    cs.sb = SBU ? __reduce_or_sync(0xffffffffu, sb0) : sb0;
    const uint32_t sb = cs.sb;
    cs.rel = (threadIdx.x & 127) == 0 ? sb : (threadIdx.x & 127) == 1 ? mapa(sb, rank ^ 1) : 0;
    cs.p0 = cs.p1 = cs.lead = cs.round = cs.fpar = 0;
    uint32_t pkA[32], pkB[32], pend = 0;
#pragma unroll
    for (int i = 0; i < 32; i++) pkA[i] = pkB[i] = 0;
    uint32_t code = item(sb, 0);
    if (threadIdx.x == 128) TS(6);
    int idx = 0;
    do {
      TRW(idx, 0);
      const int kind = code >> 9;
      uint32_t ncode;
      if (kind == K_QL) {
        float acc[96];
        ncode = gemm_tile(acc, 4, idx, w, cs, pend, pkA, pkB);
        TRW(idx, 2);
        local_epilogue(acc, code, w, cs);
        pend = 24;
        if (LHS && w == 1 && (ncode >> 9) != K_END) bar_arrive(5, 256);
        if (!LPUB || (ncode >> 9) >= K_OA) { stage_publish(w, cs); pend = 16; }
      } else {
        float acc[128];
        ncode = gemm_tile(acc, kind == K_KV ? 2 : kind == K_OB ? 16 : 4, idx, w, cs, pend, pkA, pkB);
        TRW(idx, 2);
        if (kind == K_QF) {
          mbar_arrive_cl<BAR(B_QX)>((threadIdx.x & 1) ? cs.rel : 0);
          tile_pack_write<OFF_A, 16384, 0>(acc, pkB, sb + w * 8192);
#pragma unroll
          for (int i = 0; i < 32; i++) pkA[i] = v_pack(acc[64 + 2 * i], acc[64 + 2 * i + 1]);
          T4X(pkA[31]);
          mbar_wait<BAR(B_FULL + 1)>(sb, cs.p1);
          T4X(0);
          fence_async_smem();
          attention(code, rank, idx, w, cs, pkB, pkA);
          pend = 1;
        } else {
          if (kind == K_KV) {
#pragma unroll
            for (int i = 0; i < 64; i++) acc[i] *= SCALE_LOG2;
          }
#pragma unroll
          for (int i = 0; i < 32; i++) pkA[i] = pack_bf16(acc[2 * i], acc[2 * i + 1]);
#pragma unroll
          for (int i = 0; i < 32; i++) pkB[i] = pack_bf16(acc[64 + 2 * i], acc[64 + 2 * i + 1]);
          pend = 3;
        }
      }
      code = ncode;
      idx++;
    } while ((code >> 9) != K_END);
    TRW(idx, 0);
    if (pend & 1) { stage_write(pkA, w, cs); stage_publish(w, cs); }
    if (pend & 2) {
      mbar_wait<BAR(B_EMPTY)>(sb, cs.p0 ^ 1);
      tile_write<OFF_B, 8192>(pkB, sb + w * 16384);
      fence_async_smem();
      __syncwarp();
      mbar_arrive_if<BAR(B_FIN)>(sb + w * 8, (threadIdx.x & 31) == 0);
    }
    cluster_arrive();
  }
}

typedef CUresult (*EncodeFn)(CUtensorMap*, CUtensorMapDataType, cuuint32_t, void*, const cuuint64_t*, const cuuint64_t*, const cuuint32_t*,
                             const cuuint32_t*, CUtensorMapInterleave, CUtensorMapSwizzle, CUtensorMapL2promotion, CUtensorMapFloatOOBfill);

void make_map_2d(EncodeFn enc, CUtensorMap* tm, const void* ptr, uint64_t cols, uint64_t rows) {
  cuuint64_t dims[2] = {cols, rows};
  cuuint64_t str[1] = {cols * 2};
  cuuint32_t box[2] = {64, 128};
  cuuint32_t es[2] = {1, 1};
  enc(tm, CU_TENSOR_MAP_DATA_TYPE_BFLOAT16, 2, const_cast<void*>(ptr), dims, str, box, es, CU_TENSOR_MAP_INTERLEAVE_NONE, CU_TENSOR_MAP_SWIZZLE_128B,
      CU_TENSOR_MAP_L2_PROMOTION_L2_256B, CU_TENSOR_MAP_FLOAT_OOB_FILL_NONE);
}
void make_map_3d(EncodeFn enc, CUtensorMap* tm, const void* ptr, uint64_t cols, uint64_t rows, uint64_t part, uint32_t br, uint32_t bg) {
  cuuint64_t dims[3] = {part, rows, cols / part};
  cuuint64_t str[2] = {cols * 2, part * 2};
  cuuint32_t box[3] = {64, br, bg};
  cuuint32_t es[3] = {1, 1, 1};
  enc(tm, CU_TENSOR_MAP_DATA_TYPE_BFLOAT16, 3, const_cast<void*>(ptr), dims, str, box, es, CU_TENSOR_MAP_INTERLEAVE_NONE, CU_TENSOR_MAP_SWIZZLE_128B,
      CU_TENSOR_MAP_L2_PROMOTION_L2_256B, CU_TENSOR_MAP_FLOAT_OOB_FILL_NONE);
}

static const uint32_t h_sched[NPAIR][MAX_ITEMS] = {
  {0x400,0x203,0x20251,0x20291,0x2002f5,0x602,0xe00,0xe00,0xe00,0xe00,0xe00,0xe00,0xe00,0xe00,0xe00,0xe00,0xe00,0xe00,0xe00,0xe00},
  {0x420,0x206,0x514,0x530,0x592,0x2002c5,0x2087,0x625,0xe00,0xe00,0xe00,0xe00,0xe00,0xe00,0xe00,0xe00,0xe00,0xe00,0xe00,0xe00},
  {0x440,0xff800207,0x582,0x552,0x3e02b5,0x2077,0x615,0xe00,0xe00,0xe00,0xe00,0xe00,0xe00,0xe00,0xe00,0xe00,0xe00,0xe00,0xe00,0xe00},
  {0x460,0x213,0x6,0x4c6,0x80283,0x5d5,0x800,0xe00,0xe00,0xe00,0xe00,0xe00,0xe00,0xe00,0xe00,0xe00,0xe00,0xe00,0xe00,0xe00},
  {0x0,0x400226,0x24e7,0x2527,0x5a2,0x2567,0x595,0x5d3,0x802e3,0x633,0xe00,0xe00,0xe00,0xe00,0xe00,0xe00,0xe00,0xe00,0xe00,0xe00},
  {0x480,0x4a2,0x436,0x493,0x93,0x15,0x4d3,0x4f0,0x511,0x513,0x563,0x573,0x4002e6,0x612,0xe00,0xe00,0xe00,0xe00,0xe00,0xe00},
  {0x410,0xff800217,0xc08002b7,0x2057,0x614,0xe00,0xe00,0xe00,0xe00,0xe00,0xe00,0xe00,0xe00,0xe00,0xe00,0xe00,0xe00,0xe00,0xe00,0xe00},
  {0x10,0x225,0x281,0x5e3,0x5e5,0x5b3,0x802,0xe00,0xe00,0xe00,0xe00,0xe00,0xe00,0xe00,0xe00,0xe00,0xe00,0xe00,0xe00,0xe00},
  {0x20,0x4a3,0x200245,0x531,0x2537,0x574,0x577,0x25e7,0x1002f4,0x624,0xe00,0xe00,0xe00,0xe00,0xe00,0xe00,0xe00,0xe00,0xe00,0xe00},
  {0x30,0x222,0x266,0x5d7,0x824,0xe00,0xe00,0xe00,0xe00,0xe00,0xe00,0xe00,0xe00,0xe00,0xe00,0xe00,0xe00,0xe00,0xe00,0xe00},
  {0x430,0x223,0x16,0x4f1,0x293,0x5f5,0x806,0xe00,0xe00,0xe00,0xe00,0xe00,0xe00,0xe00,0xe00,0xe00,0xe00,0xe00,0xe00,0xe00},
  {0x450,0x484,0x2,0x457,0x495,0x40252,0x3802a5,0x25d0,0x132f0,0x632,0xe00,0xe00,0xe00,0xe00,0xe00,0xe00,0xe00,0xe00,0xe00,0xe00},
  {0x40,0xff800247,0x12290,0x5e6,0x5d4,0x815,0xe00,0xe00,0xe00,0xe00,0xe00,0xe00,0xe00,0xe00,0xe00,0xe00,0xe00,0xe00,0xe00,0xe00},
  {0x50,0x485,0x80800257,0x2b1,0x801,0xe00,0xe00,0xe00,0xe00,0xe00,0xe00,0xe00,0xe00,0xe00,0xe00,0xe00,0xe00,0xe00,0xe00,0xe00},
  {0x470,0x415,0x12,0x33,0xb4,0x56,0x20271,0x5c2,0x4012f6,0x636,0xe00,0xe00,0xe00,0xe00,0xe00,0xe00,0xe00,0xe00,0xe00,0xe00},
  {0x60,0x232,0x4b1,0x4d1,0x4f3,0x4e6,0x535,0x2547,0x202a1,0x827,0xe00,0xe00,0xe00,0xe00,0xe00,0xe00,0xe00,0xe00,0xe00,0xe00},
  {0x70,0x400236,0x561,0x5c0,0x565,0x2587,0x25a7,0x1002e4,0x623,0xe00,0xe00,0xe00,0xe00,0xe00,0xe00,0xe00,0xe00,0xe00,0xe00,0xe00},
  {0x490,0x200,0x53,0xd4,0x86,0x296,0x5d1,0x122d0,0x20e7,0xe00,0xe00,0xe00,0xe00,0xe00,0xe00,0xe00,0xe00,0xe00,0xe00,0xe00},
  {0x80,0x235,0x504,0x515,0x5e0,0x556,0x5e4,0x25c7,0x5f3,0x802f3,0x604,0xe00,0xe00,0xe00,0xe00,0xe00,0xe00,0xe00,0xe00,0xe00},
  {0x401,0x202,0x35,0x4c4,0x4e4,0x280,0x2a0,0x5b1,0x816,0xe00,0xe00,0xe00,0xe00,0xe00,0xe00,0xe00,0xe00,0xe00,0xe00,0xe00},
  {0x421,0xff800227,0x526,0x572,0x5e2,0x1f22c4,0x2097,0x635,0xe00,0xe00,0xe00,0xe00,0xe00,0xe00,0xe00,0xe00,0xe00,0xe00,0xe00,0xe00},
  {0x441,0x1,0x242,0x380265,0x5f4,0x810,0xe00,0xe00,0xe00,0xe00,0xe00,0xe00,0xe00,0xe00,0xe00,0xe00,0xe00,0xe00,0xe00,0xe00},
  {0x90,0x224,0x12250,0x5a0,0x571,0x4002d6,0x601,0xe00,0xe00,0xe00,0xe00,0xe00,0xe00,0xe00,0xe00,0xe00,0xe00,0xe00,0xe00,0xe00},
  {0x461,0x11,0x52,0xb3,0x55,0xb6,0x523,0x4f5,0x553,0x591,0x122b0,0x834,0xe00,0xe00,0xe00,0xe00,0xe00,0xe00,0xe00,0xe00},
  {0x481,0x233,0x26,0x285,0x832,0xe00,0xe00,0xe00,0xe00,0xe00,0xe00,0xe00,0xe00,0xe00,0xe00,0xe00,0xe00,0xe00,0xe00,0xe00},
  {0x411,0x21,0x62,0xc3,0x65,0xc6,0x542,0x544,0x2507,0x808002d7,0x611,0xe00,0xe00,0xe00,0xe00,0xe00,0xe00,0xe00,0xe00,0xe00},
  {0x431,0x205,0x510,0x543,0x534,0x564,0x590,0x2d4,0x20b7,0x616,0xe00,0xe00,0xe00,0xe00,0xe00,0xe00,0xe00,0xe00,0xe00,0xe00},
  {0x451,0x216,0x560,0x532,0x5a1,0x570,0x597,0x802d3,0x20c7,0x626,0xe00,0xe00,0xe00,0xe00,0xe00,0xe00,0xe00,0xe00,0xe00,0xe00},
  {0x471,0x204,0xffc00277,0x412f2,0x637,0xe00,0xe00,0xe00,0xe00,0xe00,0xe00,0xe00,0xe00,0xe00,0xe00,0xe00,0xe00,0xe00,0xe00,0xe00},
  {0x491,0x201,0x14,0x4e0,0x500,0x502,0x524,0x545,0x550,0x2c3,0x202d1,0x621,0xe00,0xe00,0xe00,0xe00,0xe00,0xe00,0xe00,0xe00},
  {0x402,0x212,0x45,0x261,0x536,0x551,0x593,0x5c6,0x5b2,0x811,0xe00,0xe00,0xe00,0xe00,0xe00,0xe00,0xe00,0xe00,0xe00,0xe00},
  {0x422,0x435,0x455,0x4a4,0xa3,0x25,0x264,0x5c5,0x5b4,0x814,0xe00,0xe00,0xe00,0xe00,0xe00,0xe00,0xe00,0xe00,0xe00,0xe00},
  {0x442,0x211,0x24,0x4b0,0x520,0x522,0x4f6,0x506,0x2b2,0x835,0xe00,0xe00,0xe00,0xe00,0xe00,0xe00,0xe00,0xe00,0xe00,0xe00},
  {0x462,0x214,0x4e3,0x4d6,0x4f4,0x562,0x4002c6,0x20a7,0x606,0xe00,0xe00,0xe00,0xe00,0xe00,0xe00,0xe00,0xe00,0xe00,0xe00,0xe00},
  {0xa0,0xd1,0x3,0x64,0xc5,0x501,0x503,0x505,0x516,0x5c1,0x586,0x596,0x5b6,0x812,0xe00,0xe00,0xe00,0xe00,0xe00,0xe00},
  {0x412,0x454,0x475,0xe2,0x180254,0x2b3,0x402d2,0x620,0xe00,0xe00,0xe00,0xe00,0xe00,0xe00,0xe00,0xe00,0xe00,0xe00,0xe00,0xe00},
  {0x432,0x215,0xe6,0x24f7,0x402a2,0x837,0xe00,0xe00,0xe00,0xe00,0xe00,0xe00,0xe00,0xe00,0xe00,0xe00,0xe00,0xe00,0xe00,0xe00},
  {0xb0,0xe1,0x13,0x74,0x4e1,0x4d2,0x541,0x72282,0x3002d5,0x631,0xe00,0xe00,0xe00,0xe00,0xe00,0xe00,0xe00,0xe00,0xe00,0xe00},
  {0x403,0x31,0x72,0x494,0xa4,0x76,0x12270,0x4002b6,0x2047,0x630,0xe00,0xe00,0xe00,0xe00,0xe00,0xe00,0xe00,0xe00,0xe00,0xe00},
  {0x423,0x474,0x2407,0xf2,0x497,0x4b7,0x10e5,0x284,0x5b5,0x807,0xe00,0xe00,0xe00,0xe00,0xe00,0xe00,0xe00,0xe00,0xe00,0xe00},
  {0x443,0x210,0x2456,0x4a6,0x4b2,0x36,0x286,0x402e2,0x622,0xe00,0xe00,0xe00,0xe00,0xe00,0xe00,0xe00,0xe00,0xe00,0xe00,0xe00},
  {0x463,0x41,0x82,0x4a5,0x24a7,0x263,0x557,0x566,0x576,0x5b7,0x803,0xe00,0xe00,0xe00,0xe00,0xe00,0xe00,0xe00,0xe00,0xe00},
  {0x4a0,0x406,0x22,0x43,0xc4,0x66,0x4d4,0x2a4,0x5d2,0x15f2,0x202e1,0x617,0xe00,0xe00,0xe00,0xe00,0xe00,0xe00,0xe00,0xe00},
  {0x482,0x221,0x34,0xa5,0x4c5,0x4e5,0x580,0x554,0x584,0x5a3,0x5a5,0x2594,0x804,0xe00,0xe00,0xe00,0xe00,0xe00,0xe00,0xe00},
  {0x413,0x51,0x243,0x295,0x836,0xe00,0xe00,0xe00,0xe00,0xe00,0xe00,0xe00,0xe00,0xe00,0xe00,0xe00,0xe00,0xe00,0xe00,0xe00},
  {0xc0,0x246,0x581,0x2517,0x585,0x5c4,0x2002e5,0x613,0xe00,0xe00,0xe00,0xe00,0xe00,0xe00,0xe00,0xe00,0xe00,0xe00,0xe00,0xe00},
  {0x433,0x426,0x2427,0x486,0x2476,0x4b4,0x4c1,0x46,0xfff00287,0x202f1,0x627,0xe00,0xe00,0xe00,0xe00,0xe00,0xe00,0xe00,0xe00,0xe00},
  {0x453,0xff800237,0x808002c7,0x2067,0x634,0xe00,0xe00,0xe00,0xe00,0xe00,0xe00,0xe00,0xe00,0xe00,0xe00,0xe00,0xe00,0xe00,0xe00,0xe00},
  {0x473,0x446,0x2447,0x2417,0x496,0x94,0xf5,0x540,0x4d7,0x533,0x583,0x555,0x2c0,0x830,0xe00,0xe00,0xe00,0xe00,0xe00,0xe00},
  {0x452,0x466,0x32,0x600256,0x808002f7,0x607,0xe00,0xe00,0xe00,0xe00,0xe00,0xe00,0xe00,0xe00,0xe00,0xe00,0xe00,0xe00,0xe00,0xe00},
  {0x472,0x61,0x244,0x100294,0x825,0xe00,0xe00,0xe00,0xe00,0xe00,0xe00,0xe00,0xe00,0xe00,0xe00,0xe00,0xe00,0xe00,0xe00,0xe00},
  {0x404,0x220,0x63,0xe4,0x96,0xf6,0x40292,0x5b0,0x820,0xe00,0xe00,0xe00,0xe00,0xe00,0xe00,0xe00,0xe00,0xe00,0xe00,0xe00},
  {0x424,0x71,0x92,0xd3,0x75,0x60262,0x808002e7,0x603,0xe00,0xe00,0xe00,0xe00,0xe00,0xe00,0xe00,0xe00,0xe00,0xe00,0xe00,0xe00},
  {0x444,0x231,0x44,0xff800267,0x831,0xe00,0xe00,0xe00,0xe00,0xe00,0xe00,0xe00,0xe00,0xe00,0xe00,0xe00,0xe00,0xe00,0xe00,0xe00},
  {0x464,0x241,0x54,0xb5,0x4f2,0x808002a7,0x2017,0x20d7,0x605,0xe00,0xe00,0xe00,0xe00,0xe00,0xe00,0xe00,0xe00,0xe00,0xe00,0xe00},
  {0x4a1,0x81,0xa2,0xe3,0x85,0xd6,0x4d5,0x7f4002a6,0x122e0,0x610,0xe00,0xe00,0xe00,0xe00,0xe00,0xe00,0xe00,0xe00,0xe00,0xe00},
  {0xd0,0x234,0x274,0x5f7,0x813,0xe00,0xe00,0xe00,0xe00,0xe00,0xe00,0xe00,0xe00,0xe00,0xe00,0xe00,0xe00,0xe00,0xe00,0xe00},
  {0x483,0x230,0x73,0xf4,0xa6,0xff800297,0x2007,0x2037,0x600,0xe00,0xe00,0xe00,0xe00,0xe00,0xe00,0xe00,0xe00,0xe00,0xe00,0xe00},
  {0xe0,0xf1,0x23,0x84,0xd5,0x521,0x24c7,0x525,0x546,0x5e1,0x5c3,0x5a6,0x5d6,0x822,0xe00,0xe00,0xe00,0xe00,0xe00,0xe00},
  {0x414,0x492,0x42,0x477,0x4,0x4c2,0x4e2,0x200275,0x826,0xe00,0xe00,0xe00,0xe00,0xe00,0xe00,0xe00,0xe00,0xe00,0xe00,0xe00},
  {0x434,0x240,0x83,0x4c0,0x4c3,0x4d0,0x12260,0x2c2,0x805,0xe00,0xe00,0xe00,0xe00,0xe00,0xe00,0xe00,0xe00,0xe00,0xe00,0xe00},
  {0x405,0x91,0xb2,0x2487,0x4b3,0x4b6,0x276,0x823,0xe00,0xe00,0xe00,0xe00,0xe00,0xe00,0xe00,0xe00,0xe00,0xe00,0xe00,0xe00},
  {0x425,0xa1,0x2467,0x2437,0x4b5,0x5,0x273,0x5a4,0x575,0x5f6,0x817,0xe00,0xe00,0xe00,0xe00,0xe00,0xe00,0xe00,0xe00,0xe00},
  {0xf0,0x416,0x255,0x2a3,0x833,0xe00,0xe00,0xe00,0xe00,0xe00,0xe00,0xe00,0xe00,0xe00,0xe00,0xe00,0xe00,0xe00,0xe00,0xe00},
  {0x445,0xb1,0xc2,0xf3,0x95,0x272,0x2c1,0x821,0xe00,0xe00,0xe00,0xe00,0xe00,0xe00,0xe00,0xe00,0xe00,0xe00,0xe00,0xe00},
  {0x465,0xc1,0xd2,0x253,0x512,0x2b4,0x15f1,0x35f0,0x2027,0x30f7,0xe00,0xe00,0xe00,0xe00,0xe00,0xe00,0xe00,0xe00,0xe00,0xe00},
};

struct HostState { bool init; Params p; void* out; const void* in[9]; };
HostState g_hs;

void build_state(void* const* d_in, void* d_out) {
  void* fn = nullptr;
  cudaDriverEntryPointQueryResult qr;
  cudaGetDriverEntryPoint("cuTensorMapEncodeTiled", &fn, cudaEnableDefault, &qr);
  EncodeFn enc = (EncodeFn)fn;
  void *kv, *ctx, *oA;
  cudaGetSymbolAddress(&kv, g_kv);
  cudaGetSymbolAddress(&ctx, g_ctx);
  cudaGetSymbolAddress(&oA, g_oA);
  Params& p = g_hs.p;
  make_map_2d(enc, &p.maps[M_AX], d_in[0], 2048, SEQ / 2);
  make_map_2d(enc, &p.maps[M_BX], d_in[3], 1024, SEQ);
  make_map_2d(enc, &p.maps[M_CKV], d_in[4], 512, SEQ);
  make_map_2d(enc, &p.maps[M_OA], oA, 1024, SEQ);
  make_map_2d(enc, &p.maps[M_CTX], ctx, 4096, SEQ);
  make_map_3d(enc, &p.maps[M_WQKV], d_in[1], 3072, 1024, 1024, 32, 3);
  make_map_3d(enc, &p.maps[M_WQ], d_in[5], 4096, 1024, 64, 64, 2);
  make_map_3d(enc, &p.maps[M_WUK], d_in[6], 4096, 512, 64, 64, 2);
  make_map_3d(enc, &p.maps[M_WUV], d_in[7], 4096, 512, 64, 64, 2);
  make_map_3d(enc, &p.maps[M_WOA], d_in[2], 1024, 1024, 64, 64, 2);
  make_map_3d(enc, &p.maps[M_WOB], d_in[8], 1024, 4096, 64, 64, 2);
  make_map_2d(enc, &p.maps[M_KV_LD], kv, 256, 32 * SEQ);
  make_map_3d(enc, &p.maps[M_OA_ST], oA, 1024, SEQ, 64, 64, 1);
  make_map_3d(enc, &p.maps[M_CTX_ST], ctx, 4096, SEQ, 64, 64, 2);
  make_map_3d(enc, &p.maps[M_KV_ST], kv, 256, 32 * SEQ, 64, 64, 2);
  make_map_3d(enc, &p.maps[M_OUTA_ST], d_out, 4096, SEQ / 2, 64, 64, 2);
  make_map_3d(enc, &p.maps[M_OUTB_ST], d_out, 2048, SEQ, 64, 64, 2);
  for (int c = 0; c < NPAIR; c++)
    for (int i = 0; i < MAX_ITEMS; i++) p.sched[c][i] = h_sched[c][i];
  cudaFuncSetAttribute(mega_kernel, cudaFuncAttributeMaxDynamicSharedMemorySize, SMEM_BYTES);
}

}

extern "C" void kernel_launch(void* const* d_in, const int* in_sizes, int n_in, void* d_out, int out_size) {
  (void)in_sizes; (void)n_in; (void)out_size;
  bool same = g_hs.init && g_hs.out == d_out;
  for (int i = 0; i < 9 && same; i++) same = (g_hs.in[i] == d_in[i]);
  if (!same) {
    build_state(d_in, d_out);
    g_hs.init = true; g_hs.out = d_out;
    for (int i = 0; i < 9; i++) g_hs.in[i] = d_in[i];
  }
  mega_kernel<<<NCTA, 384, SMEM_BYTES, cudaStreamPerThread>>>(g_hs.p);
}
```

```cpp
#include <cuda_runtime.h>
#include <cuda_bf16.h>
#include <cuda.h>
#include <stdint.h>

namespace {

constexpr int SEQ = 2048;
constexpr int NCTA = 132, NPAIR = 66;
constexpr int MAX_ITEMS = 20;

__device__ __align__(1024) __nv_bfloat16 g_kv[32 * SEQ * 256];
__device__ __align__(1024) __nv_bfloat16 g_ctx[SEQ * 4096];
__device__ __align__(1024) __nv_bfloat16 g_oA[SEQ * 1024];
__device__ __align__(1024) uint8_t g_halo[16 * 16 * 2048];
struct Flags { uint32_t m[64]; uint32_t epoch[NCTA]; };
__device__ __align__(128) Flags g_flags;
enum { F_KV = 0, F_CTX = 32, F_QL = 48 };

enum { K_QL = 0, K_QF = 1, K_KV = 2, K_OA = 3, K_OB = 4, K_END = 7 };
enum { M_AX = 0, M_BX, M_CKV, M_OA, M_CTX, M_WQKV, M_WQ, M_WUK, M_WOA, M_WOB, M_WUV, M_KV_LD, M_OA_ST, M_CTX_ST, M_KV_ST, M_OUTA_ST, M_OUTB_ST, M_COUNT };

struct Params {
  CUtensorMap maps[M_COUNT];
  alignas(16) uint32_t sched[NPAIR][MAX_ITEMS];
};

#define TRC(idx, slot)
#define TRW(idx, slot)
#define T4Q(dep)
#define T4X(dep)
#define T4K()

constexpr uint32_t SB = 1024;
constexpr uint32_t OFF_A = 0;
constexpr uint32_t OFF_B = 65536;
constexpr uint32_t OFF_STG = 196608;
constexpr uint32_t OFF_HALO = 229376;
constexpr uint32_t OFF_BAR = 231424;
constexpr uint32_t OFF_MASK = OFF_BAR + 256;
constexpr uint32_t OFF_LIST = OFF_BAR + 512;
constexpr uint32_t OFF_FILLS = OFF_BAR + 608;
constexpr uint32_t SMEM_BYTES = OFF_BAR + 640;
enum { B_FULL = 0, B_EMPTY = 4, B_QEMPTY = 8, B_STGE = 10, B_STGF = 12, B_FIN = 14, B_QFULL = 16, B_QX = 17, B_LEAD = 18, B_HFULL = 19, B_HEMPTY = 20, B_RELF = 21, B_RELE = 23, B_COUNT = 25 };
__host__ __device__ constexpr uint32_t BAR(int b) { return OFF_BAR + b * 8; }
__host__ __device__ constexpr int bar_count(int b) { return b < B_EMPTY ? 1 : b < B_QEMPTY ? 4 : b < B_STGE ? 8 : b < B_STGF ? 1 : b < B_QFULL ? 4 : b == B_QX ? 2 : 1; }
#define RCONS 232
constexpr int REG_CONS = RCONS, REG_PROD = (64512 - RCONS * 256) / 128 / 8 * 8;
#define KVSLOT(h) (h)
#define PACE_MAX 1100
#define WATCH_NS 250
#define HINTS 3
#define JSPLIT 14
#define JEDGE 14
#define LSH 0
#define LPUB 1
#define SBU 1
#define LHS 1
#define LPUBP 0
#define LEADF 3
#define EARLYN 3
#define HLATE 3
#define LASTUSE 3
#define RELW 1
#define W0EARLY 2
#define EREL 1
#define JP 14
#define YIELD0 0
#define YIELD2 0
#define JDIAG2 10
#define SUMPOS 1
#define JDIAG 12
#define LEADN 2
#define LEADL LEADN
#define STGA 3
#define STGB 8
#define STGAL 4
#define STGBL 12
#define PUBD 1

__device__ __forceinline__ uint32_t smem_u32(const void* p) { return (uint32_t)__cvta_generic_to_shared(p); }
__device__ __forceinline__ void wg_fence() { asm volatile("wgmma.fence.sync.aligned;" ::: "memory"); }
__device__ __forceinline__ void wg_commit() { asm volatile("wgmma.commit_group.sync.aligned;" ::: "memory"); }
template <int N> __device__ __forceinline__ void wg_wait() { asm volatile("wgmma.wait_group.sync.aligned %0;" ::"n"(N) : "memory"); }
__host__ __device__ constexpr uint32_t dlo(uint32_t off, uint32_t lbo) { return ((SB + off) >> 4) | ((lbo >> 4) << 16); }
template <uint32_t O> __device__ __forceinline__ void mbar_init(uint32_t a, uint32_t cnt) { asm volatile("mbarrier.init.shared::cta.b64 [%0+%2], %1;" ::"r"(a), "r"(cnt), "n"(O) : "memory"); }
template <uint32_t O> __device__ __forceinline__ void mbar_expect_tx(uint32_t a, uint32_t bytes) { asm volatile("mbarrier.arrive.expect_tx.shared::cta.b64 _, [%0+%2], %1;" ::"r"(a), "r"(bytes), "n"(O) : "memory"); }
template <uint32_t O> __device__ __forceinline__ void mbar_arrive_if(uint32_t a, bool pred) {
  asm volatile("{\n.reg .pred p;\nsetp.ne.u32 p, %1, 0;\n@p mbarrier.arrive.shared::cta.b64 _, [%0+%2];\n}\n" ::"r"(a), "r"((uint32_t)pred), "n"(O) : "memory");
}
template <uint32_t O> __device__ __forceinline__ void mbar_arrive_cl(uint32_t a, uint32_t off = 0) {
  asm volatile("{\n.reg .pred p;\nsetp.ne.u32 p, %2, 0;\n@p mbarrier.arrive.shared::cluster.b64 _, [%0+%1];\n}\n" ::"r"(a + off), "n"(O), "r"(a) : "memory");
}
template <uint32_t O> __device__ __forceinline__ bool mbar_test(uint32_t a, uint32_t parity) {
  uint32_t ok;
  asm volatile("{\n.reg .pred p;\nmbarrier.test_wait.parity.shared::cta.b64 p, [%1+%3], %2;\nselp.u32 %0, 1, 0, p;\n}\n" : "=r"(ok) : "r"(a), "r"(parity), "n"(O) : "memory");
  return ok;
}
template <uint32_t O> __device__ __forceinline__ void mbar_wait(uint32_t a, uint32_t parity) {
  asm volatile("{\n.reg .pred p, q;\n.reg .u32 n;\nmov.u32 n, 0;\nWAIT_%=:\nadd.u32 n, n, 1;\nmbarrier.try_wait.parity.shared::cta.b64 p, [%0+%2], %1;\n"
               "setp.lt.u32 q, n, 4194304;\nand.pred q, q, !p;\n@q bra WAIT_%=;\n@!p st.shared.u32 [%0+1], n;\n}\n" ::"r"(a), "r"(parity), "n"(O) : "memory");
}
template <uint32_t O> __device__ __forceinline__ void mbar_wait_long(uint32_t a, uint32_t parity) {
  asm volatile("{\n.reg .pred p, q;\n.reg .u32 n;\nmov.u32 n, 0;\nWAIT_%=:\nadd.u32 n, n, 1;\nmbarrier.try_wait.parity.shared::cta.b64 p, [%0+%2], %1, 4000;\n"
               "setp.lt.u32 q, n, 1048576;\nand.pred q, q, !p;\n@q bra WAIT_%=;\n@!p st.shared.u32 [%0+1], n;\n}\n" ::"r"(a), "r"(parity), "n"(O) : "memory");
}
__device__ __forceinline__ void tma_load_2d(uint32_t dst, const CUtensorMap* tm, int c0, int c1, uint32_t bar) {
  asm volatile("cp.async.bulk.tensor.2d.shared::cluster.global.mbarrier::complete_tx::bytes [%0], [%1, {%3, %4}], [%2];" ::"r"(dst), "l"(tm), "r"(bar), "r"(c0), "r"(c1) : "memory");
}
__device__ __forceinline__ void tma_load_3d(uint32_t dst, const CUtensorMap* tm, int c0, int c1, int c2, uint32_t bar) {
  asm volatile("cp.async.bulk.tensor.3d.shared::cluster.global.mbarrier::complete_tx::bytes [%0], [%1, {%3, %4, %5}], [%2];" ::"r"(dst), "l"(tm), "r"(bar), "r"(c0), "r"(c1), "r"(c2) : "memory");
}
#define FILL_HEAD "{\n.reg .pred p, q;\n.reg .u32 n;\nmov.u32 n, 0;\nWAIT_%=:\nadd.u32 n, n, 1;\nmbarrier.try_wait.parity.shared::cta.b64 p, [%0+%1], %3;\n" \
                  "setp.lt.u32 q, n, 4194304;\nand.pred q, q, !p;\n@q bra WAIT_%=;\n@!p st.shared.u32 [%0+1], n;\nelect.sync _|p, 0xffffffff;\n" \
                  "@p mbarrier.arrive.expect_tx.shared::cta.b64 _, [%2], %4;\n"
__device__ __forceinline__ void fill_gemm(uint32_t bb, uint32_t parity, uint32_t bytes, uint32_t dstb, const CUtensorMap* mb, int b0, int b1, int b2, uint32_t dsta, const CUtensorMap* ma, int a0, int a1, uint64_t pb, uint64_t pa) {
  asm volatile(FILL_HEAD
               "@p cp.async.bulk.tensor.3d.shared::cluster.global.mbarrier::complete_tx::bytes.multicast::cluster.L2::cache_hint [%5], [%6, {%7, %8, %9}], [%2], %14, %15;\n"
               "@p cp.async.bulk.tensor.2d.shared::cluster.global.mbarrier::complete_tx::bytes.L2::cache_hint [%10], [%11, {%12, %13}], [%2], %16;\n}\n"
               ::"r"(bb), "n"(BAR(B_EMPTY)), "r"(bb + BAR(B_FULL)), "r"(parity), "r"(bytes), "r"(dstb), "l"(mb), "r"(b0), "r"(b1), "r"(b2), "r"(dsta), "l"(ma), "r"(a0), "r"(a1), "h"((uint16_t)3), "l"(pb), "l"(pa) : "memory");
}
__device__ __forceinline__ void fill_kv(uint32_t bb, uint32_t parity, uint32_t dst, const CUtensorMap* m, int c0, int c1, uint16_t mask, uint64_t pol) {
  asm volatile(FILL_HEAD
               "@p cp.async.bulk.tensor.2d.shared::cluster.global.mbarrier::complete_tx::bytes.multicast::cluster.L2::cache_hint [%5], [%6, {%7, %8}], [%2], %9, %10;\n}\n"
               ::"r"(bb), "n"(BAR(B_EMPTY)), "r"(bb + BAR(B_FULL)), "r"(parity), "r"(32768), "r"(dst), "l"(m), "r"(c0), "r"(c1), "h"(mask), "l"(pol) : "memory");
}
__device__ __forceinline__ void tma_load_2d_h(uint32_t dst, const CUtensorMap* tm, int c0, int c1, uint32_t bar, uint64_t pol) {
  asm volatile("{\n.reg .pred p;\nelect.sync _|p, 0xffffffff;\n@p cp.async.bulk.tensor.2d.shared::cluster.global.mbarrier::complete_tx::bytes.L2::cache_hint [%0], [%1, {%3, %4}], [%2], %5;\n}\n" ::"r"(dst), "l"(tm), "r"(bar), "r"(c0), "r"(c1), "l"(pol) : "memory");
}
__device__ __forceinline__ void tma_store_3d(const CUtensorMap* tm, uint32_t src, int c0, int c1, int c2, uint64_t pol) {
  asm volatile("{\n.reg .pred p;\nelect.sync _|p, 0xffffffff;\n@p cp.async.bulk.tensor.3d.global.shared::cta.bulk_group.L2::cache_hint [%0, {%2, %3, %4}], [%1], %5;\n}\n" ::"l"(tm), "r"(src), "r"(c0), "r"(c1), "r"(c2), "l"(pol) : "memory");
}
__device__ __forceinline__ void bulk_load(uint32_t dst, const void* src, uint32_t bytes, uint32_t bar) {
  asm volatile("{\n.reg .pred p;\nelect.sync _|p, 0xffffffff;\n@p cp.async.bulk.shared::cluster.global.mbarrier::complete_tx::bytes [%0], [%1], %2, [%3];\n}\n" ::"r"(dst), "l"(src), "r"(bytes), "r"(bar) : "memory");
}
__device__ __forceinline__ void bulk_store(void* dst, uint32_t src, uint32_t bytes) {
  asm volatile("{\n.reg .pred p;\nelect.sync _|p, 0xffffffff;\n@p cp.async.bulk.global.shared::cta.bulk_group [%0], [%1], %2;\n}\n" ::"l"(dst), "r"(src), "r"(bytes) : "memory");
}
__device__ __forceinline__ void bulk_send(uint32_t dst, uint32_t src, uint32_t bytes, uint32_t bar) {
  asm volatile("{\n.reg .pred p;\nelect.sync _|p, 0xffffffff;\n@p cp.async.bulk.shared::cluster.shared::cta.mbarrier::complete_tx::bytes [%0], [%1], %2, [%3];\n}\n" ::"r"(dst), "r"(src), "r"(bytes), "r"(bar) : "memory");
}
__device__ __forceinline__ uint64_t policy_evict_first() { uint64_t p; asm volatile("createpolicy.fractional.L2::evict_first.b64 %0, 1.0;" : "=l"(p)); return p; }
constexpr uint64_t POL_NORMAL = 0x1000000000000000ull;
__device__ __forceinline__ uint32_t mapa(uint32_t addr, uint32_t rank) { uint32_t r; asm("mapa.shared::cluster.u32 %0, %1, %2;" : "=r"(r) : "r"(addr), "r"(rank)); return r; }
__device__ __forceinline__ void cluster_arrive_relaxed() { asm volatile("barrier.cluster.arrive.relaxed.aligned;" ::: "memory"); }
__device__ __forceinline__ void cluster_arrive() { asm volatile("barrier.cluster.arrive.release.aligned;" ::: "memory"); }
__device__ __forceinline__ void cluster_wait() { asm volatile("barrier.cluster.wait.acquire.aligned;" ::: "memory"); }
__device__ __forceinline__ void bulk_commit() { asm volatile("cp.async.bulk.commit_group;" ::: "memory"); }
template <int N> __device__ __forceinline__ void bulk_wait_read() { asm volatile("cp.async.bulk.wait_group.read %0;" ::"n"(N) : "memory"); }
__device__ __forceinline__ void bulk_wait_all() { asm volatile("cp.async.bulk.wait_group 0;" ::: "memory"); }
__device__ __forceinline__ void fence_async_smem() { asm volatile("fence.proxy.async.shared::cta;" ::: "memory"); }
__device__ __forceinline__ void fence_async_glob() { asm volatile("fence.proxy.async.global;" ::: "memory"); }
__device__ __forceinline__ void flag_toggle(uint32_t* p, uint32_t v) { asm volatile("{\n.reg .pred p;\nelect.sync _|p, 0xffffffff;\n@p red.release.gpu.global.xor.b32 [%0], %1;\n}\n" ::"l"(p), "r"(v) : "memory"); }
template <uint32_t O> __device__ __forceinline__ uint32_t lds_acquire(uint32_t a) { uint32_t v; asm volatile("ld.acquire.cta.shared::cta.u32 %0, [%1+%2];" : "=r"(v) : "r"(a), "n"(O) : "memory"); return v; }
__device__ __forceinline__ uint32_t item_full(uint32_t sb, int idx) {
  uint32_t c;
  asm volatile("ld.shared.u32 %0, [%1+%2];" : "=r"(c) : "r"(sb + idx * 4), "n"(OFF_LIST));
  return __reduce_or_sync(0xffffffffu, c);
}
__device__ __forceinline__ uint32_t item(uint32_t sb, int idx) { return item_full(sb, idx) & 4095; }
template <int N> __device__ __forceinline__ void reg_alloc() { asm volatile("setmaxnreg.inc.sync.aligned.u32 %0;" ::"n"(N)); }
template <int N> __device__ __forceinline__ void reg_dealloc() { asm volatile("setmaxnreg.dec.sync.aligned.u32 %0;" ::"n"(N)); }
template <int I0, int I1, int N> __device__ __forceinline__ void fence_regs(float (&d)[N]) {
#pragma unroll
  for (int i = I0; i < I1; i++) asm volatile("" : "+f"(d[i])::"memory");
}
template <int N> __device__ __forceinline__ void fence_regs(float (&d)[N]) { fence_regs<0, N, N>(d); }
template <int N> __device__ __forceinline__ void fence_regs(uint32_t (&d)[N]) {
#pragma unroll
  for (int i = 0; i < N; i++) asm volatile("" : "+r"(d[i])::"memory");
}
__device__ __forceinline__ uint32_t pack_bf16(float lo, float hi) { uint32_t r; asm("cvt.rn.bf16x2.f32 %0, %1, %2;" : "=r"(r) : "f"(hi), "f"(lo)); return r; }
__device__ __forceinline__ uint32_t v_pack(float lo, float hi) { uint32_t r; asm volatile("cvt.rn.bf16x2.f32 %0, %1, %2;" : "=r"(r) : "f"(hi), "f"(lo)); return r; }
template <uint32_t O> __device__ __forceinline__ void stmatrix_x4(uint32_t a, uint32_t r0, uint32_t r1, uint32_t r2, uint32_t r3) {
  asm volatile("stmatrix.sync.aligned.m8n8.x4.shared.b16 [%0+%5], {%1, %2, %3, %4};" ::"r"(a), "r"(r0), "r"(r1), "r"(r2), "r"(r3), "n"(O) : "memory");
}
template <uint32_t O> __device__ __forceinline__ void stmatrix_x4_after(uint32_t a, uint32_t r0, uint32_t r1, uint32_t r2, uint32_t r3, float dep, uint32_t on) {
  asm volatile("{\n.reg .pred p, q;\n.reg .u32 a;\nsetp.ne.u32 p, %7, 0;\nsetp.ne.u32 q, %6, 0xffffffff;\nselp.u32 a, %0, 0, q;\n@p stmatrix.sync.aligned.m8n8.x4.shared.b16 [a+%5], {%1, %2, %3, %4};\n}\n"
               ::"r"(a), "r"(r0), "r"(r1), "r"(r2), "r"(r3), "n"(O), "r"(__float_as_uint(dep)), "r"(on) : "memory");
}
template <uint32_t O> __device__ __forceinline__ void stmatrix_x4_trans(uint32_t a, uint32_t r0, uint32_t r1, uint32_t r2, uint32_t r3) {
  asm volatile("stmatrix.sync.aligned.m8n8.x4.trans.shared.b16 [%0+%5], {%1, %2, %3, %4};" ::"r"(a), "r"(r0), "r"(r1), "r"(r2), "r"(r3), "n"(O) : "memory");
}
template <uint32_t O> __device__ __forceinline__ void sts128(uint32_t a, const uint32_t* r) { asm volatile("st.shared.v4.u32 [%0+%5], {%1, %2, %3, %4};" ::"r"(a), "r"(r[0]), "r"(r[1]), "r"(r[2]), "r"(r[3]), "n"(O) : "memory"); }
template <uint32_t O> __device__ __forceinline__ void lds128(uint32_t* r, uint32_t a) { asm volatile("ld.shared.v4.u32 {%0, %1, %2, %3}, [%4+%5];" : "=r"(r[0]), "=r"(r[1]), "=r"(r[2]), "=r"(r[3]) : "r"(a), "n"(O) : "memory"); }
__device__ __forceinline__ uint32_t transpose8(uint32_t a) { uint32_t d; asm volatile("movmatrix.sync.aligned.m8n8.trans.b16 %0, %1;" : "=r"(d) : "r"(a)); return d; }
__device__ __forceinline__ float ex2(float x) { float y; asm("ex2.approx.ftz.f32 %0, %1;" : "=f"(y) : "f"(x)); return y; }
__device__ __forceinline__ float rcp(float x) { float y; asm("rcp.approx.ftz.f32 %0, %1;" : "=f"(y) : "f"(x)); return y; }
__device__ __forceinline__ void bar_sync(int id, int n) { asm volatile("bar.sync %0, %1;" ::"r"(id), "r"(n) : "memory"); }
__device__ __forceinline__ void bar_arrive(int id, int n) { asm volatile("bar.arrive %0, %1;" ::"r"(id), "r"(n) : "memory"); }
__device__ __forceinline__ void mma16816(float (&c)[4], uint32_t a0, uint32_t a1, uint32_t a2, uint32_t a3, uint32_t b0, uint32_t b1) {
  asm("mma.sync.aligned.m16n8k16.row.col.f32.bf16.bf16.f32 {%0, %1, %2, %3}, {%4, %5, %6, %7}, {%8, %9}, {%0, %1, %2, %3};"
      : "+f"(c[0]), "+f"(c[1]), "+f"(c[2]), "+f"(c[3]) : "r"(a0), "r"(a1), "r"(a2), "r"(a3), "r"(b0), "r"(b1));
}
__device__ __forceinline__ void mma16816z(float (&c)[4], uint32_t a0, uint32_t a1, uint32_t a2, uint32_t a3, uint32_t b0, uint32_t b1, float z) {
  asm("mma.sync.aligned.m16n8k16.row.col.f32.bf16.bf16.f32 {%0, %1, %2, %3}, {%4, %5, %6, %7}, {%8, %9}, {%10, %10, %10, %10};"
      : "=f"(c[0]), "=f"(c[1]), "=f"(c[2]), "=f"(c[3]) : "r"(a0), "r"(a1), "r"(a2), "r"(a3), "r"(b0), "r"(b1), "f"(z));
}
__device__ __forceinline__ uint4 ldg128(const void* p) { uint4 v; asm volatile("ld.global.cg.v4.u32 {%0, %1, %2, %3}, [%4];" : "=r"(v.x), "=r"(v.y), "=r"(v.z), "=r"(v.w) : "l"(p) : "memory"); return v; }
__device__ __forceinline__ uint32_t ldg16(const void* p) { uint16_t v; asm volatile("ld.global.cg.u16 %0, [%1];" : "=h"(v) : "l"(p) : "memory"); return v; }
__device__ __forceinline__ float quad_sum(float v) {
  v += __shfl_xor_sync(0xffffffffu, v, 1);
  v += __shfl_xor_sync(0xffffffffu, v, 2);
  return v;
}
__device__ __forceinline__ bool elect_one() { uint32_t p; asm volatile("{\n.reg .pred p;\nelect.sync _|p, 0xffffffff;\nselp.u32 %0, 1, 0, p;\n}\n" : "=r"(p)); return p; }
#define UNLIKELY(x) __builtin_expect(!!(x), 0)

__device__ __forceinline__ void wg_gemm_init(float (&d)[128], uint32_t alo, uint32_t blo) {
  asm volatile("{\n.reg .pred p;\n.reg .b64 da, db;\nmov.b64 da, {%128, 0x40000040};\nmov.b64 db, {%129, 0x40000040};\nsetp.ne.b32 p, 0, 0;\n"
    "wgmma.mma_async.sync.aligned.m64n256k16.f32.bf16.bf16 {"
    "%0, %1, %2, %3, %4, %5, %6, %7, %8, %9, %10, %11, %12, %13, %14, %15, %16, %17, %18, %19, %20, %21, %22, %23, %24, %25, %26, %27, %28, %29, %30, %31, "
    "%32, %33, %34, %35, %36, %37, %38, %39, %40, %41, %42, %43, %44, %45, %46, %47, %48, %49, %50, %51, %52, %53, %54, %55, %56, %57, %58, %59, %60, %61, %62, %63, "
    "%64, %65, %66, %67, %68, %69, %70, %71, %72, %73, %74, %75, %76, %77, %78, %79, %80, %81, %82, %83, %84, %85, %86, %87, %88, %89, %90, %91, %92, %93, %94, %95, "
    "%96, %97, %98, %99, %100, %101, %102, %103, %104, %105, %106, %107, %108, %109, %110, %111, %112, %113, %114, %115, %116, %117, %118, %119, %120, %121, %122, %123, %124, %125, %126, %127}, "
    "da, db, p, 1, 1, 0, 1;\n}\n"
    : "=f"(d[0]), "=f"(d[1]), "=f"(d[2]), "=f"(d[3]), "=f"(d[4]), "=f"(d[5]), "=f"(d[6]), "=f"(d[7]), "=f"(d[8]), "=f"(d[9]), "=f"(d[10]), "=f"(d[11]), "=f"(d[12]), "=f"(d[13]), "=f"(d[14]), "=f"(d[15]),
      "=f"(d[16]), "=f"(d[17]), "=f"(d[18]), "=f"(d[19]), "=f"(d[20]), "=f"(d[21]), "=f"(d[22]), "=f"(d[23]), "=f"(d[24]), "=f"(d[25]), "=f"(d[26]), "=f"(d[27]), "=f"(d[28]), "=f"(d[29]), "=f"(d[30]), "=f"(d[31]),
      "=f"(d[32]), "=f"(d[33]), "=f"(d[34]), "=f"(d[35]), "=f"(d[36]), "=f"(d[37]), "=f"(d[38]), "=f"(d[39]), "=f"(d[40]), "=f"(d[41]), "=f"(d[42]), "=f"(d[43]), "=f"(d[44]), "=f"(d[45]), "=f"(d[46]), "=f"(d[47]),
      "=f"(d[48]), "=f"(d[49]), "=f"(d[50]), "=f"(d[51]), "=f"(d[52]), "=f"(d[53]), "=f"(d[54]), "=f"(d[55]), "=f"(d[56]), "=f"(d[57]), "=f"(d[58]), "=f"(d[59]), "=f"(d[60]), "=f"(d[61]), "=f"(d[62]), "=f"(d[63]),
      "=f"(d[64]), "=f"(d[65]), "=f"(d[66]), "=f"(d[67]), "=f"(d[68]), "=f"(d[69]), "=f"(d[70]), "=f"(d[71]), "=f"(d[72]), "=f"(d[73]), "=f"(d[74]), "=f"(d[75]), "=f"(d[76]), "=f"(d[77]), "=f"(d[78]), "=f"(d[79]),
      "=f"(d[80]), "=f"(d[81]), "=f"(d[82]), "=f"(d[83]), "=f"(d[84]), "=f"(d[85]), "=f"(d[86]), "=f"(d[87]), "=f"(d[88]), "=f"(d[89]), "=f"(d[90]), "=f"(d[91]), "=f"(d[92]), "=f"(d[93]), "=f"(d[94]), "=f"(d[95]),
      "=f"(d[96]), "=f"(d[97]), "=f"(d[98]), "=f"(d[99]), "=f"(d[100]), "=f"(d[101]), "=f"(d[102]), "=f"(d[103]), "=f"(d[104]), "=f"(d[105]), "=f"(d[106]), "=f"(d[107]), "=f"(d[108]), "=f"(d[109]), "=f"(d[110]), "=f"(d[111]),
      "=f"(d[112]), "=f"(d[113]), "=f"(d[114]), "=f"(d[115]), "=f"(d[116]), "=f"(d[117]), "=f"(d[118]), "=f"(d[119]), "=f"(d[120]), "=f"(d[121]), "=f"(d[122]), "=f"(d[123]), "=f"(d[124]), "=f"(d[125]), "=f"(d[126]), "=f"(d[127])
    : "r"(alo), "r"(blo));
}
__device__ __forceinline__ void wg_gemm_acc(float (&d)[128], uint32_t alo, uint32_t blo) {
  asm volatile("{\n.reg .pred p;\n.reg .b64 da, db;\nmov.b64 da, {%128, 0x40000040};\nmov.b64 db, {%129, 0x40000040};\nsetp.eq.b32 p, 0, 0;\n"
    "wgmma.mma_async.sync.aligned.m64n256k16.f32.bf16.bf16 {"
    "%0, %1, %2, %3, %4, %5, %6, %7, %8, %9, %10, %11, %12, %13, %14, %15, %16, %17, %18, %19, %20, %21, %22, %23, %24, %25, %26, %27, %28, %29, %30, %31, "
    "%32, %33, %34, %35, %36, %37, %38, %39, %40, %41, %42, %43, %44, %45, %46, %47, %48, %49, %50, %51, %52, %53, %54, %55, %56, %57, %58, %59, %60, %61, %62, %63, "
    "%64, %65, %66, %67, %68, %69, %70, %71, %72, %73, %74, %75, %76, %77, %78, %79, %80, %81, %82, %83, %84, %85, %86, %87, %88, %89, %90, %91, %92, %93, %94, %95, "
    "%96, %97, %98, %99, %100, %101, %102, %103, %104, %105, %106, %107, %108, %109, %110, %111, %112, %113, %114, %115, %116, %117, %118, %119, %120, %121, %122, %123, %124, %125, %126, %127}, "
    "da, db, p, 1, 1, 0, 1;\n}\n"
    : "+f"(d[0]), "+f"(d[1]), "+f"(d[2]), "+f"(d[3]), "+f"(d[4]), "+f"(d[5]), "+f"(d[6]), "+f"(d[7]), "+f"(d[8]), "+f"(d[9]), "+f"(d[10]), "+f"(d[11]), "+f"(d[12]), "+f"(d[13]), "+f"(d[14]), "+f"(d[15]),
      "+f"(d[16]), "+f"(d[17]), "+f"(d[18]), "+f"(d[19]), "+f"(d[20]), "+f"(d[21]), "+f"(d[22]), "+f"(d[23]), "+f"(d[24]), "+f"(d[25]), "+f"(d[26]), "+f"(d[27]), "+f"(d[28]), "+f"(d[29]), "+f"(d[30]), "+f"(d[31]),
      "+f"(d[32]), "+f"(d[33]), "+f"(d[34]), "+f"(d[35]), "+f"(d[36]), "+f"(d[37]), "+f"(d[38]), "+f"(d[39]), "+f"(d[40]), "+f"(d[41]), "+f"(d[42]), "+f"(d[43]), "+f"(d[44]), "+f"(d[45]), "+f"(d[46]), "+f"(d[47]),
      "+f"(d[48]), "+f"(d[49]), "+f"(d[50]), "+f"(d[51]), "+f"(d[52]), "+f"(d[53]), "+f"(d[54]), "+f"(d[55]), "+f"(d[56]), "+f"(d[57]), "+f"(d[58]), "+f"(d[59]), "+f"(d[60]), "+f"(d[61]), "+f"(d[62]), "+f"(d[63]),
      "+f"(d[64]), "+f"(d[65]), "+f"(d[66]), "+f"(d[67]), "+f"(d[68]), "+f"(d[69]), "+f"(d[70]), "+f"(d[71]), "+f"(d[72]), "+f"(d[73]), "+f"(d[74]), "+f"(d[75]), "+f"(d[76]), "+f"(d[77]), "+f"(d[78]), "+f"(d[79]),
      "+f"(d[80]), "+f"(d[81]), "+f"(d[82]), "+f"(d[83]), "+f"(d[84]), "+f"(d[85]), "+f"(d[86]), "+f"(d[87]), "+f"(d[88]), "+f"(d[89]), "+f"(d[90]), "+f"(d[91]), "+f"(d[92]), "+f"(d[93]), "+f"(d[94]), "+f"(d[95]),
      "+f"(d[96]), "+f"(d[97]), "+f"(d[98]), "+f"(d[99]), "+f"(d[100]), "+f"(d[101]), "+f"(d[102]), "+f"(d[103]), "+f"(d[104]), "+f"(d[105]), "+f"(d[106]), "+f"(d[107]), "+f"(d[108]), "+f"(d[109]), "+f"(d[110]), "+f"(d[111]),
      "+f"(d[112]), "+f"(d[113]), "+f"(d[114]), "+f"(d[115]), "+f"(d[116]), "+f"(d[117]), "+f"(d[118]), "+f"(d[119]), "+f"(d[120]), "+f"(d[121]), "+f"(d[122]), "+f"(d[123]), "+f"(d[124]), "+f"(d[125]), "+f"(d[126]), "+f"(d[127])
    : "r"(alo), "r"(blo));
}
__device__ __forceinline__ void wg_gemm_init(float (&d)[96], uint32_t alo, uint32_t blo) {
  asm volatile("{\n.reg .pred p;\n.reg .b64 da, db;\nmov.b64 da, {%96, 0x40000040};\nmov.b64 db, {%97, 0x40000040};\nsetp.ne.b32 p, 0, 0;\n"
    "wgmma.mma_async.sync.aligned.m64n192k16.f32.bf16.bf16 {"
    "%0, %1, %2, %3, %4, %5, %6, %7, %8, %9, %10, %11, %12, %13, %14, %15, %16, %17, %18, %19, %20, %21, %22, %23, %24, %25, %26, %27, %28, %29, %30, %31, "
    "%32, %33, %34, %35, %36, %37, %38, %39, %40, %41, %42, %43, %44, %45, %46, %47, %48, %49, %50, %51, %52, %53, %54, %55, %56, %57, %58, %59, %60, %61, %62, %63, "
    "%64, %65, %66, %67, %68, %69, %70, %71, %72, %73, %74, %75, %76, %77, %78, %79, %80, %81, %82, %83, %84, %85, %86, %87, %88, %89, %90, %91, %92, %93, %94, %95}, "
    "da, db, p, 1, 1, 0, 1;\n}\n"
    : "=f"(d[0]), "=f"(d[1]), "=f"(d[2]), "=f"(d[3]), "=f"(d[4]), "=f"(d[5]), "=f"(d[6]), "=f"(d[7]), "=f"(d[8]), "=f"(d[9]), "=f"(d[10]), "=f"(d[11]), "=f"(d[12]), "=f"(d[13]), "=f"(d[14]), "=f"(d[15]),
      "=f"(d[16]), "=f"(d[17]), "=f"(d[18]), "=f"(d[19]), "=f"(d[20]), "=f"(d[21]), "=f"(d[22]), "=f"(d[23]), "=f"(d[24]), "=f"(d[25]), "=f"(d[26]), "=f"(d[27]), "=f"(d[28]), "=f"(d[29]), "=f"(d[30]), "=f"(d[31]),
      "=f"(d[32]), "=f"(d[33]), "=f"(d[34]), "=f"(d[35]), "=f"(d[36]), "=f"(d[37]), "=f"(d[38]), "=f"(d[39]), "=f"(d[40]), "=f"(d[41]), "=f"(d[42]), "=f"(d[43]), "=f"(d[44]), "=f"(d[45]), "=f"(d[46]), "=f"(d[47]),
      "=f"(d[48]), "=f"(d[49]), "=f"(d[50]), "=f"(d[51]), "=f"(d[52]), "=f"(d[53]), "=f"(d[54]), "=f"(d[55]), "=f"(d[56]), "=f"(d[57]), "=f"(d[58]), "=f"(d[59]), "=f"(d[60]), "=f"(d[61]), "=f"(d[62]), "=f"(d[63]),
      "=f"(d[64]), "=f"(d[65]), "=f"(d[66]), "=f"(d[67]), "=f"(d[68]), "=f"(d[69]), "=f"(d[70]), "=f"(d[71]), "=f"(d[72]), "=f"(d[73]), "=f"(d[74]), "=f"(d[75]), "=f"(d[76]), "=f"(d[77]), "=f"(d[78]), "=f"(d[79]),
      "=f"(d[80]), "=f"(d[81]), "=f"(d[82]), "=f"(d[83]), "=f"(d[84]), "=f"(d[85]), "=f"(d[86]), "=f"(d[87]), "=f"(d[88]), "=f"(d[89]), "=f"(d[90]), "=f"(d[91]), "=f"(d[92]), "=f"(d[93]), "=f"(d[94]), "=f"(d[95])
    : "r"(alo), "r"(blo));
}
__device__ __forceinline__ void wg_gemm_acc(float (&d)[96], uint32_t alo, uint32_t blo) {
  asm volatile("{\n.reg .pred p;\n.reg .b64 da, db;\nmov.b64 da, {%96, 0x40000040};\nmov.b64 db, {%97, 0x40000040};\nsetp.eq.b32 p, 0, 0;\n"
    "wgmma.mma_async.sync.aligned.m64n192k16.f32.bf16.bf16 {"
    "%0, %1, %2, %3, %4, %5, %6, %7, %8, %9, %10, %11, %12, %13, %14, %15, %16, %17, %18, %19, %20, %21, %22, %23, %24, %25, %26, %27, %28, %29, %30, %31, "
    "%32, %33, %34, %35, %36, %37, %38, %39, %40, %41, %42, %43, %44, %45, %46, %47, %48, %49, %50, %51, %52, %53, %54, %55, %56, %57, %58, %59, %60, %61, %62, %63, "
    "%64, %65, %66, %67, %68, %69, %70, %71, %72, %73, %74, %75, %76, %77, %78, %79, %80, %81, %82, %83, %84, %85, %86, %87, %88, %89, %90, %91, %92, %93, %94, %95}, "
    "da, db, p, 1, 1, 0, 1;\n}\n"
    : "+f"(d[0]), "+f"(d[1]), "+f"(d[2]), "+f"(d[3]), "+f"(d[4]), "+f"(d[5]), "+f"(d[6]), "+f"(d[7]), "+f"(d[8]), "+f"(d[9]), "+f"(d[10]), "+f"(d[11]), "+f"(d[12]), "+f"(d[13]), "+f"(d[14]), "+f"(d[15]),
      "+f"(d[16]), "+f"(d[17]), "+f"(d[18]), "+f"(d[19]), "+f"(d[20]), "+f"(d[21]), "+f"(d[22]), "+f"(d[23]), "+f"(d[24]), "+f"(d[25]), "+f"(d[26]), "+f"(d[27]), "+f"(d[28]), "+f"(d[29]), "+f"(d[30]), "+f"(d[31]),
      "+f"(d[32]), "+f"(d[33]), "+f"(d[34]), "+f"(d[35]), "+f"(d[36]), "+f"(d[37]), "+f"(d[38]), "+f"(d[39]), "+f"(d[40]), "+f"(d[41]), "+f"(d[42]), "+f"(d[43]), "+f"(d[44]), "+f"(d[45]), "+f"(d[46]), "+f"(d[47]),
      "+f"(d[48]), "+f"(d[49]), "+f"(d[50]), "+f"(d[51]), "+f"(d[52]), "+f"(d[53]), "+f"(d[54]), "+f"(d[55]), "+f"(d[56]), "+f"(d[57]), "+f"(d[58]), "+f"(d[59]), "+f"(d[60]), "+f"(d[61]), "+f"(d[62]), "+f"(d[63]),
      "+f"(d[64]), "+f"(d[65]), "+f"(d[66]), "+f"(d[67]), "+f"(d[68]), "+f"(d[69]), "+f"(d[70]), "+f"(d[71]), "+f"(d[72]), "+f"(d[73]), "+f"(d[74]), "+f"(d[75]), "+f"(d[76]), "+f"(d[77]), "+f"(d[78]), "+f"(d[79]),
      "+f"(d[80]), "+f"(d[81]), "+f"(d[82]), "+f"(d[83]), "+f"(d[84]), "+f"(d[85]), "+f"(d[86]), "+f"(d[87]), "+f"(d[88]), "+f"(d[89]), "+f"(d[90]), "+f"(d[91]), "+f"(d[92]), "+f"(d[93]), "+f"(d[94]), "+f"(d[95])
    : "r"(alo), "r"(blo));
}
__device__ __forceinline__ void wg_qk_init(float (&d)[64], uint32_t alo, uint32_t blo) {
  asm volatile("{\n.reg .pred p;\n.reg .b64 da, db;\nmov.b64 da, {%64, 0x40000040};\nmov.b64 db, {%65, 0x40000040};\nsetp.ne.b32 p, 0, 0;\n"
    "wgmma.mma_async.sync.aligned.m64n128k16.f32.bf16.bf16 {"
    "%0, %1, %2, %3, %4, %5, %6, %7, %8, %9, %10, %11, %12, %13, %14, %15, %16, %17, %18, %19, %20, %21, %22, %23, %24, %25, %26, %27, %28, %29, %30, %31, "
    "%32, %33, %34, %35, %36, %37, %38, %39, %40, %41, %42, %43, %44, %45, %46, %47, %48, %49, %50, %51, %52, %53, %54, %55, %56, %57, %58, %59, %60, %61, %62, %63}, "
    "da, db, p, 1, 1, 0, 0;\n}\n"
    : "=f"(d[0]), "=f"(d[1]), "=f"(d[2]), "=f"(d[3]), "=f"(d[4]), "=f"(d[5]), "=f"(d[6]), "=f"(d[7]), "=f"(d[8]), "=f"(d[9]), "=f"(d[10]), "=f"(d[11]), "=f"(d[12]), "=f"(d[13]), "=f"(d[14]), "=f"(d[15]),
      "=f"(d[16]), "=f"(d[17]), "=f"(d[18]), "=f"(d[19]), "=f"(d[20]), "=f"(d[21]), "=f"(d[22]), "=f"(d[23]), "=f"(d[24]), "=f"(d[25]), "=f"(d[26]), "=f"(d[27]), "=f"(d[28]), "=f"(d[29]), "=f"(d[30]), "=f"(d[31]),
      "=f"(d[32]), "=f"(d[33]), "=f"(d[34]), "=f"(d[35]), "=f"(d[36]), "=f"(d[37]), "=f"(d[38]), "=f"(d[39]), "=f"(d[40]), "=f"(d[41]), "=f"(d[42]), "=f"(d[43]), "=f"(d[44]), "=f"(d[45]), "=f"(d[46]), "=f"(d[47]),
      "=f"(d[48]), "=f"(d[49]), "=f"(d[50]), "=f"(d[51]), "=f"(d[52]), "=f"(d[53]), "=f"(d[54]), "=f"(d[55]), "=f"(d[56]), "=f"(d[57]), "=f"(d[58]), "=f"(d[59]), "=f"(d[60]), "=f"(d[61]), "=f"(d[62]), "=f"(d[63])
    : "r"(alo), "r"(blo));
}
__device__ __forceinline__ void wg_qk_acc(float (&d)[64], uint32_t alo, uint32_t blo) {
  asm volatile("{\n.reg .pred p;\n.reg .b64 da, db;\nmov.b64 da, {%64, 0x40000040};\nmov.b64 db, {%65, 0x40000040};\nsetp.eq.b32 p, 0, 0;\n"
    "wgmma.mma_async.sync.aligned.m64n128k16.f32.bf16.bf16 {"
    "%0, %1, %2, %3, %4, %5, %6, %7, %8, %9, %10, %11, %12, %13, %14, %15, %16, %17, %18, %19, %20, %21, %22, %23, %24, %25, %26, %27, %28, %29, %30, %31, "
    "%32, %33, %34, %35, %36, %37, %38, %39, %40, %41, %42, %43, %44, %45, %46, %47, %48, %49, %50, %51, %52, %53, %54, %55, %56, %57, %58, %59, %60, %61, %62, %63}, "
    "da, db, p, 1, 1, 0, 0;\n}\n"
    : "+f"(d[0]), "+f"(d[1]), "+f"(d[2]), "+f"(d[3]), "+f"(d[4]), "+f"(d[5]), "+f"(d[6]), "+f"(d[7]), "+f"(d[8]), "+f"(d[9]), "+f"(d[10]), "+f"(d[11]), "+f"(d[12]), "+f"(d[13]), "+f"(d[14]), "+f"(d[15]),
      "+f"(d[16]), "+f"(d[17]), "+f"(d[18]), "+f"(d[19]), "+f"(d[20]), "+f"(d[21]), "+f"(d[22]), "+f"(d[23]), "+f"(d[24]), "+f"(d[25]), "+f"(d[26]), "+f"(d[27]), "+f"(d[28]), "+f"(d[29]), "+f"(d[30]), "+f"(d[31]),
      "+f"(d[32]), "+f"(d[33]), "+f"(d[34]), "+f"(d[35]), "+f"(d[36]), "+f"(d[37]), "+f"(d[38]), "+f"(d[39]), "+f"(d[40]), "+f"(d[41]), "+f"(d[42]), "+f"(d[43]), "+f"(d[44]), "+f"(d[45]), "+f"(d[46]), "+f"(d[47]),
      "+f"(d[48]), "+f"(d[49]), "+f"(d[50]), "+f"(d[51]), "+f"(d[52]), "+f"(d[53]), "+f"(d[54]), "+f"(d[55]), "+f"(d[56]), "+f"(d[57]), "+f"(d[58]), "+f"(d[59]), "+f"(d[60]), "+f"(d[61]), "+f"(d[62]), "+f"(d[63])
    : "r"(alo), "r"(blo));
}
__device__ __forceinline__ void wg_qk64_init(float (&d)[64], uint32_t alo, uint32_t blo) {
  asm volatile("{\n.reg .pred p;\n.reg .b64 da, db;\nmov.b64 da, {%32, 0x40000040};\nmov.b64 db, {%33, 0x40000040};\nsetp.ne.b32 p, 0, 0;\n"
    "wgmma.mma_async.sync.aligned.m64n64k16.f32.bf16.bf16 {"
    "%0, %1, %2, %3, %4, %5, %6, %7, %8, %9, %10, %11, %12, %13, %14, %15, %16, %17, %18, %19, %20, %21, %22, %23, %24, %25, %26, %27, %28, %29, %30, %31}, "
    "da, db, p, 1, 1, 0, 0;\n}\n"
    : "=f"(d[0]), "=f"(d[1]), "=f"(d[2]), "=f"(d[3]), "=f"(d[4]), "=f"(d[5]), "=f"(d[6]), "=f"(d[7]), "=f"(d[8]), "=f"(d[9]), "=f"(d[10]), "=f"(d[11]), "=f"(d[12]), "=f"(d[13]), "=f"(d[14]), "=f"(d[15]),
      "=f"(d[16]), "=f"(d[17]), "=f"(d[18]), "=f"(d[19]), "=f"(d[20]), "=f"(d[21]), "=f"(d[22]), "=f"(d[23]), "=f"(d[24]), "=f"(d[25]), "=f"(d[26]), "=f"(d[27]), "=f"(d[28]), "=f"(d[29]), "=f"(d[30]), "=f"(d[31])
    : "r"(alo), "r"(blo));
}
__device__ __forceinline__ void wg_qk64_acc(float (&d)[64], uint32_t alo, uint32_t blo) {
  asm volatile("{\n.reg .pred p;\n.reg .b64 da, db;\nmov.b64 da, {%32, 0x40000040};\nmov.b64 db, {%33, 0x40000040};\nsetp.eq.b32 p, 0, 0;\n"
    "wgmma.mma_async.sync.aligned.m64n64k16.f32.bf16.bf16 {"
    "%0, %1, %2, %3, %4, %5, %6, %7, %8, %9, %10, %11, %12, %13, %14, %15, %16, %17, %18, %19, %20, %21, %22, %23, %24, %25, %26, %27, %28, %29, %30, %31}, "
    "da, db, p, 1, 1, 0, 0;\n}\n"
    : "+f"(d[0]), "+f"(d[1]), "+f"(d[2]), "+f"(d[3]), "+f"(d[4]), "+f"(d[5]), "+f"(d[6]), "+f"(d[7]), "+f"(d[8]), "+f"(d[9]), "+f"(d[10]), "+f"(d[11]), "+f"(d[12]), "+f"(d[13]), "+f"(d[14]), "+f"(d[15]),
      "+f"(d[16]), "+f"(d[17]), "+f"(d[18]), "+f"(d[19]), "+f"(d[20]), "+f"(d[21]), "+f"(d[22]), "+f"(d[23]), "+f"(d[24]), "+f"(d[25]), "+f"(d[26]), "+f"(d[27]), "+f"(d[28]), "+f"(d[29]), "+f"(d[30]), "+f"(d[31])
    : "r"(alo), "r"(blo));
}
__device__ __forceinline__ void wg_pv_init(float (&d)[64], const uint32_t* a, uint32_t blo) {
  asm volatile("{\n.reg .pred p;\n.reg .b64 da, db;\nmov.b64 db, {%68, 0x40000040};\nsetp.ne.b32 p, 0, 0;\n"
    "wgmma.mma_async.sync.aligned.m64n128k16.f32.bf16.bf16 {"
    "%0, %1, %2, %3, %4, %5, %6, %7, %8, %9, %10, %11, %12, %13, %14, %15, %16, %17, %18, %19, %20, %21, %22, %23, %24, %25, %26, %27, %28, %29, %30, %31, "
    "%32, %33, %34, %35, %36, %37, %38, %39, %40, %41, %42, %43, %44, %45, %46, %47, %48, %49, %50, %51, %52, %53, %54, %55, %56, %57, %58, %59, %60, %61, %62, %63}, "
    "{%64, %65, %66, %67}, db, p, 1, 1, 1;\n}\n"
    : "=f"(d[0]), "=f"(d[1]), "=f"(d[2]), "=f"(d[3]), "=f"(d[4]), "=f"(d[5]), "=f"(d[6]), "=f"(d[7]), "=f"(d[8]), "=f"(d[9]), "=f"(d[10]), "=f"(d[11]), "=f"(d[12]), "=f"(d[13]), "=f"(d[14]), "=f"(d[15]),
      "=f"(d[16]), "=f"(d[17]), "=f"(d[18]), "=f"(d[19]), "=f"(d[20]), "=f"(d[21]), "=f"(d[22]), "=f"(d[23]), "=f"(d[24]), "=f"(d[25]), "=f"(d[26]), "=f"(d[27]), "=f"(d[28]), "=f"(d[29]), "=f"(d[30]), "=f"(d[31]),
      "=f"(d[32]), "=f"(d[33]), "=f"(d[34]), "=f"(d[35]), "=f"(d[36]), "=f"(d[37]), "=f"(d[38]), "=f"(d[39]), "=f"(d[40]), "=f"(d[41]), "=f"(d[42]), "=f"(d[43]), "=f"(d[44]), "=f"(d[45]), "=f"(d[46]), "=f"(d[47]),
      "=f"(d[48]), "=f"(d[49]), "=f"(d[50]), "=f"(d[51]), "=f"(d[52]), "=f"(d[53]), "=f"(d[54]), "=f"(d[55]), "=f"(d[56]), "=f"(d[57]), "=f"(d[58]), "=f"(d[59]), "=f"(d[60]), "=f"(d[61]), "=f"(d[62]), "=f"(d[63])
    : "r"(a[0]), "r"(a[1]), "r"(a[2]), "r"(a[3]), "r"(blo));
}
__device__ __forceinline__ void wg_pv_acc(float (&d)[64], const uint32_t* a, uint32_t blo) {
  asm volatile("{\n.reg .pred p;\n.reg .b64 da, db;\nmov.b64 db, {%68, 0x40000040};\nsetp.eq.b32 p, 0, 0;\n"
    "wgmma.mma_async.sync.aligned.m64n128k16.f32.bf16.bf16 {"
    "%0, %1, %2, %3, %4, %5, %6, %7, %8, %9, %10, %11, %12, %13, %14, %15, %16, %17, %18, %19, %20, %21, %22, %23, %24, %25, %26, %27, %28, %29, %30, %31, "
    "%32, %33, %34, %35, %36, %37, %38, %39, %40, %41, %42, %43, %44, %45, %46, %47, %48, %49, %50, %51, %52, %53, %54, %55, %56, %57, %58, %59, %60, %61, %62, %63}, "
    "{%64, %65, %66, %67}, db, p, 1, 1, 1;\n}\n"
    : "+f"(d[0]), "+f"(d[1]), "+f"(d[2]), "+f"(d[3]), "+f"(d[4]), "+f"(d[5]), "+f"(d[6]), "+f"(d[7]), "+f"(d[8]), "+f"(d[9]), "+f"(d[10]), "+f"(d[11]), "+f"(d[12]), "+f"(d[13]), "+f"(d[14]), "+f"(d[15]),
      "+f"(d[16]), "+f"(d[17]), "+f"(d[18]), "+f"(d[19]), "+f"(d[20]), "+f"(d[21]), "+f"(d[22]), "+f"(d[23]), "+f"(d[24]), "+f"(d[25]), "+f"(d[26]), "+f"(d[27]), "+f"(d[28]), "+f"(d[29]), "+f"(d[30]), "+f"(d[31]),
      "+f"(d[32]), "+f"(d[33]), "+f"(d[34]), "+f"(d[35]), "+f"(d[36]), "+f"(d[37]), "+f"(d[38]), "+f"(d[39]), "+f"(d[40]), "+f"(d[41]), "+f"(d[42]), "+f"(d[43]), "+f"(d[44]), "+f"(d[45]), "+f"(d[46]), "+f"(d[47]),
      "+f"(d[48]), "+f"(d[49]), "+f"(d[50]), "+f"(d[51]), "+f"(d[52]), "+f"(d[53]), "+f"(d[54]), "+f"(d[55]), "+f"(d[56]), "+f"(d[57]), "+f"(d[58]), "+f"(d[59]), "+f"(d[60]), "+f"(d[61]), "+f"(d[62]), "+f"(d[63])
    : "r"(a[0]), "r"(a[1]), "r"(a[2]), "r"(a[3]), "r"(blo));
}

struct Cons {
  uint32_t sb;
  uint32_t rel;
  uint32_t p0, p1;
  uint32_t lead, round, fpar;
};

template <uint32_t OFF, uint32_t GROUP> __device__ __forceinline__ void tile_write(const uint32_t (&pk)[32], uint32_t base) {
  const uint32_t lane = threadIdx.x & 31, wq = (threadIdx.x >> 5) & 3;
  const uint32_t a = base + (wq * 16 + (lane & 15)) * 128 + (((lane >> 4) ^ (lane & 7)) << 4);
#define TW(j) stmatrix_x4<OFF + (j >> 2) * GROUP>(a ^ ((j & 3) * 32), pk[4 * j + 0], pk[4 * j + 1], pk[4 * j + 2], pk[4 * j + 3])
  TW(0); TW(1); TW(2); TW(3); TW(4); TW(5); TW(6); TW(7);
#undef TW
}
template <uint32_t OFF, uint32_t GROUP, int A0> __device__ __forceinline__ void tile_pack_write(const float (&acc)[128], uint32_t (&pk)[32], uint32_t base) {
  const uint32_t lane = threadIdx.x & 31, wq = (threadIdx.x >> 5) & 3;
  const uint32_t a = base + (wq * 16 + (lane & 15)) * 128 + (((lane >> 4) ^ (lane & 7)) << 4);
#define TW(j) \
  pk[4 * j + 0] = v_pack(acc[A0 + 8 * j + 0], acc[A0 + 8 * j + 1]); pk[4 * j + 1] = v_pack(acc[A0 + 8 * j + 2], acc[A0 + 8 * j + 3]); \
  pk[4 * j + 2] = v_pack(acc[A0 + 8 * j + 4], acc[A0 + 8 * j + 5]); pk[4 * j + 3] = v_pack(acc[A0 + 8 * j + 6], acc[A0 + 8 * j + 7]); \
  stmatrix_x4<OFF + (j >> 2) * GROUP>(a ^ ((j & 3) * 32), pk[4 * j + 0], pk[4 * j + 1], pk[4 * j + 2], pk[4 * j + 3])
  TW(0); TW(1); TW(2); TW(3); TW(4); TW(5); TW(6); TW(7);
#undef TW
}
__device__ __forceinline__ void stage_write(const uint32_t (&pk)[32], int w, const Cons& cs) {
  mbar_wait<BAR(B_STGE)>(cs.sb + w * 8, (cs.round & 1) ^ 1);
  tile_write<OFF_STG, 8192>(pk, cs.sb + w * 16384);
}
__device__ __forceinline__ void stage_publish(int w, Cons& cs) {
  fence_async_smem();
  __syncwarp();
  mbar_arrive_if<BAR(B_STGF)>(cs.sb + w * 8, (threadIdx.x & 31) == 0);
  cs.round++;
}

template <int ST, bool INIT, int NA> __device__ __forceinline__ void g_issue(float (&acc)[NA], uint32_t wa) {
  constexpr uint32_t A = dlo(OFF_A + ST * 16384, 16), B = dlo(OFF_B + ST * 32768, NA == 128 ? 8192 : 4096);
  wg_fence();
  if (INIT) wg_gemm_init(acc, A + wa, B); else wg_gemm_acc(acc, A + wa, B);
#pragma unroll
  for (int kk = 1; kk < 4; kk++) wg_gemm_acc(acc, A + wa + kk * 2, B + (NA == 128 ? kk * 128 : (kk >> 1) * 768 + (kk & 1) * 128));
  wg_commit();
}
template <int NA>
__device__ __forceinline__ uint32_t gemm_tile(float (&acc)[NA], int nk4, int idx, int w, Cons& cs, uint32_t pend, const uint32_t (&pkA)[32], const uint32_t (&pkB)[32]) {
  const uint32_t wa = w * 512, sb = cs.sb, rel = cs.rel;
  constexpr int SA = NA == 128 ? STGA : STGAL, SBB = NA == 128 ? STGB : STGBL;
#define HOOK(n) \
  if (n == LPUBP && (pend & 8)) stage_publish(w, cs); \
  if (LHS && n == 0 && (pend & 16) && w == 0) bar_sync(5, 256); \
  if (n == SA && (pend & 1)) stage_write(pkA, w, cs); \
  if (n == SA + PUBD && (pend & 1)) { stage_publish(w, cs); pend &= 6; } \
  if (n == SBB && (pend & 2)) { stage_write(pkB, w, cs); pend = 4; } \
  if (n == SBB + PUBD && (pend & 4)) { stage_publish(w, cs); pend = 0; }
  mbar_wait<BAR(B_FULL + 0)>(sb, cs.p0);
  g_issue<0, true>(acc, wa);
  HOOK(0);
  mbar_wait<BAR(B_FULL + 1)>(sb, cs.p1);
  g_issue<1, false>(acc, wa);
  HOOK(2);
  wg_wait<1>(); T4K();
  mbar_arrive_cl<BAR(B_EMPTY + 0)>(rel);
  HOOK(3);
  mbar_wait<BAR(B_FULL + 2)>(sb, cs.p0);
  g_issue<2, false>(acc, wa);
  HOOK(4);
  wg_wait<1>(); T4K();
  mbar_arrive_cl<BAR(B_EMPTY + 1)>(rel);
  HOOK(5);
  mbar_wait<BAR(B_FULL + 3)>(sb, cs.p1);
  g_issue<3, false>(acc, wa);
  HOOK(6);
  const uint32_t ncode = item(sb, idx + 1);
  wg_wait<1>(); T4K();
  mbar_arrive_cl<BAR(B_EMPTY + 2)>(rel);
  HOOK(7);
  cs.p0 ^= 1; cs.p1 ^= 1;
  const bool final_tile = (ncode >> 9) == K_END;
  constexpr int LD = NA == 128 ? LEADN : LEADL;
#pragma unroll 1
  for (int q = 1; q < nk4; q++) {
    const bool tail = q == nk4 - 1;
    mbar_wait<BAR(B_FULL + 0)>(sb, cs.p0);
    g_issue<0, false>(acc, wa);
    HOOK(8);
    wg_wait<1>(); T4K();
    mbar_arrive_cl<BAR(B_EMPTY + 3)>(rel);
    HOOK(9);
    mbar_wait<BAR(B_FULL + 1)>(sb, cs.p1);
    uint32_t rel0 = rel;
    if (LEADF == 3 && NA == 128 && final_tile && tail && w == 1) {
      wg_wait<0>();
      mbar_arrive_cl<BAR(B_EMPTY + 0)>(rel);
      rel0 = 0;
      mbar_wait<BAR(B_LEAD)>(sb, cs.lead);
    }
    g_issue<1, false>(acc, wa);
    HOOK(10);
    wg_wait<1>(); T4K();
    mbar_arrive_cl<BAR(B_EMPTY + 0)>(rel0);
    HOOK(11);
    mbar_wait<BAR(B_FULL + 2)>(sb, cs.p0);
    uint32_t rel1 = rel;
    if (LD == 2 && tail && w == 1 && !(LEADF == 3 && NA == 128 && final_tile)) {
      if (EREL) { wg_wait<0>(); mbar_arrive_cl<BAR(B_EMPTY + 1)>(rel); rel1 = 0; }
      mbar_wait<BAR(B_LEAD)>(sb, cs.lead);
    }
    g_issue<2, false>(acc, wa);
    HOOK(12);
    wg_wait<1>(); T4K();
    mbar_arrive_cl<BAR(B_EMPTY + 1)>(rel1);
    HOOK(13);
    mbar_wait<BAR(B_FULL + 3)>(sb, cs.p1);
    if (LD == 1 && tail && w == 1) mbar_wait<BAR(B_LEAD)>(sb, cs.lead);
    g_issue<3, false>(acc, wa);
    mbar_arrive_if<BAR(B_LEAD)>(sb, tail && threadIdx.x == 128);
    HOOK(14);
    wg_wait<1>(); T4K();
    mbar_arrive_cl<BAR(B_EMPTY + 2)>(rel);
    cs.p0 ^= 1; cs.p1 ^= 1;
  }
#undef HOOK
  cs.lead ^= 1;
  wg_wait<0>();
  fence_regs(acc);
  T4Q(__float_as_uint(acc[0]));
  mbar_arrive_cl<BAR(B_EMPTY + 3)>(rel);
  return ncode;
}

__device__ __forceinline__ void local_probs(bool first, const float (&S)[3][4], uint32_t (&pb)[4]) {
  const int lane = threadIdx.x & 31, g = lane >> 2, t = lane & 3;
  const bool c0 = 2 * t > g, c1 = 2 * t + 1 > g;
  float x0 = c0 ? S[0][0] : S[1][0], x1 = c1 ? S[0][1] : S[1][1], y0 = c0 ? S[1][2] : S[2][2], y1 = c1 ? S[1][3] : S[2][3];
  if (first && c0) x0 = -INFINITY;
  if (first && c1) x1 = -INFINITY;
  float m0 = fmaxf(x0, x1), m1 = fmaxf(y0, y1);
  if (LSH & 1) {
    m0 = fmaxf(fmaxf(m0, __shfl_xor_sync(0xffffffffu, m0, 1)), fmaxf(__shfl_xor_sync(0xffffffffu, m0, 2), __shfl_xor_sync(0xffffffffu, m0, 3)));
    m1 = fmaxf(fmaxf(m1, __shfl_xor_sync(0xffffffffu, m1, 1)), fmaxf(__shfl_xor_sync(0xffffffffu, m1, 2), __shfl_xor_sync(0xffffffffu, m1, 3)));
  } else {
    m0 = fmaxf(m0, __shfl_xor_sync(0xffffffffu, m0, 1)); m1 = fmaxf(m1, __shfl_xor_sync(0xffffffffu, m1, 1));
    m0 = fmaxf(m0, __shfl_xor_sync(0xffffffffu, m0, 2)); m1 = fmaxf(m1, __shfl_xor_sync(0xffffffffu, m1, 2));
  }
  constexpr float C = 0.17677669529663687f * 1.4426950408889634f;
  const float b0 = -m0 * C, b1 = -m1 * C;
  x0 = ex2(fmaf(x0, C, b0)); x1 = ex2(fmaf(x1, C, b0)); y0 = ex2(fmaf(y0, C, b1)); y1 = ex2(fmaf(y1, C, b1));
  auto qs = [](float v) { return (LSH & 2) ? (v + __shfl_xor_sync(0xffffffffu, v, 1)) + (__shfl_xor_sync(0xffffffffu, v, 2) + __shfl_xor_sync(0xffffffffu, v, 3)) : quad_sum(v); };
  const float l0 = rcp(qs(x0 + x1)), l1 = rcp(qs(y0 + y1));
  const uint32_t px = pack_bf16(x0 * l0, x1 * l0), py = pack_bf16(y0 * l1, y1 * l1);
  const uint32_t m = (c0 ? 0xffffu : 0u) | (c1 ? 0xffff0000u : 0u);
  pb[0] = px & m; pb[1] = px & ~m; pb[2] = py & m; pb[3] = py & ~m;
}
__device__ __forceinline__ void local_epilogue(const float (&acc)[96], uint32_t code, int w, Cons& cs) {
  const uint32_t lane = threadIdx.x & 31, wq = (threadIdx.x >> 5) & 3, cw = w * 4 + wq;
  const bool has_halo = (code & 15) != 0;
  const uint32_t hpar = cs.fpar >> 1;
  cs.fpar ^= has_halo ? 2 : 0;
  uint32_t kf[3][8], vt[3][8];
#pragma unroll
  for (int j = 0; j < 8; j++) { kf[2][j] = pack_bf16(acc[32 + 4 * j + 2], acc[32 + 4 * j + 3]); vt[2][j] = transpose8(pack_bf16(acc[64 + 4 * j + 2], acc[64 + 4 * j + 3])); }
  const uint32_t xa = cs.sb + OFF_STG + 8192 + w * 16384 + wq * 2048 + lane * 16;
  mbar_wait<BAR(B_STGE)>(cs.sb + w * 8, (cs.round & 1) ^ 1);
  sts128<0>(xa, &kf[2][0]); sts128<512>(xa, &kf[2][4]); sts128<1024>(xa, &vt[2][0]); sts128<1536>(xa, &vt[2][4]);
  if (cw == 3) bar_arrive(4, 160);
  uint32_t q[8][2];
#pragma unroll
  for (int j = 0; j < 8; j++) {
    q[j][0] = pack_bf16(acc[4 * j], acc[4 * j + 1]); q[j][1] = pack_bf16(acc[4 * j + 2], acc[4 * j + 3]);
    kf[1][j] = pack_bf16(acc[32 + 4 * j], acc[32 + 4 * j + 1]); vt[1][j] = transpose8(pack_bf16(acc[64 + 4 * j], acc[64 + 4 * j + 1]));
  }
  bar_sync(3 + w, 128 + 32 * w);
  uint32_t ra = xa - (wq == 0 ? 16384 - 3 * 2048 : 2048);
  if (cw == 0) {
    ra = has_halo ? cs.sb + OFF_HALO + lane * 16 : xa;
    if (has_halo) mbar_wait<BAR(B_HFULL)>(cs.sb, hpar);
  }
  lds128<0>(&kf[0][0], ra); lds128<512>(&kf[0][4], ra); lds128<1024>(&vt[0][0], ra); lds128<1536>(&vt[0][4], ra);
  float z;
  asm volatile("ld.shared.f32 %0, [%1+%2];" : "=f"(z) : "r"(cs.sb), "n"(OFF_FILLS + 4) : "memory");
  float S[2][3][4];
#pragma unroll
  for (int u = 0; u < 2; u++)
#pragma unroll
    for (int n = 0; n < 3; n++) mma16816z(S[u][n], q[4 * u][0], q[4 * u][1], q[4 * u + 1][0], q[4 * u + 1][1], kf[n][4 * u], kf[n][4 * u + 1], z);
#pragma unroll
  for (int u = 0; u < 2; u++)
#pragma unroll
    for (int n = 0; n < 3; n++) mma16816(S[u][n], q[4 * u + 2][0], q[4 * u + 2][1], q[4 * u + 3][0], q[4 * u + 3][1], kf[n][4 * u + 2], kf[n][4 * u + 3]);
  uint32_t pb[2][4];
#pragma unroll
  for (int u = 0; u < 2; u++) local_probs(cw == 0 && !has_halo, S[u], pb[u]);
  const uint32_t oa = cs.sb + w * 16384 + (wq * 16 + (lane & 7)) * 128 + (((lane >> 3) ^ (lane & 7)) << 4);
#pragma unroll
  for (int u = 0; u < 2; u++)
#pragma unroll
    for (int hf = 0; hf < 2; hf++) {
      float O[2][4];
#pragma unroll
      for (int mt = 0; mt < 2; mt++) {
        O[mt][0] = O[mt][1] = O[mt][2] = O[mt][3] = 0.f;
        mma16816(O[mt], vt[hf][4 * u + 2 * mt], vt[hf][4 * u + 2 * mt + 1], vt[hf + 1][4 * u + 2 * mt], vt[hf + 1][4 * u + 2 * mt + 1], pb[u][2 * hf], pb[u][2 * hf + 1]);
      }
      const uint32_t o0 = pack_bf16(O[0][0], O[0][1]), o1 = pack_bf16(O[0][2], O[0][3]), o2 = pack_bf16(O[1][0], O[1][1]), o3 = pack_bf16(O[1][2], O[1][3]);
      if (hf == 0) stmatrix_x4_trans<OFF_STG>(oa ^ (u * 64), o0, o1, o2, o3); else stmatrix_x4_trans<OFF_STG + 1024>(oa ^ (u * 64), o0, o1, o2, o3);
    }
  mbar_arrive_if<BAR(B_HEMPTY)>(cs.sb, has_halo && threadIdx.x == 128);
}

constexpr float SCALE_LOG2 = 0.08838834764831845f * 1.4426950408889634f;
#define SUM_LO 8.673617379884035e-19f
#define SUM_HI 1152921504606846976.f
template <int J0> __device__ __forceinline__ void causal_mask(float (&S)[64], int r) {
#pragma unroll
  for (int j = 0; j < 8; j++) {
    if (8 * j > r) S[4 * (J0 + j) + 0] = -INFINITY;
    if (8 * j + 1 > r) S[4 * (J0 + j) + 1] = -INFINITY;
    if (8 * j - 8 > r) S[4 * (J0 + j) + 2] = -INFINITY;
    if (8 * j - 7 > r) S[4 * (J0 + j) + 3] = -INFINITY;
  }
}
__device__ __forceinline__ float v_ex2(float x) { float y; asm volatile("ex2.approx.ftz.f32 %0, %1;" : "=f"(y) : "f"(x)); return y; }
__device__ __forceinline__ float v_add(float a, float b) { float y; asm volatile("add.f32 %0, %1, %2;" : "=f"(y) : "f"(a), "f"(b)); return y; }
__device__ __forceinline__ float v_mul(float a, float b) { float y; asm volatile("mul.f32 %0, %1, %2;" : "=f"(y) : "f"(a), "f"(b)); return y; }
template <int MJ> __device__ __forceinline__ float exp_el(float x, int j, int e, int r) {
  float p = v_ex2(x);
  if (j >= MJ) asm volatile("{\n.reg .pred q;\nsetp.lt.s32 q, %1, %2;\n@q mov.b32 %0, 0f00000000;\n}\n" : "+f"(p) : "r"(r), "r"(8 * (j - MJ) + (e & 1) - 4 * (e & 2)));
  return p;
}
template <int J0, int J1, int MJ = 16> __device__ __forceinline__ void exp_inplace(float (&S)[64], float& l0, float& l1, int r = 0) {
#pragma unroll
  for (int j = J0; j < J1; j++) {
#pragma unroll
    for (int e = 0; e < 4; e++) S[4 * j + e] = exp_el<MJ>(S[4 * j + e], j, e, r);
    l0 = v_add(l0, S[4 * j + 0]); l1 = v_add(l1, S[4 * j + 2]); l0 = v_add(l0, S[4 * j + 1]); l1 = v_add(l1, S[4 * j + 3]);
  }
}
template <int JS, int MJ, bool OUT>
__device__ __forceinline__ void exp_pack(float (&S)[64], uint32_t (&P)[32], float& l0, float& l1, int r, const float (&O)[64], float a0, float a1, uint32_t (&pk)[32]) {
#pragma unroll
  for (int j = JS; j < 16; j++) {
    const float p0 = exp_el<MJ>(S[4 * j + 0], j, 0, r), p1 = exp_el<MJ>(S[4 * j + 1], j, 1, r), p2 = exp_el<MJ>(S[4 * j + 2], j, 2, r), p3 = exp_el<MJ>(S[4 * j + 3], j, 3, r);
#pragma unroll
    for (int k = (j - JS) * JS / (16 - JS); k < (j + 1 - JS) * JS / (16 - JS); k++) { P[2 * k] = v_pack(S[4 * k + 0], S[4 * k + 1]); P[2 * k + 1] = v_pack(S[4 * k + 2], S[4 * k + 3]); }
    if (OUT) {
#pragma unroll
      for (int k = (j - JS) * 16 / (16 - JS); k < (j + 1 - JS) * 16 / (16 - JS); k++) {
        pk[2 * k] = v_pack(v_mul(O[4 * k + 0], a0), v_mul(O[4 * k + 1], a0)); pk[2 * k + 1] = v_pack(v_mul(O[4 * k + 2], a1), v_mul(O[4 * k + 3], a1));
      }
    }
    l0 = v_add(l0, p0); l1 = v_add(l1, p2); l0 = v_add(l0, p1); l1 = v_add(l1, p3);
    P[2 * j] = v_pack(p0, p1); P[2 * j + 1] = v_pack(p2, p3);
  }
}
__device__ __forceinline__ void pin_after(float a, float b) {
  asm volatile("{\n.reg .pred p;\nsetp.eq.u32 p, %0, 0xffffffff;\n@p st.shared.b32 [%1], %1;\n}\n" ::"r"(__float_as_uint(a)), "r"(__float_as_uint(b)) : "memory");
}
template <bool HALF> __device__ __forceinline__ void issue_qk(float (&S)[64], uint32_t qlo, uint32_t klo) {
  wg_fence();
  if (HALF) wg_qk64_init(S, qlo, klo); else wg_qk_init(S, qlo, klo);
#pragma unroll
  for (int kk = 1; kk < 8; kk++) {
    const uint32_t off = ((kk >> 2) * 16384 + (kk & 3) * 32) >> 4;
    if (HALF) wg_qk64_acc(S, qlo + off, klo + off); else wg_qk_acc(S, qlo + off, klo + off);
  }
  wg_commit();
}
template <int NK, int ACC> __device__ __forceinline__ void issue_pv(float (&O)[64], const uint32_t (&P)[32], uint32_t vlo) {
  wg_fence();
  if (ACC) wg_pv_acc(O, &P[0], vlo); else wg_pv_init(O, &P[0], vlo);
#pragma unroll
  for (int kk = 1; kk < NK; kk++) wg_pv_acc(O, &P[4 * kk], vlo + kk * 128);
  wg_commit();
}
__device__ __forceinline__ uint32_t row_norm(float l0, float l1, float& a0, float& a1) {
  const float q0 = quad_sum(l0), q1 = quad_sum(l1);
  a0 = rcp(q0); a1 = rcp(q1);
  return __reduce_or_sync(0xffffffffu, (q0 >= SUM_LO && q0 <= SUM_HI && q1 >= SUM_LO && q1 <= SUM_HI) ? 0u : 1u);
}
__device__ __forceinline__ void slow_item(float (&O)[64], float& a0, float& a1, int head, int tile, uint32_t qbase, int w) {
  const int lane = threadIdx.x & 31, g = lane >> 2, t = lane & 3;
  const int rw = w * 64 + (int)__reduce_or_sync(0xffffffffu, (threadIdx.x >> 1) & 48);
  const int row0 = tile * 128 + rw;
  const uint32_t qa_ = qbase + (rw + g) * 128 + ((t ^ g) << 4);
  const __nv_bfloat16* kp = g_kv + ((size_t)head * SEQ + g) * 256 + 8 * t;
  const __nv_bfloat16* vp = g_kv + ((size_t)head * SEQ + 2 * t) * 256 + 128 + g;
  float m0 = -INFINITY, m1 = -INFINITY, l0 = 0.f, l1 = 0.f;
#pragma unroll
  for (int i = 0; i < 64; i++) O[i] = 0.f;
#pragma unroll 1
  for (int key0 = 0; key0 < row0 + 16; key0 += 16) {
    float c[2][4] = {{0.f, 0.f, 0.f, 0.f}, {0.f, 0.f, 0.f, 0.f}};
#pragma unroll 1
    for (int cc = 0; cc < 4; cc++) {
      uint32_t qa[4], qb[4];
      const uint32_t a = (qa_ ^ ((cc & 1) * 64)) + (cc >> 1) * 16384;
      lds128<0>(qa, a); lds128<1024>(qb, a);
#pragma unroll
      for (int n = 0; n < 2; n++) {
        const uint4 kf = ldg128(kp + (size_t)(key0 + 8 * n) * 256 + cc * 32);
        mma16816(c[n], qa[0], qb[0], qa[1], qb[1], kf.x, kf.y);
        mma16816(c[n], qa[2], qb[2], qa[3], qb[3], kf.z, kf.w);
      }
    }
#pragma unroll
    for (int n = 0; n < 2; n++)
#pragma unroll
      for (int e = 0; e < 4; e++)
        if (key0 + 8 * n + 2 * t + (e & 1) > row0 + g + (e >> 1) * 8) c[n][e] = -INFINITY;
    float x0 = fmaxf(fmaxf(c[0][0], c[0][1]), fmaxf(c[1][0], c[1][1])), x1 = fmaxf(fmaxf(c[0][2], c[0][3]), fmaxf(c[1][2], c[1][3]));
    x0 = fmaxf(x0, __shfl_xor_sync(0xffffffffu, x0, 1)); x1 = fmaxf(x1, __shfl_xor_sync(0xffffffffu, x1, 1));
    x0 = fmaxf(x0, __shfl_xor_sync(0xffffffffu, x0, 2)); x1 = fmaxf(x1, __shfl_xor_sync(0xffffffffu, x1, 2));
    const float n0 = fmaxf(m0, x0), n1 = fmaxf(m1, x1);
    const float r0 = ex2(m0 - n0), r1 = ex2(m1 - n1);
    m0 = n0; m1 = n1;
#pragma unroll
    for (int n = 0; n < 2; n++) { c[n][0] = ex2(c[n][0] - n0); c[n][1] = ex2(c[n][1] - n0); c[n][2] = ex2(c[n][2] - n1); c[n][3] = ex2(c[n][3] - n1); }
    l0 = l0 * r0 + ((c[0][0] + c[0][1]) + (c[1][0] + c[1][1]));
    l1 = l1 * r1 + ((c[0][2] + c[0][3]) + (c[1][2] + c[1][3]));
    const uint32_t p0 = pack_bf16(c[0][0], c[0][1]), p1 = pack_bf16(c[0][2], c[0][3]), p2 = pack_bf16(c[1][0], c[1][1]), p3 = pack_bf16(c[1][2], c[1][3]);
#pragma unroll
    for (int j = 0; j < 16; j++) {
      const __nv_bfloat16* v = vp + (size_t)key0 * 256 + j * 8;
      const uint32_t b0 = ldg16(v) | (ldg16(v + 256) << 16), b1 = ldg16(v + 8 * 256) | (ldg16(v + 9 * 256) << 16);
      float o[4] = {O[4 * j] * r0, O[4 * j + 1] * r0, O[4 * j + 2] * r1, O[4 * j + 3] * r1};
      mma16816(o, p0, p1, p2, p3, b0, b1);
      O[4 * j] = o[0]; O[4 * j + 1] = o[1]; O[4 * j + 2] = o[2]; O[4 * j + 3] = o[3];
    }
  }
  a0 = rcp(quad_sum(l0)); a1 = rcp(quad_sum(l1));
}
__device__ __forceinline__ void att_output(const float (&O)[64], float a0, float a1, uint32_t (&pk)[32]) {
#pragma unroll
  for (int k = 0; k < 16; k++) { pk[2 * k] = v_pack(v_mul(O[4 * k + 0], a0), v_mul(O[4 * k + 1], a0)); pk[2 * k + 1] = v_pack(v_mul(O[4 * k + 2], a1), v_mul(O[4 * k + 3], a1)); }
}
template <int J1> __device__ __forceinline__ void exp_stage(float (&S)[64], float& l0, float& l1, const uint32_t (&P)[32], int w, const Cons& cs, uint32_t on) {
  const uint32_t lane = threadIdx.x & 31, wq = (threadIdx.x >> 5) & 3;
  const uint32_t a = cs.sb + w * 16384 + (wq * 16 + (lane & 15)) * 128 + (((lane >> 4) ^ (lane & 7)) << 4);
#define ES(c) \
  exp_inplace<c * J1 / 8, (c + 1) * J1 / 8>(S, l0, l1); \
  stmatrix_x4_after<OFF_STG + (c >> 2) * 8192>(a ^ ((c & 3) * 32), P[4 * c + 0], P[4 * c + 1], P[4 * c + 2], P[4 * c + 3], (c & 1) ? l1 : l0, on)
  ES(0); ES(1); ES(2); ES(3); ES(4); ES(5); ES(6); ES(7);
#undef ES
}
struct Att { uint32_t qd, kd, vd, c8, cb, xc, xp, pub; };
__device__ __forceinline__ void att_advance(Att& t) {
  constexpr uint32_t SLOT = 32768 >> 4;
  t.kd ^= SLOT; t.vd ^= SLOT; t.c8 ^= 8; t.cb ^= 8;
  const uint32_t x = t.xc; t.xc = t.xp ^ 1; t.xp = x;
}
template <bool SECOND>
__device__ __forceinline__ uint32_t diag_step(float (&S)[64], float (&O)[64], uint32_t (&P)[32], uint32_t (&pk)[32], float& l0, float& l1, uint32_t& unsafe, Att& t, int r, int w, Cons& cs) {
  constexpr int JD = SECOND ? JDIAG2 : JDIAG;
  const uint32_t sb = cs.sb;
  float a0 = 0.f, a1 = 0.f;
  uint32_t ready;
  auto sums = [&]() {
    unsafe = row_norm(l0, l1, a0, a1);
    mbar_arrive_if<BAR(B_QEMPTY)>(sb, (threadIdx.x & 31) == 0 && !unsafe);
    l0 = l1 = 0.f;
  };
  auto look_ahead = [&]() { ready = mbar_test<BAR(B_FULL)>(t.cb, t.xc); if (!SECOND) ready &= mbar_test<BAR(B_QFULL)>(sb, cs.fpar & 1); };
  if (w == 1) {
    bar_sync(2, 256);
    issue_qk<false>(S, t.qd, t.kd);
    if (YIELD2 && SECOND) bar_arrive(5, 256);
    if (!SECOND && t.pub) { stage_publish(w, cs); t.pub = 0; }
    if (SECOND && SUMPOS == 0) sums();
    mbar_wait<BAR(B_FULL + 2)>(t.cb ^ 8, t.xp);
    issue_pv<8, 1>(O, P, t.vd);
    bar_arrive(1, 256);
    att_advance(t);
    wg_wait<1>();
    fence_regs(S);
    T4Q(__float_as_uint(S[0]));
    mbar_arrive_cl<BAR(B_EMPTY)>(cs.rel, t.c8 ^ 8);
    if (SECOND && SUMPOS == 1) sums();
    exp_inplace<0, JD, 8>(S, l0, l1, r);
    pin_after(l0, l1);
    wg_wait<0>();
    fence_regs(O);
    fence_regs(P);
    mbar_arrive_cl<BAR(B_EMPTY + 2)>(cs.rel, t.c8);
    look_ahead();
    exp_pack<JD, 8, SECOND>(S, P, l0, l1, r, O, a0, a1, pk);
  } else {
    bar_sync(1, 256);
    issue_qk<true>(S, t.qd, t.kd);
    mbar_wait<BAR(B_FULL + 2)>(t.cb ^ 8, t.xp);
    issue_pv<SECOND ? 4 : 8, 1>(O, P, t.vd);
    bar_arrive(2, 256);
    if (!SECOND && t.pub) { stage_publish(w, cs); t.pub = 0; }
    att_advance(t);
    if (SECOND) {
      sums();
      if (YIELD2) bar_sync(5, 256);
    }
    wg_wait<1>();
    fence_regs<0, 32>(S);
    T4Q(__float_as_uint(S[0]));
    mbar_arrive_cl<BAR(B_EMPTY)>(cs.rel, t.c8 ^ 8);
    exp_inplace<0, 8, 0>(S, l0, l1, r);
    pin_after(l0, l1);
    wg_wait<0>();
    fence_regs(O);
    fence_regs(P);
    mbar_arrive_cl<BAR(B_EMPTY + 2)>(cs.rel, t.c8);
    look_ahead();
#pragma unroll
    for (int k = 0; k < 8; k++) { P[2 * k] = v_pack(S[4 * k + 0], S[4 * k + 1]); P[2 * k + 1] = v_pack(S[4 * k + 2], S[4 * k + 3]); }
    if (SECOND) att_output(O, a0, a1, pk);
  }
  return __reduce_or_sync(0xffffffffu, ready ^ 1);
}
__device__ __forceinline__ void attention(uint32_t code, uint32_t rank, int idx, int w, Cons& cs, uint32_t (&P)[32], uint32_t (&pk)[32]) {
  const int lane = threadIdx.x & 31, wq = (threadIdx.x >> 5) & 3;
  constexpr int JS = JSPLIT, JE = JEDGE;
  const uint32_t sb = cs.sb;
  const int y = (code & 15) * 2 + rank;
  const int r = wq * 16 + (lane >> 2) - 2 * (lane & 3);
  float O[64], S[64];
  float l0 = 0.f, l1 = 0.f;
  Att t = {dlo(OFF_A, 16) + w * 512, dlo(OFF_B, 16), dlo(OFF_B + 98304, 16384), 0, sb, cs.p0, cs.p1, 0};
  uint32_t unsafe = 0, late;
  int ns;
  auto stage_step = [&](bool signal, uint32_t on) {
    att_advance(t);
    t.pub = W0EARLY == 2 ? 1 : on;
    wg_wait<1>();
    fence_regs(S);
    T4Q(__float_as_uint(S[0]));
    mbar_arrive_cl<BAR(B_EMPTY)>(cs.rel, t.c8 ^ 8);
    exp_stage<JE>(S, l0, l1, pk, w, cs, on);
    pin_after(l0, l1);
    if (signal) bar_arrive(5, 256);
    wg_wait<0>();
    fence_regs(O);
    fence_regs(P);
    mbar_arrive_cl<BAR(B_EMPTY + 2)>(cs.rel, t.c8);
    const uint32_t ready = mbar_test<BAR(B_FULL)>(t.cb, t.xc);
    exp_pack<JE, 16, false>(S, P, l0, l1, r, O, 0.f, 0.f, pk);
    late = __reduce_or_sync(0xffffffffu, ready ^ 1);
  };
  bar_sync(3 - w, 128 + 128 * w);
  if (y >= 2) {
    issue_qk<false>(O, t.qd, dlo(OFF_B + 32768, 16));
    mbar_wait<BAR(B_FULL)>(sb, t.xc);
    issue_qk<false>(S, t.qd, dlo(OFF_B, 16));
    bar_arrive(1 + (w ^ 1), 256);
    T4X(0);
    wg_wait<1>();
    fence_regs(O);
    T4Q(0);
    mbar_arrive_cl<BAR(B_EMPTY + 1)>(cs.rel);
    if (W0EARLY == 2) exp_stage<JP>(O, l0, l1, pk, w, cs, w ^ 1); else exp_inplace<0, JP>(O, l0, l1);
    pin_after(l0, l1);
    const uint32_t rd = mbar_test<BAR(B_FULL + 3)>(sb, t.xp);
    exp_pack<JP, 16, false>(O, P, l0, l1, r, O, 0.f, 0.f, pk);
    if (UNLIKELY(__reduce_or_sync(0xffffffffu, rd ^ 1))) mbar_wait<BAR(B_FULL + 3)>(sb, t.xp);
    bar_sync(1 + w, 256);
    issue_pv<8, 0>(O, P, t.vd);
    bar_arrive(1 + (w ^ 1), 256);
    if (YIELD0 && w == 1) bar_sync(5, 256);
    stage_step(YIELD0 && w == 0, W0EARLY ? w : 1);
    ns = y - 2;
  } else {
    issue_qk<false>(S, t.qd, dlo(OFF_B + 32768, 16));
    bar_arrive(1 + (w ^ 1), 256);
    T4X(0);
    if (W0EARLY != 1 || w == 1) { tile_write<OFF_STG, 8192>(pk, sb + w * 16384); stage_publish(w, cs); }
    wg_wait<0>();
    fence_regs(S);
    T4Q(__float_as_uint(S[0]));
    mbar_arrive_cl<BAR(B_EMPTY + 1)>(cs.rel);
    causal_mask<0>(S, r + 64 * w + 128 * y);
    causal_mask<8>(S, r + 64 * w + 128 * y - 64);
    exp_pack<0, 16, false>(S, P, l0, l1, r, S, 0.f, 0.f, pk);
#pragma unroll
    for (int i = 0; i < 64; i++) O[i] = 0.f;
    late = 1;
    ns = 0;
  }
#pragma unroll 1
  for (uint32_t head = 0;; head++) {
    while (ns > 0) {
      if (UNLIKELY(late)) mbar_wait<BAR(B_FULL)>(t.cb, t.xc);
      bar_sync(1 + w, 256);
      issue_qk<false>(S, t.qd, t.kd);
      if (t.pub) { stage_publish(w, cs); t.pub = 0; }
      mbar_wait<BAR(B_FULL + 2)>(t.cb ^ 8, t.xp);
      issue_pv<8, 1>(O, P, t.vd);
      bar_arrive(1 + (w ^ 1), 256);
      ns--;
      att_advance(t);
      wg_wait<1>();
      fence_regs(S);
      T4Q(__float_as_uint(S[0]));
      mbar_arrive_cl<BAR(B_EMPTY)>(cs.rel, t.c8 ^ 8);
      exp_inplace<0, JS>(S, l0, l1);
      pin_after(l0, l1);
      wg_wait<0>();
      fence_regs(O);
      fence_regs(P);
      mbar_arrive_cl<BAR(B_EMPTY + 2)>(cs.rel, t.c8);
      const uint32_t rd = mbar_test<BAR(B_FULL)>(t.cb, t.xc);
      exp_pack<JS, 16, false>(S, P, l0, l1, 0, O, 0.f, 0.f, pk);
      late = __reduce_or_sync(0xffffffffu, rd ^ 1);
    }
    if (head == 0) {
      if (y != 0) {
        if (UNLIKELY(late)) mbar_wait<BAR(B_FULL)>(t.cb, t.xc);
        late = diag_step<false>(S, O, P, pk, l0, l1, unsafe, t, r, w, cs);
      }
      t.qd += 32768 >> 4;
      TRW(idx, 4);
      if (UNLIKELY(late)) { mbar_wait<BAR(B_QFULL)>(sb, cs.fpar & 1); mbar_wait<BAR(B_FULL)>(t.cb, t.xc); }
      late = diag_step<true>(S, O, P, pk, l0, l1, unsafe, t, r, w, cs);
    } else {
      bar_sync(1 + w, 256);
      mbar_wait<BAR(B_FULL + 2)>(t.cb ^ 8, t.xp);
      if (y != 1 || w) issue_pv<8, 1>(O, P, t.vd); else issue_pv<4, 1>(O, P, t.vd);
      if (w == 0) bar_arrive(2, 256);
      if (t.pub) stage_publish(w, cs);
      float a0, a1;
      unsafe = row_norm(l0, l1, a0, a1);
      mbar_arrive_if<BAR(B_QEMPTY + 1)>(sb, lane == 0 && !unsafe);
      wg_wait<0>();
      fence_regs(O);
      fence_regs(P);
      mbar_arrive_cl<BAR(B_EMPTY + 2)>(cs.rel, t.c8 ^ 8);
      att_output(O, a0, a1, pk);
    }
    if (UNLIKELY(unsafe)) {
      float a0, a1;
      slow_item(S, a0, a1, ((code >> 4) & 31) * 2 + head, y ^ head, sb + OFF_A + head * 32768, w);
      __syncwarp();
      mbar_arrive_if<BAR(B_QEMPTY)>(sb + head * 8, lane == 0);
      att_output(S, a0, a1, pk);
    }
    if (head) break;
    if (y != 1) {
      if (UNLIKELY(late)) mbar_wait<BAR(B_FULL)>(t.cb, t.xc);
      bar_sync(1 + w, 256);
      issue_qk<false>(S, t.qd, t.kd);
      mbar_wait<BAR(B_STGE)>(sb + w * 8, (cs.round & 1) ^ 1);
      mbar_wait<BAR(B_FULL + 2)>(t.cb ^ 8, t.xp);
      if (w == 0) issue_pv<4, 0>(O, P, t.vd); else issue_pv<8, 0>(O, P, t.vd);
      bar_arrive(1 + (w ^ 1), 256);
      stage_step(false, 1);
      ns = (y ^ 1) - 1;
    } else {
      stage_write(pk, w, cs);
      t.pub = 1;
#pragma unroll
      for (int i = 0; i < 64; i++) O[i] = 0.f;
    }
  }
  cs.p1 = t.xp ^ 1; cs.p0 = t.xc;
  cs.fpar ^= 1;
}

struct Src { const CUtensorMap *ma, *mb; int a0, a1, b0, b1, b2; uint32_t hb; };
__device__ __forceinline__ Src gemm_src(const Params& p, uint32_t code, uint32_t rank, uint32_t h) {
  const int kind = code >> 9, x = (code >> 4) & 31, m = code & 15;
  Src s;
  s.ma = &p.maps[M_AX + kind];
  s.mb = &p.maps[(kind == K_KV && h) ? M_WUV : M_WQKV + kind];
  if (kind == K_QL) { s.a0 = rank * 1024; s.a1 = m * 128; s.b0 = x * 64; s.b1 = h * 32; s.b2 = 0; s.hb = 12288; }
  else { s.a0 = 0; s.a1 = (2 * m + rank) * 128; s.b0 = 0; s.b1 = 0; s.b2 = kind == K_KV ? x * 2 : x * 4 + h * 2; s.hb = 16384; }
  return s;
}
__global__ void __cluster_dims__(2, 1, 1) __launch_bounds__(384, 1) mega_kernel(const __grid_constant__ Params p) {
  extern __shared__ __align__(1024) uint8_t smem_raw[];
  const uint32_t sb = smem_u32(smem_raw), sb0 = sb;
  const uint32_t bid = blockIdx.x, rank = bid & 1;
  const int warp = __shfl_sync(0xffffffffu, threadIdx.x >> 5, 0);
  auto early_load = [&](uint32_t code0, int s0, int s1) {
    const Src u = gemm_src(p, code0, rank, 0), v = gemm_src(p, code0, rank, 1);
#pragma unroll
    for (int s = s0; s < s1; s++) {
      const uint32_t bar = sb + BAR(B_FULL) + s * 8;
      if (elect_one()) {
        mbar_expect_tx<0>(bar, 16384 + 2 * u.hb);
        tma_load_2d(sb + OFF_A + s * 16384, u.ma, u.a0 + s * 64, u.a1, bar);
        tma_load_3d(sb + OFF_B + s * 32768, u.mb, u.b0, u.b1 + s * 64, u.b2, bar);
        tma_load_3d(sb + OFF_B + s * 32768 + u.hb, v.mb, v.b0, v.b1 + s * 64, v.b2, bar);
      }
    }
  };
#define BI(b) mbar_init<BAR(b)>(sb, bar_count(b))
  static_assert(B_COUNT == 25, "barrier set-up");
  if (warp == 0) {
    const uint32_t c0 = p.sched[bid >> 1][threadIdx.x & 1];
    if (elect_one()) {
      BI(0); BI(1); BI(2); BI(3);
      asm volatile("fence.mbarrier_init.release.cluster;" ::: "memory");
    }
    __syncwarp();
    early_load(__shfl_sync(0xffffffffu, c0, 0) & 4095, 0, EARLYN);
  }
  if (threadIdx.x == 32 || threadIdx.x == 64 || threadIdx.x == 96) {
    if (threadIdx.x == 32) { BI(4); BI(5); BI(6); BI(7); BI(8); BI(9); BI(21); }
    else if (threadIdx.x == 64) { BI(10); BI(11); BI(12); BI(13); BI(14); BI(15); BI(22); }
    else {
      BI(16); BI(17); BI(18); BI(19); BI(20); BI(23); BI(24);
      asm volatile("st.shared.v2.u32 [%0+%2], {%1, %1};" ::"r"(sb), "r"(0), "n"(OFF_FILLS) : "memory");
      if ((sb & 0xffffffu) != SB) __trap();
    }
    asm volatile("fence.mbarrier_init.release.cluster;" ::: "memory");
  }
#undef BI
  if (warp == 4) {
    const int i = threadIdx.x - 128;
    if (i < MAX_ITEMS / 4) {
      const uint4 v = *reinterpret_cast<const uint4*>(&p.sched[bid >> 1][4 * i]);
      asm volatile("st.shared.v4.u32 [%0+%5], {%1, %2, %3, %4};" ::"r"(sb + i * 16), "r"(v.x), "r"(v.y), "r"(v.z), "r"(v.w), "n"(OFF_LIST) : "memory");
    }
    asm volatile("st.shared.v2.u32 [%0+%2], {%1, %1};" ::"r"(sb + i * 8), "r"(0), "n"(OFF_MASK) : "memory");
  }
  bar_sync(0, 384);
  cluster_arrive_relaxed();
  const int wg = warp >> 2;
  if (wg == 0) {
    reg_dealloc<REG_PROD>();
    if (EARLYN < 4 && warp == 0) early_load(item(sb, 0), EARLYN, 4);
    cluster_wait();
    const int lane = threadIdx.x & 31;
    auto need = [&](uint32_t& have, int i, int b) {
      if (!((have >> b) & 1)) {
        uint32_t n = 0;
        while (have = __reduce_or_sync(0xffffffffu, lds_acquire<OFF_MASK>(sb + i * 4)), !((have >> b) & 1)) { __nanosleep(32); if (++n > (1u << 22)) __trap(); }
        fence_async_glob();
      }
    };
    if (warp == 0) {
      uint32_t e0 = 0, e1 = 0;
      uint32_t qe = 0, after_att = 0, fills = 0;
      const uint64_t pol_first = policy_evict_first(), pol_normal = POL_NORMAL;
      for (int idx = 0;; idx++) {
        const uint32_t full = item_full(sb, idx), code = full & 4095;
        const int kind = code >> 9, x = (code >> 4) & 31, m = code & 15, y = 2 * m + rank;
        if (kind == K_END) break;
        const uint32_t last = full & (((LASTUSE & (kind >= K_OA ? 4 : 1)) ? 0x3000u : 0u) | ((LASTUSE & 2) ? 0xffff0000u : 0u));
        {
          const Src u = gemm_src(p, code, rank, rank);
          const uint64_t pa = (last & 0x1000) ? pol_first : pol_normal, pb = (last & 0x2000) ? pol_first : pol_normal;
          const int nk = kind == K_KV ? 8 : kind == K_OB ? 64 : 16;
          uint32_t have = kind >= K_OA ? 0u : 0xffffffffu;
#pragma unroll 1
          for (int k = idx == 0 ? 4 : 0; k < nk; k++) {
            const uint32_t s = k & 3;
            int kk = k;
            if (k >= 64 - 4 * HLATE) { const int j = (k >> 1) - (32 - 2 * HLATE); kk = (32 - 2 * HLATE + (j < HLATE ? 2 * j : 2 * (j - HLATE) + 1)) * 2 + (k & 1); }
            need(have, (kind == K_OA ? F_QL : F_CTX) + y, kind == K_OA ? k : kk >> 1);
            if (after_att && !(k & 1)) {
              mbar_wait<BAR(B_QEMPTY)>(sb + k * 4, qe);
              if (k == 2) { after_att = 0; qe ^= 1; }
            }
            fill_gemm(sb + s * 8, (s & 1) ? e1 : e0, 16384 + 2 * u.hb, sb + OFF_B + s * 32768 + rank * u.hb, u.mb, u.b0, u.b1 + kk * 64, u.b2, sb + OFF_A + s * 16384, u.ma, u.a0 + kk * 64, u.a1, pb, pa);
            asm volatile("st.volatile.shared.u32 [%0+%2], %1;" ::"r"(sb), "r"(++fills), "n"(OFF_FILLS) : "memory");
            if (s == 3) { e0 ^= 1; e1 ^= 1; }
          }
        }
        if (kind == K_QF) {
          uint32_t have = 0, xc = e1, xp = e0 ^ 1;
#pragma unroll 1
          for (int j = 0; j < 8 * m + 8; j++) {
            const int i = j >> 1, v = j & 1;
            if (v ? i == 0 : i == 4 * m + 3) continue;
            const int ib = i - v;
            if (i == 2 * m + 1 + rank && !v) have = 0;
            const int h = 2 * x + (ib >= 2 * m + 1 + (int)rank), blk = ib <= 2 * m + 1 ? ib : 4 * m + 2 - ib;
            const int row = KVSLOT(h) * SEQ + blk * 128;
            if (!v) need(have, F_KV + h, blk);
            const uint32_t b = 2 * v + ((ib + 1) & 1);
            const uint32_t dst = sb + OFF_B + b * 32768;
            const bool own = ib == 2 * m + 1;
            const uint64_t pol = ((last >> (16 + (h & 1) * 8 + (blk >> 1))) & 1) ? pol_first : pol_normal;
            fill_kv(sb + b * 8, v ? xp : xc, dst + rank * 16384, &p.maps[M_KV_LD], (2 * v + rank) * 64, row, own ? 1 + rank : 3, pol);
            if (own) tma_load_2d_h(dst + (rank ^ 1) * 16384, &p.maps[M_KV_LD], (2 * v + (rank ^ 1)) * 64, row, sb + BAR(B_FULL) + b * 8, pol);
            if (v || i == 0) { const uint32_t t = xc; xc = xp ^ 1; xp = t; }
          }
          e0 ^= 1;
          after_att = 1;
        }
      }
    } else if (warp == 2) {
      const uint32_t epoch = g_flags.epoch[bid];
      const uint64_t full = (lane >> 3) == 2 ? ~0ull : 0x0000ffff0000ffffull, flip = 0ull - (epoch & 1);
      uint64_t seen = 0;
      uint32_t tries = 0, hp = 1, hcode;
      int hidx = -1;
      auto next_halo = [&]() { do hcode = item(sb, ++hidx); while ((hcode >> 9) != K_END && ((hcode >> 9) != K_QL || (hcode & 15) == 0)); };
      next_halo();
      while (true) {
        const bool all = __all_sync(0xffffffffu, seen == full);
        if (all && (hcode >> 9) == K_END) break;
        if (!all) {
          uint64_t v;
          asm volatile("ld.acquire.gpu.global.u64 %0, [%1];" : "=l"(v) : "l"(&g_flags.m[2 * lane]) : "memory");
          v = (v ^ flip) & full;
          if (v != seen) { seen = v; asm volatile("st.release.cta.shared::cta.u64 [%0+%2], %1;" ::"r"(sb + lane * 8), "l"(v), "n"(OFF_MASK) : "memory"); }
        }
        if ((hcode >> 9) != K_END) {
          const int x = (hcode >> 4) & 31, m = hcode & 15;
          bool there = __any_sync(0xffffffffu, lane == F_QL / 2 + m - 1 && ((seen >> (32 * rank + x)) & 1));
          if (there && __all_sync(0xffffffffu, mbar_test<BAR(B_HEMPTY)>(sb, hp))) {
            __syncwarp();
            fence_async_glob();
            if (elect_one()) mbar_expect_tx<BAR(B_HFULL)>(sb, 2048);
            bulk_load(sb + OFF_HALO, g_halo + ((2 * m + rank - 2) * 16 + x) * 2048, 2048, sb + BAR(B_HFULL));
            hp ^= 1;
            next_halo();
          }
        }
        __nanosleep(WATCH_NS);
        if (++tries > (1u << 20)) __trap();
      }
      if (lane == 0) g_flags.epoch[bid] = epoch + 1;
    } else if (warp == 3) {
      uint32_t n = 0;
      for (int idx = 0; RELW; idx++) {
        const uint32_t code = item(sb, idx);
        const int kind = code >> 9, x = (code >> 4) & 31, y = 2 * (code & 15) + rank;
        if (kind == K_END) break;
        if (kind > K_KV) continue;
#pragma unroll 1
        for (int r = 0; r <= (kind == K_QF); r++, n++) {
          mbar_wait_long<BAR(B_RELF)>(sb + (n & 1) * 8, (n >> 1) & 1);
          mbar_arrive_if<BAR(B_RELE)>(sb + (n & 1) * 8, lane == 0);
          flag_toggle(&g_flags.m[kind == K_QL ? F_QL + y : kind == K_KV ? F_KV + x : F_CTX + (y ^ r)], 1u << (kind == K_QL ? x : kind == K_KV ? y : 2 * x + r));
          TRC(idx, 12 + (kind == K_KV ? 1 : r));
        }
      }
    } else {
      {
        uint32_t round = 0, fpar = 0, nrel = 0;
        const uint32_t rb = mapa(sb, rank ^ 1);
        const uint64_t pol_first = policy_evict_first(), pol_normal = POL_NORMAL;
        auto pace = [&]() {
          uint32_t c0, c, t0, t;
          asm volatile("ld.volatile.shared.u32 %0, [%1+%2];" : "=r"(c0) : "r"(sb), "n"(OFF_FILLS) : "memory");
          asm volatile("mov.u32 %0, %clock;" : "=r"(t0));
          do {
            asm volatile("ld.volatile.shared.u32 %0, [%1+%2];" : "=r"(c) : "r"(sb), "n"(OFF_FILLS) : "memory");
            asm volatile("mov.u32 %0, %clock;" : "=r"(t));
          } while (__all_sync(0xffffffffu, c == c0 && t - t0 < PACE_MAX));
        };
        for (int idx = 0;; idx++) {
          const uint32_t code = item(sb, idx);
          const int kind = code >> 9, x = (code >> 4) & 31, m = code & 15, y = 2 * m + rank;
          if (kind == K_END) break;
          const bool last = (item(sb, idx + 1) >> 9) == K_END;
          if (kind == K_QF) {
            if (elect_one()) mbar_expect_tx<BAR(B_QFULL)>(sb, 32768);
            mbar_wait_long<BAR(B_QX)>(sb, fpar);
#pragma unroll 1
            for (int v = 0; v < 2; v++) {
              mbar_wait<BAR(B_STGF)>(sb + v * 8, round & 1);
              bulk_send(rb + OFF_A + 32768 + v * 8192, sb + OFF_STG + v * 16384, 8192, rb + BAR(B_QFULL));
              bulk_send(rb + OFF_A + 49152 + v * 8192, sb + OFF_STG + v * 16384 + 8192, 8192, rb + BAR(B_QFULL));
            }
            mbar_wait<BAR(B_QFULL)>(sb, fpar);
            mbar_arrive_cl<BAR(B_STGE)>(lane < 2 ? rb : 0, lane * 8);
            round++; fpar ^= 1;
          }
          const CUtensorMap* mc = &p.maps[M_OA_ST + kind];
          const uint64_t pol = (((HINTS & 1) && kind >= K_OA) || ((HINTS & 2) && kind == K_QF) || ((HINTS & 4) && kind == K_QL) || ((HINTS & 8) && kind == K_KV)) ? pol_first : pol_normal;
          int row = kind == K_KV ? KVSLOT(x) * SEQ + y * 128 : kind == K_OA ? m * 128 : y * 128;
          int cg = kind == K_QL ? x : kind == K_QF ? x * 4 : kind == K_KV ? 0 : kind == K_OA ? rank * 32 + x * 4 : 16 + x * 4;
          const int nr = kind == K_QL ? 1 : 2;
#pragma unroll 1
          for (int r = 0; r < nr; r++) {
            mbar_wait_long<BAR(B_STGF)>(sb, round & 1);
            if (last && kind >= K_KV) {
              TRC(idx + 1, 6);
              tma_store_3d(mc, sb + OFF_STG, 0, row, cg, pol);
              mbar_wait<BAR(B_FIN)>(sb, 0);
              TRC(idx + 1, 7);
              tma_store_3d(mc, sb + OFF_B, 0, row, cg + 2, pol);
              mbar_wait<BAR(B_STGF + 1)>(sb, round & 1);
              TRC(idx + 1, 8);
              tma_store_3d(mc, sb + OFF_STG + 16384, 0, row + 64, cg, pol);
              mbar_wait<BAR(B_FIN + 1)>(sb, 0);
              TRC(idx + 1, 9);
              tma_store_3d(mc, sb + OFF_B + 16384, 0, row + 64, cg + 2, pol);
              bulk_commit();
              r = 1;
            } else {
              const bool paced = !last && (kind >= K_KV || r == 1);
              if (paced) pace();
              tma_store_3d(mc, sb + OFF_STG, 0, row, cg, pol);
              bulk_commit();
              mbar_wait<BAR(B_STGF + 1)>(sb, round & 1);
              if (paced) pace();
              tma_store_3d(mc, sb + OFF_STG + 16384, 0, row + 64, cg, pol);
              if (kind == K_QL) bulk_store(g_halo + (y * 16 + x) * 2048, sb + OFF_STG + 16384 + 8192 + 3 * 2048, 2048);
              bulk_commit();
              bulk_wait_read<1>();
              mbar_arrive_if<BAR(B_STGE)>(sb, lane == 0);
              bulk_wait_read<0>();
              mbar_arrive_if<BAR(B_STGE + 1)>(sb, lane == 0);
              round++;
            }
            if (kind == K_QF || (kind <= K_KV && r == nr - 1)) {
              bulk_wait_all();
              if (RELW) {
                mbar_wait<BAR(B_RELE)>(sb + (nrel & 1) * 8, ((nrel >> 1) & 1) ^ 1);
                __syncwarp();
                mbar_arrive_if<BAR(B_RELF)>(sb + (nrel & 1) * 8, lane == 0);
                nrel++;
              } else {
                flag_toggle(&g_flags.m[kind == K_QL ? F_QL + y : kind == K_KV ? F_KV + x : F_CTX + (y ^ r)], 1u << (kind == K_QL ? x : kind == K_KV ? y : 2 * x + r));
                TRC(idx, 12 + r);
              }
            }
            cg += 2;
            if (kind == K_QF) row ^= 128;
          }
        }
        bulk_wait_all();
      }
      cluster_arrive_relaxed();
      cluster_wait();
    }
  } else {
    reg_alloc<REG_CONS>();
    cluster_wait();
    const int w = wg - 1;
    Cons cs;
    cs.sb = SBU ? __reduce_or_sync(0xffffffffu, sb0) : sb0;
    const uint32_t sb = cs.sb;
    cs.rel = (threadIdx.x & 127) == 0 ? sb : (threadIdx.x & 127) == 1 ? mapa(sb, rank ^ 1) : 0;
    cs.p0 = cs.p1 = cs.lead = cs.round = cs.fpar = 0;
    uint32_t pkA[32], pkB[32], pend = 0;
#pragma unroll
    for (int i = 0; i < 32; i++) pkA[i] = pkB[i] = 0;
    uint32_t code = item(sb, 0);
    int idx = 0;
    do {
      TRW(idx, 0);
      const int kind = code >> 9;
      uint32_t ncode;
      if (kind == K_QL) {
        float acc[96];
        ncode = gemm_tile(acc, 4, idx, w, cs, pend, pkA, pkB);
        TRW(idx, 2);
        local_epilogue(acc, code, w, cs);
        pend = 24;
        if (LHS && w == 1 && (ncode >> 9) != K_END) bar_arrive(5, 256);
        if (!LPUB || (ncode >> 9) >= K_OA) { stage_publish(w, cs); pend = 16; }
      } else {
        float acc[128];
        ncode = gemm_tile(acc, kind == K_KV ? 2 : kind == K_OB ? 16 : 4, idx, w, cs, pend, pkA, pkB);
        TRW(idx, 2);
        if (kind == K_QF) {
          mbar_arrive_cl<BAR(B_QX)>((threadIdx.x & 1) ? cs.rel : 0);
          tile_pack_write<OFF_A, 16384, 0>(acc, pkB, sb + w * 8192);
#pragma unroll
          for (int i = 0; i < 32; i++) pkA[i] = v_pack(acc[64 + 2 * i], acc[64 + 2 * i + 1]);
          T4X(pkA[31]);
          mbar_wait<BAR(B_STGE)>(sb + w * 8, (cs.round & 1) ^ 1);
          if (W0EARLY == 1 && w == 0) { tile_write<OFF_STG, 8192>(pkA, sb); stage_publish(w, cs); }
          mbar_wait<BAR(B_FULL + 1)>(sb, cs.p1);
          T4X(0);
          fence_async_smem();
          attention(code, rank, idx, w, cs, pkB, pkA);
          pend = 1;
        } else {
          if (kind == K_KV) {
#pragma unroll
            for (int i = 0; i < 64; i++) acc[i] *= SCALE_LOG2;
          }
#pragma unroll
          for (int i = 0; i < 32; i++) pkA[i] = pack_bf16(acc[2 * i], acc[2 * i + 1]);
#pragma unroll
          for (int i = 0; i < 32; i++) pkB[i] = pack_bf16(acc[64 + 2 * i], acc[64 + 2 * i + 1]);
          pend = 3;
        }
      }
      code = ncode;
      idx++;
    } while ((code >> 9) != K_END);
    TRW(idx, 0);
    if (pend & 1) { stage_write(pkA, w, cs); stage_publish(w, cs); }
    if (pend & 2) {
      mbar_wait<BAR(B_EMPTY)>(sb, cs.p0 ^ 1);
      tile_write<OFF_B, 8192>(pkB, sb + w * 16384);
      fence_async_smem();
      __syncwarp();
      mbar_arrive_if<BAR(B_FIN)>(sb + w * 8, (threadIdx.x & 31) == 0);
    }
    cluster_arrive();
  }
}

typedef CUresult (*EncodeFn)(CUtensorMap*, CUtensorMapDataType, cuuint32_t, void*, const cuuint64_t*, const cuuint64_t*, const cuuint32_t*,
                             const cuuint32_t*, CUtensorMapInterleave, CUtensorMapSwizzle, CUtensorMapL2promotion, CUtensorMapFloatOOBfill);

void make_map_2d(EncodeFn enc, CUtensorMap* tm, const void* ptr, uint64_t cols, uint64_t rows) {
  cuuint64_t dims[2] = {cols, rows};
  cuuint64_t str[1] = {cols * 2};
  cuuint32_t box[2] = {64, 128};
  cuuint32_t es[2] = {1, 1};
  enc(tm, CU_TENSOR_MAP_DATA_TYPE_BFLOAT16, 2, const_cast<void*>(ptr), dims, str, box, es, CU_TENSOR_MAP_INTERLEAVE_NONE, CU_TENSOR_MAP_SWIZZLE_128B,
      CU_TENSOR_MAP_L2_PROMOTION_L2_256B, CU_TENSOR_MAP_FLOAT_OOB_FILL_NONE);
}
void make_map_3d(EncodeFn enc, CUtensorMap* tm, const void* ptr, uint64_t cols, uint64_t rows, uint64_t part, uint32_t br, uint32_t bg) {
  cuuint64_t dims[3] = {part, rows, cols / part};
  cuuint64_t str[2] = {cols * 2, part * 2};
  cuuint32_t box[3] = {64, br, bg};
  cuuint32_t es[3] = {1, 1, 1};
  enc(tm, CU_TENSOR_MAP_DATA_TYPE_BFLOAT16, 3, const_cast<void*>(ptr), dims, str, box, es, CU_TENSOR_MAP_INTERLEAVE_NONE, CU_TENSOR_MAP_SWIZZLE_128B,
      CU_TENSOR_MAP_L2_PROMOTION_L2_256B, CU_TENSOR_MAP_FLOAT_OOB_FILL_NONE);
}

static const uint32_t h_sched[NPAIR][MAX_ITEMS] = {
  {0x400,0xff800207,0x554,0x564,0x566,0x1e02c4,0x20a7,0x625,0xe00,0xe00,0xe00,0xe00,0xe00,0xe00,0xe00,0xe00,0xe00,0xe00,0xe00,0xe00},
  {0x420,0x454,0x2,0x83,0x25,0xb6,0x4f0,0x2a5,0x25d0,0x202f1,0x636,0xe00,0xe00,0xe00,0xe00,0xe00,0xe00,0xe00,0xe00,0xe00},
  {0x440,0x200,0xe3,0x55,0x520,0x4d4,0x524,0xfff002a7,0x2037,0x30f7,0xe00,0xe00,0xe00,0xe00,0xe00,0xe00,0xe00,0xe00,0xe00,0xe00},
  {0x460,0x206,0x32281,0x2c2,0x202e1,0x603,0xe00,0xe00,0xe00,0xe00,0xe00,0xe00,0xe00,0xe00,0xe00,0xe00,0xe00,0xe00,0xe00,0xe00},
  {0x410,0x1,0x92,0x24,0xd5,0x40252,0x202a1,0x830,0xe00,0xe00,0xe00,0xe00,0xe00,0xe00,0xe00,0xe00,0xe00,0xe00,0xe00,0xe00},
  {0x430,0x474,0x12,0x93,0x4c1,0x4e1,0x4e3,0x4d5,0x513,0x536,0x583,0x2a0,0x5f3,0x815,0xe00,0xe00,0xe00,0xe00,0xe00,0xe00},
  {0x450,0x205,0x510,0x512,0x534,0x584,0x2547,0x574,0x2d3,0x20d7,0x616,0xe00,0xe00,0xe00,0xe00,0xe00,0xe00,0xe00,0xe00,0xe00},
  {0x470,0x406,0x485,0x4a1,0x486,0x497,0x4a5,0xa6,0x180284,0x1002f4,0x634,0xe00,0xe00,0xe00,0xe00,0xe00,0xe00,0xe00,0xe00,0xe00},
  {0x401,0x11,0x244,0x2a4,0x812,0xe00,0xe00,0xe00,0xe00,0xe00,0xe00,0xe00,0xe00,0xe00,0xe00,0xe00,0xe00,0xe00,0xe00,0xe00},
  {0x0,0xb1,0x33,0xd4,0x36,0x24c7,0x505,0x526,0x563,0x546,0x5e3,0x596,0x5f6,0x816,0xe00,0xe00,0xe00,0xe00,0xe00,0xe00},
  {0x421,0x201,0x94,0x276,0x5d2,0x837,0xe00,0xe00,0xe00,0xe00,0xe00,0xe00,0xe00,0xe00,0xe00,0xe00,0xe00,0xe00,0xe00,0xe00},
  {0x441,0x21,0xa2,0x34,0xe5,0x285,0x1002e4,0x613,0xe00,0xe00,0xe00,0xe00,0xe00,0xe00,0xe00,0xe00,0xe00,0xe00,0xe00,0xe00},
  {0x10,0x224,0x4d7,0x515,0x544,0x5c0,0x585,0x577,0x2002e5,0x633,0xe00,0xe00,0xe00,0xe00,0xe00,0xe00,0xe00,0xe00,0xe00,0xe00},
  {0x461,0x203,0x76,0x523,0x506,0x802a3,0x822,0xe00,0xe00,0xe00,0xe00,0xe00,0xe00,0xe00,0xe00,0xe00,0xe00,0xe00,0xe00,0xe00},
  {0x480,0x210,0xf3,0x4c2,0xffc00277,0x802e3,0x622,0xe00,0xe00,0xe00,0xe00,0xe00,0xe00,0xe00,0xe00,0xe00,0xe00,0xe00,0xe00,0xe00},
  {0x20,0x233,0x4b3,0x260,0x290,0x5c6,0x5b6,0x800,0xe00,0xe00,0xe00,0xe00,0xe00,0xe00,0xe00,0xe00,0xe00,0xe00,0xe00,0xe00},
  {0x411,0x31,0xb2,0x256,0x586,0x590,0x2594,0x803,0xe00,0xe00,0xe00,0xe00,0xe00,0xe00,0xe00,0xe00,0xe00,0xe00,0xe00,0xe00},
  {0x431,0x426,0xff800247,0x4002c6,0x2077,0x614,0xe00,0xe00,0xe00,0xe00,0xe00,0xe00,0xe00,0xe00,0xe00,0xe00,0xe00,0xe00,0xe00,0xe00},
  {0x451,0x41,0xc2,0xff800257,0x592,0x1802d4,0x600,0xe00,0xe00,0xe00,0xe00,0xe00,0xe00,0xe00,0xe00,0xe00,0xe00,0xe00,0xe00,0xe00},
  {0x471,0x446,0x466,0x2456,0x2467,0x4a3,0x4c3,0x4b4,0x296,0x15f1,0x35f0,0x2017,0x2067,0x632,0xe00,0xe00,0xe00,0xe00,0xe00,0xe00},
  {0x490,0x484,0x22,0xa3,0x35,0xc6,0x40272,0x4002e6,0x623,0xe00,0xe00,0xe00,0xe00,0xe00,0xe00,0xe00,0xe00,0xe00,0xe00,0xe00},
  {0x402,0x465,0x32,0x476,0x495,0x75,0x521,0x4d3,0x525,0x2517,0x5e0,0x5a2,0x5c4,0x2002f5,0x604,0xe00,0xe00,0xe00,0xe00,0xe00},
  {0x30,0x400226,0x80293,0x834,0xe00,0xe00,0xe00,0xe00,0xe00,0xe00,0xe00,0xe00,0xe00,0xe00,0xe00,0xe00,0xe00,0xe00,0xe00,0xe00},
  {0x422,0x211,0xa4,0x500,0x502,0xffe00297,0x322d1,0x631,0xe00,0xe00,0xe00,0xe00,0xe00,0xe00,0xe00,0xe00,0xe00,0xe00,0xe00,0xe00},
  {0x40,0x2447,0x82,0x44,0xf5,0xe6,0x4f5,0x535,0x553,0x808002d7,0x611,0xe00,0xe00,0xe00,0xe00,0xe00,0xe00,0xe00,0xe00,0xe00},
  {0x442,0x416,0x42,0xb3,0x200255,0x5a3,0x5a5,0x5b7,0x813,0xe00,0xe00,0xe00,0xe00,0xe00,0xe00,0xe00,0xe00,0xe00,0xe00,0xe00},
  {0x462,0x220,0x4,0x65,0x4c5,0x522,0x541,0x514,0x545,0x573,0x5c3,0x5e5,0x5d6,0x806,0xe00,0xe00,0xe00,0xe00,0xe00,0xe00},
  {0x481,0x436,0x52,0xc3,0x45,0xd6,0x32261,0x5c2,0x4002f6,0x624,0xe00,0xe00,0xe00,0xe00,0xe00,0xe00,0xe00,0xe00,0xe00,0xe00},
  {0x412,0x204,0xffe00287,0x402f2,0x637,0xe00,0xe00,0xe00,0xe00,0xe00,0xe00,0xe00,0xe00,0xe00,0xe00,0xe00,0xe00,0xe00,0xe00,0xe00},
  {0x50,0xc1,0x43,0xe4,0x46,0x4e5,0x24e7,0x543,0x533,0x5c1,0x2567,0x593,0x5b5,0x833,0xe00,0xe00,0xe00,0xe00,0xe00,0xe00},
  {0x432,0x4a0,0x62,0xd3,0x4a4,0x200265,0x576,0x5d7,0x804,0xe00,0xe00,0xe00,0xe00,0xe00,0xe00,0xe00,0xe00,0xe00,0xe00,0xe00},
  {0x452,0x455,0x241,0xc5,0x286,0x831,0xe00,0xe00,0xe00,0xe00,0xe00,0xe00,0xe00,0xe00,0xe00,0xe00,0xe00,0xe00,0xe00,0xe00},
  {0x472,0x51,0x245,0x562,0x550,0x808002e7,0x607,0xe00,0xe00,0xe00,0xe00,0xe00,0xe00,0xe00,0xe00,0xe00,0xe00,0xe00,0xe00,0xe00},
  {0x403,0x61,0xd2,0x4a2,0x2496,0x4a6,0x501,0x250,0x537,0x565,0x2587,0x5e6,0x5b1,0x827,0xe00,0xe00,0xe00,0xe00,0xe00,0xe00},
  {0x423,0x71,0x243,0x4e6,0x100294,0x821,0xe00,0xe00,0xe00,0xe00,0xe00,0xe00,0xe00,0xe00,0xe00,0xe00,0xe00,0xe00,0xe00,0xe00},
  {0x443,0x202,0x85,0x200275,0x5d4,0x820,0xe00,0xe00,0xe00,0xe00,0xe00,0xe00,0xe00,0xe00,0xe00,0xe00,0xe00,0xe00,0xe00,0xe00},
  {0x482,0x212,0x95,0x80263,0x5a4,0x2575,0x5d5,0x836,0xe00,0xe00,0xe00,0xe00,0xe00,0xe00,0xe00,0xe00,0xe00,0xe00,0xe00,0xe00},
  {0x413,0x213,0x86,0x540,0x511,0x530,0x402a2,0x832,0xe00,0xe00,0xe00,0xe00,0xe00,0xe00,0xe00,0xe00,0xe00,0xe00,0xe00,0xe00},
  {0x433,0x216,0x516,0x532,0x572,0x2002c5,0x20b7,0x635,0xe00,0xe00,0xe00,0xe00,0xe00,0xe00,0xe00,0xe00,0xe00,0xe00,0xe00,0xe00},
  {0x60,0xd1,0x53,0xf4,0x24a7,0x4d0,0x504,0x280,0x808002f7,0x626,0xe00,0xe00,0xe00,0xe00,0xe00,0xe00,0xe00,0xe00,0xe00,0xe00},
  {0x453,0x222,0xa5,0x4c6,0x273,0x595,0x5b0,0x802,0xe00,0xe00,0xe00,0xe00,0xe00,0xe00,0xe00,0xe00,0xe00,0xe00,0xe00,0xe00},
  {0x70,0x240,0x2477,0xff800267,0x5f2,0x835,0xe00,0xe00,0xe00,0xe00,0xe00,0xe00,0xe00,0xe00,0xe00,0xe00,0xe00,0xe00,0xe00,0xe00},
  {0x491,0x475,0x72,0x494,0x2487,0x100254,0x5e2,0x5e4,0x25e7,0x5d1,0x812f3,0x627,0xe00,0xe00,0xe00,0xe00,0xe00,0xe00,0xe00,0xe00},
  {0x80,0xe1,0x63,0x5,0x56,0x503,0x4f3,0x561,0x531,0x5e1,0x591,0x5a6,0x5b2,0x826,0xe00,0xe00,0xe00,0xe00,0xe00,0xe00},
  {0x492,0x214,0x4d6,0x4f6,0x24f4,0x808002c7,0x20c7,0x606,0xe00,0xe00,0xe00,0xe00,0xe00,0xe00,0xe00,0xe00,0xe00,0xe00,0xe00,0xe00},
  {0x90,0x236,0x292,0x5b3,0x824,0xe00,0xe00,0xe00,0xe00,0xe00,0xe00,0xe00,0xe00,0xe00,0xe00,0xe00,0xe00,0xe00,0xe00,0xe00},
  {0x404,0x223,0x96,0x100274,0x5f4,0x807,0xe00,0xe00,0xe00,0xe00,0xe00,0xe00,0xe00,0xe00,0xe00,0xe00,0xe00,0xe00,0xe00,0xe00},
  {0x424,0x221,0xb4,0x4b6,0x4b0,0x283,0x5c7,0x5d3,0x825,0xe00,0xe00,0xe00,0xe00,0xe00,0xe00,0xe00,0xe00,0xe00,0xe00,0xe00},
  {0x444,0x231,0xc4,0x80253,0x556,0x4002d6,0x1630,0xe00,0xe00,0xe00,0xe00,0xe00,0xe00,0xe00,0xe00,0xe00,0xe00,0xe00,0xe00,0xe00},
  {0xa0,0x225,0x542,0x2507,0x555,0x571,0x2c3,0x132f0,0x621,0xe00,0xe00,0xe00,0xe00,0xe00,0xe00,0xe00,0xe00,0xe00,0xe00,0xe00},
  {0x463,0x81,0xe2,0x54,0x6,0x40262,0x2b1,0x817,0xe00,0xe00,0xe00,0xe00,0xe00,0xe00,0xe00,0xe00,0xe00,0xe00,0xe00,0xe00},
  {0x414,0x493,0x2417,0x3,0x4c0,0x4e0,0x100264,0x2c1,0x402d2,0x601,0xe00,0xe00,0xe00,0xe00,0xe00,0xe00,0xe00,0xe00,0xe00,0xe00},
  {0x434,0x407,0x2437,0x13,0x74,0x4c4,0x4b5,0x24b1,0x4f7,0x581,0x5a0,0x551,0x122b0,0x811,0xe00,0xe00,0xe00,0xe00,0xe00,0xe00},
  {0x473,0xff800217,0x582,0x552,0x3e02b5,0x2097,0x615,0xe00,0xe00,0xe00,0xe00,0xe00,0xe00,0xe00,0xe00,0xe00,0xe00,0xe00,0xe00,0xe00},
  {0x405,0x230,0x14,0x266,0x2002d5,0x612,0xe00,0xe00,0xe00,0xe00,0xe00,0xe00,0xe00,0xe00,0xe00,0xe00,0xe00,0xe00,0xe00,0xe00},
  {0xb0,0xf1,0x73,0x15,0x66,0x10f6,0x2a6,0x2007,0x2047,0x620,0xe00,0xe00,0xe00,0xe00,0xe00,0xe00,0xe00,0xe00,0xe00,0xe00},
  {0xc0,0x234,0x295,0x823,0xe00,0xe00,0xe00,0xe00,0xe00,0xe00,0xe00,0xe00,0xe00,0xe00,0xe00,0xe00,0xe00,0xe00,0xe00,0xe00},
  {0xd0,0x242,0x26,0x4d2,0x4f2,0x580,0x2b3,0x2d0,0x2027,0x20e7,0xe00,0xe00,0xe00,0xe00,0xe00,0xe00,0xe00,0xe00,0xe00,0xe00},
  {0x425,0x215,0x20271,0x570,0x597,0x122c0,0x402e2,0x617,0xe00,0xe00,0xe00,0xe00,0xe00,0xe00,0xe00,0xe00,0xe00,0xe00,0xe00,0xe00},
  {0xe0,0xff800237,0x32291,0x5b4,0x810,0xe00,0xe00,0xe00,0xe00,0xe00,0xe00,0xe00,0xe00,0xe00,0xe00,0xe00,0xe00,0xe00,0xe00,0xe00},
  {0x445,0x427,0x457,0x23,0x84,0x4e2,0x4b7,0x20251,0x5a1,0x2557,0x5c5,0x5f7,0x814,0xe00,0xe00,0xe00,0xe00,0xe00,0xe00,0xe00},
  {0x483,0x232,0xb5,0x4e4,0x4d1,0x40282,0x5a7,0x5f5,0x805,0xe00,0xe00,0xe00,0xe00,0xe00,0xe00,0xe00,0xe00,0xe00,0xe00,0xe00},
  {0x464,0x91,0xf2,0x64,0x16,0x4b2,0x4f1,0x560,0x808002b7,0x2057,0x602,0xe00,0xe00,0xe00,0xe00,0xe00,0xe00,0xe00,0xe00,0xe00},
  {0x415,0xff800227,0x2527,0x404002b6,0x2087,0x605,0xe00,0xe00,0xe00,0xe00,0xe00,0xe00,0xe00,0xe00,0xe00,0xe00,0xe00,0xe00,0xe00,0xe00},
  {0xf0,0x235,0x12270,0x2b4,0x122e0,0x610,0xe00,0xe00,0xe00,0xe00,0xe00,0xe00,0xe00,0xe00,0xe00,0xe00,0xe00,0xe00,0xe00,0xe00},
  {0x435,0xa1,0x400246,0x2b2,0x801,0xe00,0xe00,0xe00,0xe00,0xe00,0xe00,0xe00,0xe00,0xe00,0xe00,0xe00,0xe00,0xe00,0xe00,0xe00},
};

struct HostState { bool init; Params p; void* out; const void* in[9]; };
HostState g_hs;

void build_state(void* const* d_in, void* d_out) {
  void* fn = nullptr;
  cudaDriverEntryPointQueryResult qr;
  cudaGetDriverEntryPoint("cuTensorMapEncodeTiled", &fn, cudaEnableDefault, &qr);
  EncodeFn enc = (EncodeFn)fn;
  void *kv, *ctx, *oA;
  cudaGetSymbolAddress(&kv, g_kv);
  cudaGetSymbolAddress(&ctx, g_ctx);
  cudaGetSymbolAddress(&oA, g_oA);
  Params& p = g_hs.p;
  make_map_2d(enc, &p.maps[M_AX], d_in[0], 2048, SEQ / 2);
  make_map_2d(enc, &p.maps[M_BX], d_in[3], 1024, SEQ);
  make_map_2d(enc, &p.maps[M_CKV], d_in[4], 512, SEQ);
  make_map_2d(enc, &p.maps[M_OA], oA, 1024, SEQ);
  make_map_2d(enc, &p.maps[M_CTX], ctx, 4096, SEQ);
  make_map_3d(enc, &p.maps[M_WQKV], d_in[1], 3072, 1024, 1024, 32, 3);
  make_map_3d(enc, &p.maps[M_WQ], d_in[5], 4096, 1024, 64, 64, 2);
  make_map_3d(enc, &p.maps[M_WUK], d_in[6], 4096, 512, 64, 64, 2);
  make_map_3d(enc, &p.maps[M_WUV], d_in[7], 4096, 512, 64, 64, 2);
  make_map_3d(enc, &p.maps[M_WOA], d_in[2], 1024, 1024, 64, 64, 2);
  make_map_3d(enc, &p.maps[M_WOB], d_in[8], 1024, 4096, 64, 64, 2);
  make_map_2d(enc, &p.maps[M_KV_LD], kv, 256, 32 * SEQ);
  make_map_3d(enc, &p.maps[M_OA_ST], oA, 1024, SEQ, 64, 64, 1);
  make_map_3d(enc, &p.maps[M_CTX_ST], ctx, 4096, SEQ, 64, 64, 2);
  make_map_3d(enc, &p.maps[M_KV_ST], kv, 256, 32 * SEQ, 64, 64, 2);
  make_map_3d(enc, &p.maps[M_OUTA_ST], d_out, 4096, SEQ / 2, 64, 64, 2);
  make_map_3d(enc, &p.maps[M_OUTB_ST], d_out, 2048, SEQ, 64, 64, 2);
  for (int c = 0; c < NPAIR; c++)
    for (int i = 0; i < MAX_ITEMS; i++) p.sched[c][i] = h_sched[c][i];
  cudaFuncSetAttribute(mega_kernel, cudaFuncAttributeMaxDynamicSharedMemorySize, SMEM_BYTES);
}

}

extern "C" void kernel_launch(void* const* d_in, const int* in_sizes, int n_in, void* d_out, int out_size) {
  (void)in_sizes; (void)n_in; (void)out_size;
  bool same = g_hs.init && g_hs.out == d_out;
  for (int i = 0; i < 9 && same; i++) same = (g_hs.in[i] == d_in[i]);
  if (!same) {
    build_state(d_in, d_out);
    g_hs.init = true; g_hs.out = d_out;
    for (int i = 0; i < 9; i++) g_hs.in[i] = d_in[i];
  }
  mega_kernel<<<NCTA, 384, SMEM_BYTES, cudaStreamPerThread>>>(g_hs.p);
}
```

```cpp
#include <cuda_runtime.h>
#include <cuda_bf16.h>
#include <cuda.h>
#include <stdint.h>

namespace {

constexpr int SEQ = 2048;
constexpr int NCTA = 132, NPAIR = 66;
constexpr int MAX_ITEMS = 20;

__device__ __align__(1024) __nv_bfloat16 g_kv[32 * SEQ * 256];
__device__ __align__(1024) __nv_bfloat16 g_ctx[SEQ * 4096];
__device__ __align__(1024) __nv_bfloat16 g_oA[SEQ * 1024];
__device__ __align__(1024) uint8_t g_halo[16 * 16 * 2048];
struct Flags { uint32_t m[64]; uint32_t epoch[NCTA]; };
__device__ __align__(128) Flags g_flags;
enum { F_KV = 0, F_CTX = 32, F_QL = 48 };

enum { K_QL = 0, K_QF = 1, K_KV = 2, K_OA = 3, K_OB = 4, K_END = 7 };
enum { M_AX = 0, M_BX, M_CKV, M_OA, M_CTX, M_WQKV, M_WQ, M_WUK, M_WOA, M_WOB, M_WUV, M_KV_LD, M_OA_ST, M_CTX_ST, M_KV_ST, M_OUTA_ST, M_OUTB_ST, M_COUNT };

struct Params {
  CUtensorMap maps[M_COUNT];
  alignas(16) uint32_t sched[NPAIR][MAX_ITEMS];
};

#define TRC(idx, slot)
#define TRW(idx, slot)
#define T4Q(dep)
#define T4X(dep)
#define T4K()

constexpr uint32_t SB = 1024;
constexpr uint32_t OFF_A = 0;
constexpr uint32_t OFF_B = 65536;
constexpr uint32_t OFF_STG = 196608;
constexpr uint32_t OFF_HALO = 229376;
constexpr uint32_t OFF_BAR = 231424;
constexpr uint32_t OFF_MASK = OFF_BAR + 256;
constexpr uint32_t OFF_LIST = OFF_BAR + 512;
constexpr uint32_t OFF_FILLS = OFF_BAR + 608;
constexpr uint32_t SMEM_BYTES = OFF_BAR + 640;
enum { B_FULL = 0, B_EMPTY = 4, B_QEMPTY = 8, B_STGE = 10, B_STGF = 12, B_FIN = 14, B_QFULL = 16, B_QX = 17, B_LEAD = 18, B_HFULL = 19, B_HEMPTY = 20, B_RELF = 21, B_RELE = 23, B_COUNT = 25 };
__host__ __device__ constexpr uint32_t BAR(int b) { return OFF_BAR + b * 8; }
__host__ __device__ constexpr int bar_count(int b) { return b < B_EMPTY ? 1 : b < B_QEMPTY ? 4 : b < B_STGE ? 8 : b < B_STGF ? 1 : b < B_QFULL ? 4 : b == B_QX ? 2 : 1; }
#define RCONS 232
constexpr int REG_CONS = RCONS, REG_PROD = (64512 - RCONS * 256) / 128 / 8 * 8;
#define KVSLOT(h) (h)
#define PACE_MAX 1100
#define WATCH_NS 250
#define HINTS 3
#define JSPLIT 14
#define JEDGE 14
#define LSH 1
#define LPUB 1
#define SBU 1
#define LHS 1
#define LPUBP 0
#define LEADF 3
#define EARLYN 3
#define HLATE 3
#define LASTUSE 3
#define RELW 1
#define MEARLY 1
#define LVL 1
#define EREL 1
#define JP 14
#define JDIAG2 8
#define JDIAG 10
#define LEADN 2
#define LEADL 2
#define STGA 3
#define STGB 8
#define STGAL 4
#define STGBL 12
#define PUBD 1

__device__ __forceinline__ uint32_t smem_u32(const void* p) { return (uint32_t)__cvta_generic_to_shared(p); }
__device__ __forceinline__ void wg_fence() { asm volatile("wgmma.fence.sync.aligned;" ::: "memory"); }
__device__ __forceinline__ void wg_commit() { asm volatile("wgmma.commit_group.sync.aligned;" ::: "memory"); }
template <int N> __device__ __forceinline__ void wg_wait() { asm volatile("wgmma.wait_group.sync.aligned %0;" ::"n"(N) : "memory"); }
__host__ __device__ constexpr uint32_t dlo(uint32_t off, uint32_t lbo) { return ((SB + off) >> 4) | ((lbo >> 4) << 16); }
template <uint32_t O> __device__ __forceinline__ void mbar_init(uint32_t a, uint32_t cnt) { asm volatile("mbarrier.init.shared::cta.b64 [%0+%2], %1;" ::"r"(a), "r"(cnt), "n"(O) : "memory"); }
template <uint32_t O> __device__ __forceinline__ void mbar_expect_tx(uint32_t a, uint32_t bytes) { asm volatile("mbarrier.arrive.expect_tx.shared::cta.b64 _, [%0+%2], %1;" ::"r"(a), "r"(bytes), "n"(O) : "memory"); }
template <uint32_t O> __device__ __forceinline__ void mbar_arrive_if(uint32_t a, bool pred) {
  asm volatile("{\n.reg .pred p;\nsetp.ne.u32 p, %1, 0;\n@p mbarrier.arrive.shared::cta.b64 _, [%0+%2];\n}\n" ::"r"(a), "r"((uint32_t)pred), "n"(O) : "memory");
}
template <uint32_t O> __device__ __forceinline__ void mbar_arrive_cl(uint32_t a, uint32_t off = 0) {
  asm volatile("{\n.reg .pred p;\nsetp.ne.u32 p, %2, 0;\n@p mbarrier.arrive.shared::cluster.b64 _, [%0+%1];\n}\n" ::"r"(a + off), "n"(O), "r"(a) : "memory");
}
template <uint32_t O> __device__ __forceinline__ bool mbar_test(uint32_t a, uint32_t parity) {
  uint32_t ok;
  asm volatile("{\n.reg .pred p;\nmbarrier.test_wait.parity.shared::cta.b64 p, [%1+%3], %2;\nselp.u32 %0, 1, 0, p;\n}\n" : "=r"(ok) : "r"(a), "r"(parity), "n"(O) : "memory");
  return ok;
}
template <uint32_t O> __device__ __forceinline__ void mbar_wait(uint32_t a, uint32_t parity) {
  asm volatile("{\n.reg .pred p, q;\n.reg .u32 n;\nmov.u32 n, 0;\nWAIT_%=:\nadd.u32 n, n, 1;\nmbarrier.try_wait.parity.shared::cta.b64 p, [%0+%2], %1;\n"
               "setp.lt.u32 q, n, 4194304;\nand.pred q, q, !p;\n@q bra WAIT_%=;\n@!p st.shared.u32 [%0+1], n;\n}\n" ::"r"(a), "r"(parity), "n"(O) : "memory");
}
template <uint32_t O> __device__ __forceinline__ void mbar_wait_long(uint32_t a, uint32_t parity) {
  asm volatile("{\n.reg .pred p, q;\n.reg .u32 n;\nmov.u32 n, 0;\nWAIT_%=:\nadd.u32 n, n, 1;\nmbarrier.try_wait.parity.shared::cta.b64 p, [%0+%2], %1, 4000;\n"
               "setp.lt.u32 q, n, 1048576;\nand.pred q, q, !p;\n@q bra WAIT_%=;\n@!p st.shared.u32 [%0+1], n;\n}\n" ::"r"(a), "r"(parity), "n"(O) : "memory");
}
__device__ __forceinline__ void tma_load_2d(uint32_t dst, const CUtensorMap* tm, int c0, int c1, uint32_t bar) {
  asm volatile("cp.async.bulk.tensor.2d.shared::cluster.global.mbarrier::complete_tx::bytes [%0], [%1, {%3, %4}], [%2];" ::"r"(dst), "l"(tm), "r"(bar), "r"(c0), "r"(c1) : "memory");
}
__device__ __forceinline__ void tma_load_3d(uint32_t dst, const CUtensorMap* tm, int c0, int c1, int c2, uint32_t bar) {
  asm volatile("cp.async.bulk.tensor.3d.shared::cluster.global.mbarrier::complete_tx::bytes [%0], [%1, {%3, %4, %5}], [%2];" ::"r"(dst), "l"(tm), "r"(bar), "r"(c0), "r"(c1), "r"(c2) : "memory");
}
#define FILL_HEAD "{\n.reg .pred p, q;\n.reg .u32 n;\nmov.u32 n, 0;\nWAIT_%=:\nadd.u32 n, n, 1;\nmbarrier.try_wait.parity.shared::cta.b64 p, [%0+%1], %3;\n" \
                  "setp.lt.u32 q, n, 4194304;\nand.pred q, q, !p;\n@q bra WAIT_%=;\n@!p st.shared.u32 [%0+1], n;\nelect.sync _|p, 0xffffffff;\n" \
                  "@p mbarrier.arrive.expect_tx.shared::cta.b64 _, [%2], %4;\n"
__device__ __forceinline__ void fill_gemm(uint32_t bb, uint32_t parity, uint32_t bytes, uint32_t dstb, const CUtensorMap* mb, int b0, int b1, int b2, uint32_t dsta, const CUtensorMap* ma, int a0, int a1, uint64_t pb, uint64_t pa) {
  asm volatile(FILL_HEAD
               "@p cp.async.bulk.tensor.3d.shared::cluster.global.mbarrier::complete_tx::bytes.multicast::cluster.L2::cache_hint [%5], [%6, {%7, %8, %9}], [%2], %14, %15;\n"
               "@p cp.async.bulk.tensor.2d.shared::cluster.global.mbarrier::complete_tx::bytes.L2::cache_hint [%10], [%11, {%12, %13}], [%2], %16;\n}\n"
               ::"r"(bb), "n"(BAR(B_EMPTY)), "r"(bb + BAR(B_FULL)), "r"(parity), "r"(bytes), "r"(dstb), "l"(mb), "r"(b0), "r"(b1), "r"(b2), "r"(dsta), "l"(ma), "r"(a0), "r"(a1), "h"((uint16_t)3), "l"(pb), "l"(pa) : "memory");
}
__device__ __forceinline__ void fill_kv(uint32_t bb, uint32_t parity, uint32_t dst, const CUtensorMap* m, int c0, int c1, uint16_t mask, uint64_t pol) {
  asm volatile(FILL_HEAD
               "@p cp.async.bulk.tensor.2d.shared::cluster.global.mbarrier::complete_tx::bytes.multicast::cluster.L2::cache_hint [%5], [%6, {%7, %8}], [%2], %9, %10;\n}\n"
               ::"r"(bb), "n"(BAR(B_EMPTY)), "r"(bb + BAR(B_FULL)), "r"(parity), "r"(32768), "r"(dst), "l"(m), "r"(c0), "r"(c1), "h"(mask), "l"(pol) : "memory");
}
__device__ __forceinline__ void tma_load_2d_h(uint32_t dst, const CUtensorMap* tm, int c0, int c1, uint32_t bar, uint64_t pol) {
  asm volatile("{\n.reg .pred p;\nelect.sync _|p, 0xffffffff;\n@p cp.async.bulk.tensor.2d.shared::cluster.global.mbarrier::complete_tx::bytes.L2::cache_hint [%0], [%1, {%3, %4}], [%2], %5;\n}\n" ::"r"(dst), "l"(tm), "r"(bar), "r"(c0), "r"(c1), "l"(pol) : "memory");
}
__device__ __forceinline__ void tma_store_3d(const CUtensorMap* tm, uint32_t src, int c0, int c1, int c2, uint64_t pol) {
  asm volatile("{\n.reg .pred p;\nelect.sync _|p, 0xffffffff;\n@p cp.async.bulk.tensor.3d.global.shared::cta.bulk_group.L2::cache_hint [%0, {%2, %3, %4}], [%1], %5;\n}\n" ::"l"(tm), "r"(src), "r"(c0), "r"(c1), "r"(c2), "l"(pol) : "memory");
}
__device__ __forceinline__ void bulk_load(uint32_t dst, const void* src, uint32_t bytes, uint32_t bar) {
  asm volatile("{\n.reg .pred p;\nelect.sync _|p, 0xffffffff;\n@p cp.async.bulk.shared::cluster.global.mbarrier::complete_tx::bytes [%0], [%1], %2, [%3];\n}\n" ::"r"(dst), "l"(src), "r"(bytes), "r"(bar) : "memory");
}
__device__ __forceinline__ void bulk_store(void* dst, uint32_t src, uint32_t bytes) {
  asm volatile("{\n.reg .pred p;\nelect.sync _|p, 0xffffffff;\n@p cp.async.bulk.global.shared::cta.bulk_group [%0], [%1], %2;\n}\n" ::"l"(dst), "r"(src), "r"(bytes) : "memory");
}
__device__ __forceinline__ void bulk_send(uint32_t dst, uint32_t src, uint32_t bytes, uint32_t bar) {
  asm volatile("{\n.reg .pred p;\nelect.sync _|p, 0xffffffff;\n@p cp.async.bulk.shared::cluster.shared::cta.mbarrier::complete_tx::bytes [%0], [%1], %2, [%3];\n}\n" ::"r"(dst), "r"(src), "r"(bytes), "r"(bar) : "memory");
}
__device__ __forceinline__ uint64_t policy_evict_first() { uint64_t p; asm volatile("createpolicy.fractional.L2::evict_first.b64 %0, 1.0;" : "=l"(p)); return p; }
constexpr uint64_t POL_NORMAL = 0x1000000000000000ull;
__device__ __forceinline__ uint32_t mapa(uint32_t addr, uint32_t rank) { uint32_t r; asm("mapa.shared::cluster.u32 %0, %1, %2;" : "=r"(r) : "r"(addr), "r"(rank)); return r; }
__device__ __forceinline__ void cluster_arrive_relaxed() { asm volatile("barrier.cluster.arrive.relaxed.aligned;" ::: "memory"); }
__device__ __forceinline__ void cluster_arrive() { asm volatile("barrier.cluster.arrive.release.aligned;" ::: "memory"); }
__device__ __forceinline__ void cluster_wait() { asm volatile("barrier.cluster.wait.acquire.aligned;" ::: "memory"); }
__device__ __forceinline__ void bulk_commit() { asm volatile("cp.async.bulk.commit_group;" ::: "memory"); }
template <int N> __device__ __forceinline__ void bulk_wait_read() { asm volatile("cp.async.bulk.wait_group.read %0;" ::"n"(N) : "memory"); }
__device__ __forceinline__ void bulk_wait_all() { asm volatile("cp.async.bulk.wait_group 0;" ::: "memory"); }
__device__ __forceinline__ void fence_async_smem() { asm volatile("fence.proxy.async.shared::cta;" ::: "memory"); }
__device__ __forceinline__ void fence_async_glob() { asm volatile("fence.proxy.async.global;" ::: "memory"); }
__device__ __forceinline__ void flag_toggle(uint32_t* p, uint32_t v) { asm volatile("{\n.reg .pred p;\nelect.sync _|p, 0xffffffff;\n@p red.release.gpu.global.xor.b32 [%0], %1;\n}\n" ::"l"(p), "r"(v) : "memory"); }
template <uint32_t O> __device__ __forceinline__ uint32_t lds_acquire(uint32_t a) { uint32_t v; asm volatile("ld.acquire.cta.shared::cta.u32 %0, [%1+%2];" : "=r"(v) : "r"(a), "n"(O) : "memory"); return v; }
__device__ __forceinline__ uint32_t item_full(uint32_t sb, int idx) {
  uint32_t c;
  asm volatile("ld.shared.u32 %0, [%1+%2];" : "=r"(c) : "r"(sb + idx * 4), "n"(OFF_LIST));
  return __reduce_or_sync(0xffffffffu, c);
}
__device__ __forceinline__ uint32_t item(uint32_t sb, int idx) { return item_full(sb, idx) & 4095; }
template <int N> __device__ __forceinline__ void reg_alloc() { asm volatile("setmaxnreg.inc.sync.aligned.u32 %0;" ::"n"(N)); }
template <int N> __device__ __forceinline__ void reg_dealloc() { asm volatile("setmaxnreg.dec.sync.aligned.u32 %0;" ::"n"(N)); }
template <int I0, int I1, int N> __device__ __forceinline__ void fence_regs(float (&d)[N]) {
#pragma unroll
  for (int i = I0; i < I1; i++) asm volatile("" : "+f"(d[i])::"memory");
}
template <int N> __device__ __forceinline__ void fence_regs(float (&d)[N]) { fence_regs<0, N, N>(d); }
template <int N> __device__ __forceinline__ void fence_regs(uint32_t (&d)[N]) {
#pragma unroll
  for (int i = 0; i < N; i++) asm volatile("" : "+r"(d[i])::"memory");
}
__device__ __forceinline__ uint32_t pack_bf16(float lo, float hi) { uint32_t r; asm("cvt.rn.bf16x2.f32 %0, %1, %2;" : "=r"(r) : "f"(hi), "f"(lo)); return r; }
__device__ __forceinline__ uint32_t v_pack(float lo, float hi) { uint32_t r; asm volatile("cvt.rn.bf16x2.f32 %0, %1, %2;" : "=r"(r) : "f"(hi), "f"(lo)); return r; }
template <uint32_t O> __device__ __forceinline__ void stmatrix_x4(uint32_t a, uint32_t r0, uint32_t r1, uint32_t r2, uint32_t r3) {
  asm volatile("stmatrix.sync.aligned.m8n8.x4.shared.b16 [%0+%5], {%1, %2, %3, %4};" ::"r"(a), "r"(r0), "r"(r1), "r"(r2), "r"(r3), "n"(O) : "memory");
}
template <uint32_t O> __device__ __forceinline__ void stmatrix_x4_after(uint32_t a, uint32_t r0, uint32_t r1, uint32_t r2, uint32_t r3, float dep, uint32_t on) {
  asm volatile("{\n.reg .pred p, q;\n.reg .u32 a;\nsetp.ne.u32 p, %7, 0;\nsetp.ne.u32 q, %6, 0xffffffff;\nselp.u32 a, %0, 0, q;\n@p stmatrix.sync.aligned.m8n8.x4.shared.b16 [a+%5], {%1, %2, %3, %4};\n}\n"
               ::"r"(a), "r"(r0), "r"(r1), "r"(r2), "r"(r3), "n"(O), "r"(__float_as_uint(dep)), "r"(on) : "memory");
}
template <uint32_t O> __device__ __forceinline__ void stmatrix_x4_trans(uint32_t a, uint32_t r0, uint32_t r1, uint32_t r2, uint32_t r3) {
  asm volatile("stmatrix.sync.aligned.m8n8.x4.trans.shared.b16 [%0+%5], {%1, %2, %3, %4};" ::"r"(a), "r"(r0), "r"(r1), "r"(r2), "r"(r3), "n"(O) : "memory");
}
template <uint32_t O> __device__ __forceinline__ void sts64(uint32_t a, const uint32_t* r) { asm volatile("st.shared.v2.u32 [%0+%3], {%1, %2};" ::"r"(a), "r"(r[0]), "r"(r[1]), "n"(O) : "memory"); }
template <uint32_t O> __device__ __forceinline__ void lds64(uint32_t* r, uint32_t a) { asm volatile("ld.shared.v2.u32 {%0, %1}, [%2+%3];" : "=r"(r[0]), "=r"(r[1]) : "r"(a), "n"(O) : "memory"); }
template <uint32_t O> __device__ __forceinline__ void lds128(uint32_t* r, uint32_t a) { asm volatile("ld.shared.v4.u32 {%0, %1, %2, %3}, [%4+%5];" : "=r"(r[0]), "=r"(r[1]), "=r"(r[2]), "=r"(r[3]) : "r"(a), "n"(O) : "memory"); }
__device__ __forceinline__ uint32_t transpose8(uint32_t a) { uint32_t d; asm volatile("movmatrix.sync.aligned.m8n8.trans.b16 %0, %1;" : "=r"(d) : "r"(a)); return d; }
__device__ __forceinline__ float ex2(float x) { float y; asm("ex2.approx.ftz.f32 %0, %1;" : "=f"(y) : "f"(x)); return y; }
__device__ __forceinline__ float rcp(float x) { float y; asm("rcp.approx.ftz.f32 %0, %1;" : "=f"(y) : "f"(x)); return y; }
__device__ __forceinline__ void bar_sync(int id, int n) { asm volatile("bar.sync %0, %1;" ::"r"(id), "r"(n) : "memory"); }
__device__ __forceinline__ void bar_arrive(int id, int n) { asm volatile("bar.arrive %0, %1;" ::"r"(id), "r"(n) : "memory"); }
__device__ __forceinline__ void mma16816(float (&c)[4], uint32_t a0, uint32_t a1, uint32_t a2, uint32_t a3, uint32_t b0, uint32_t b1) {
  asm("mma.sync.aligned.m16n8k16.row.col.f32.bf16.bf16.f32 {%0, %1, %2, %3}, {%4, %5, %6, %7}, {%8, %9}, {%0, %1, %2, %3};"
      : "+f"(c[0]), "+f"(c[1]), "+f"(c[2]), "+f"(c[3]) : "r"(a0), "r"(a1), "r"(a2), "r"(a3), "r"(b0), "r"(b1));
}
__device__ __forceinline__ void mma16816z(float (&c)[4], uint32_t a0, uint32_t a1, uint32_t a2, uint32_t a3, uint32_t b0, uint32_t b1, const uint32_t (&z)[4]) {
  asm("mma.sync.aligned.m16n8k16.row.col.f32.bf16.bf16.f32 {%0, %1, %2, %3}, {%4, %5, %6, %7}, {%8, %9}, {%10, %11, %12, %13};"
      : "=f"(c[0]), "=f"(c[1]), "=f"(c[2]), "=f"(c[3]) : "r"(a0), "r"(a1), "r"(a2), "r"(a3), "r"(b0), "r"(b1),
        "f"(__uint_as_float(z[0])), "f"(__uint_as_float(z[1])), "f"(__uint_as_float(z[2])), "f"(__uint_as_float(z[3])));
}
__device__ __forceinline__ uint4 ldg128(const void* p) { uint4 v; asm volatile("ld.global.cg.v4.u32 {%0, %1, %2, %3}, [%4];" : "=r"(v.x), "=r"(v.y), "=r"(v.z), "=r"(v.w) : "l"(p) : "memory"); return v; }
__device__ __forceinline__ uint32_t ldg16(const void* p) { uint16_t v; asm volatile("ld.global.cg.u16 %0, [%1];" : "=h"(v) : "l"(p) : "memory"); return v; }
__device__ __forceinline__ float quad_sum(float v) {
  v += __shfl_xor_sync(0xffffffffu, v, 1);
  v += __shfl_xor_sync(0xffffffffu, v, 2);
  return v;
}
__device__ __forceinline__ bool elect_one() { uint32_t p; asm volatile("{\n.reg .pred p;\nelect.sync _|p, 0xffffffff;\nselp.u32 %0, 1, 0, p;\n}\n" : "=r"(p)); return p; }
#define UNLIKELY(x) __builtin_expect(!!(x), 0)

__device__ __forceinline__ void wg_gemm_init(float (&d)[128], uint32_t alo, uint32_t blo) {
  asm volatile("{\n.reg .pred p;\n.reg .b64 da, db;\nmov.b64 da, {%128, 0x40000040};\nmov.b64 db, {%129, 0x40000040};\nsetp.ne.b32 p, 0, 0;\n"
    "wgmma.mma_async.sync.aligned.m64n256k16.f32.bf16.bf16 {"
    "%0, %1, %2, %3, %4, %5, %6, %7, %8, %9, %10, %11, %12, %13, %14, %15, %16, %17, %18, %19, %20, %21, %22, %23, %24, %25, %26, %27, %28, %29, %30, %31, "
    "%32, %33, %34, %35, %36, %37, %38, %39, %40, %41, %42, %43, %44, %45, %46, %47, %48, %49, %50, %51, %52, %53, %54, %55, %56, %57, %58, %59, %60, %61, %62, %63, "
    "%64, %65, %66, %67, %68, %69, %70, %71, %72, %73, %74, %75, %76, %77, %78, %79, %80, %81, %82, %83, %84, %85, %86, %87, %88, %89, %90, %91, %92, %93, %94, %95, "
    "%96, %97, %98, %99, %100, %101, %102, %103, %104, %105, %106, %107, %108, %109, %110, %111, %112, %113, %114, %115, %116, %117, %118, %119, %120, %121, %122, %123, %124, %125, %126, %127}, "
    "da, db, p, 1, 1, 0, 1;\n}\n"
    : "=f"(d[0]), "=f"(d[1]), "=f"(d[2]), "=f"(d[3]), "=f"(d[4]), "=f"(d[5]), "=f"(d[6]), "=f"(d[7]), "=f"(d[8]), "=f"(d[9]), "=f"(d[10]), "=f"(d[11]), "=f"(d[12]), "=f"(d[13]), "=f"(d[14]), "=f"(d[15]),
      "=f"(d[16]), "=f"(d[17]), "=f"(d[18]), "=f"(d[19]), "=f"(d[20]), "=f"(d[21]), "=f"(d[22]), "=f"(d[23]), "=f"(d[24]), "=f"(d[25]), "=f"(d[26]), "=f"(d[27]), "=f"(d[28]), "=f"(d[29]), "=f"(d[30]), "=f"(d[31]),
      "=f"(d[32]), "=f"(d[33]), "=f"(d[34]), "=f"(d[35]), "=f"(d[36]), "=f"(d[37]), "=f"(d[38]), "=f"(d[39]), "=f"(d[40]), "=f"(d[41]), "=f"(d[42]), "=f"(d[43]), "=f"(d[44]), "=f"(d[45]), "=f"(d[46]), "=f"(d[47]),
      "=f"(d[48]), "=f"(d[49]), "=f"(d[50]), "=f"(d[51]), "=f"(d[52]), "=f"(d[53]), "=f"(d[54]), "=f"(d[55]), "=f"(d[56]), "=f"(d[57]), "=f"(d[58]), "=f"(d[59]), "=f"(d[60]), "=f"(d[61]), "=f"(d[62]), "=f"(d[63]),
      "=f"(d[64]), "=f"(d[65]), "=f"(d[66]), "=f"(d[67]), "=f"(d[68]), "=f"(d[69]), "=f"(d[70]), "=f"(d[71]), "=f"(d[72]), "=f"(d[73]), "=f"(d[74]), "=f"(d[75]), "=f"(d[76]), "=f"(d[77]), "=f"(d[78]), "=f"(d[79]),
      "=f"(d[80]), "=f"(d[81]), "=f"(d[82]), "=f"(d[83]), "=f"(d[84]), "=f"(d[85]), "=f"(d[86]), "=f"(d[87]), "=f"(d[88]), "=f"(d[89]), "=f"(d[90]), "=f"(d[91]), "=f"(d[92]), "=f"(d[93]), "=f"(d[94]), "=f"(d[95]),
      "=f"(d[96]), "=f"(d[97]), "=f"(d[98]), "=f"(d[99]), "=f"(d[100]), "=f"(d[101]), "=f"(d[102]), "=f"(d[103]), "=f"(d[104]), "=f"(d[105]), "=f"(d[106]), "=f"(d[107]), "=f"(d[108]), "=f"(d[109]), "=f"(d[110]), "=f"(d[111]),
      "=f"(d[112]), "=f"(d[113]), "=f"(d[114]), "=f"(d[115]), "=f"(d[116]), "=f"(d[117]), "=f"(d[118]), "=f"(d[119]), "=f"(d[120]), "=f"(d[121]), "=f"(d[122]), "=f"(d[123]), "=f"(d[124]), "=f"(d[125]), "=f"(d[126]), "=f"(d[127])
    : "r"(alo), "r"(blo));
}
__device__ __forceinline__ void wg_gemm_acc(float (&d)[128], uint32_t alo, uint32_t blo) {
  asm volatile("{\n.reg .pred p;\n.reg .b64 da, db;\nmov.b64 da, {%128, 0x40000040};\nmov.b64 db, {%129, 0x40000040};\nsetp.eq.b32 p, 0, 0;\n"
    "wgmma.mma_async.sync.aligned.m64n256k16.f32.bf16.bf16 {"
    "%0, %1, %2, %3, %4, %5, %6, %7, %8, %9, %10, %11, %12, %13, %14, %15, %16, %17, %18, %19, %20, %21, %22, %23, %24, %25, %26, %27, %28, %29, %30, %31, "
    "%32, %33, %34, %35, %36, %37, %38, %39, %40, %41, %42, %43, %44, %45, %46, %47, %48, %49, %50, %51, %52, %53, %54, %55, %56, %57, %58, %59, %60, %61, %62, %63, "
    "%64, %65, %66, %67, %68, %69, %70, %71, %72, %73, %74, %75, %76, %77, %78, %79, %80, %81, %82, %83, %84, %85, %86, %87, %88, %89, %90, %91, %92, %93, %94, %95, "
    "%96, %97, %98, %99, %100, %101, %102, %103, %104, %105, %106, %107, %108, %109, %110, %111, %112, %113, %114, %115, %116, %117, %118, %119, %120, %121, %122, %123, %124, %125, %126, %127}, "
    "da, db, p, 1, 1, 0, 1;\n}\n"
    : "+f"(d[0]), "+f"(d[1]), "+f"(d[2]), "+f"(d[3]), "+f"(d[4]), "+f"(d[5]), "+f"(d[6]), "+f"(d[7]), "+f"(d[8]), "+f"(d[9]), "+f"(d[10]), "+f"(d[11]), "+f"(d[12]), "+f"(d[13]), "+f"(d[14]), "+f"(d[15]),
      "+f"(d[16]), "+f"(d[17]), "+f"(d[18]), "+f"(d[19]), "+f"(d[20]), "+f"(d[21]), "+f"(d[22]), "+f"(d[23]), "+f"(d[24]), "+f"(d[25]), "+f"(d[26]), "+f"(d[27]), "+f"(d[28]), "+f"(d[29]), "+f"(d[30]), "+f"(d[31]),
      "+f"(d[32]), "+f"(d[33]), "+f"(d[34]), "+f"(d[35]), "+f"(d[36]), "+f"(d[37]), "+f"(d[38]), "+f"(d[39]), "+f"(d[40]), "+f"(d[41]), "+f"(d[42]), "+f"(d[43]), "+f"(d[44]), "+f"(d[45]), "+f"(d[46]), "+f"(d[47]),
      "+f"(d[48]), "+f"(d[49]), "+f"(d[50]), "+f"(d[51]), "+f"(d[52]), "+f"(d[53]), "+f"(d[54]), "+f"(d[55]), "+f"(d[56]), "+f"(d[57]), "+f"(d[58]), "+f"(d[59]), "+f"(d[60]), "+f"(d[61]), "+f"(d[62]), "+f"(d[63]),
      "+f"(d[64]), "+f"(d[65]), "+f"(d[66]), "+f"(d[67]), "+f"(d[68]), "+f"(d[69]), "+f"(d[70]), "+f"(d[71]), "+f"(d[72]), "+f"(d[73]), "+f"(d[74]), "+f"(d[75]), "+f"(d[76]), "+f"(d[77]), "+f"(d[78]), "+f"(d[79]),
      "+f"(d[80]), "+f"(d[81]), "+f"(d[82]), "+f"(d[83]), "+f"(d[84]), "+f"(d[85]), "+f"(d[86]), "+f"(d[87]), "+f"(d[88]), "+f"(d[89]), "+f"(d[90]), "+f"(d[91]), "+f"(d[92]), "+f"(d[93]), "+f"(d[94]), "+f"(d[95]),
      "+f"(d[96]), "+f"(d[97]), "+f"(d[98]), "+f"(d[99]), "+f"(d[100]), "+f"(d[101]), "+f"(d[102]), "+f"(d[103]), "+f"(d[104]), "+f"(d[105]), "+f"(d[106]), "+f"(d[107]), "+f"(d[108]), "+f"(d[109]), "+f"(d[110]), "+f"(d[111]),
      "+f"(d[112]), "+f"(d[113]), "+f"(d[114]), "+f"(d[115]), "+f"(d[116]), "+f"(d[117]), "+f"(d[118]), "+f"(d[119]), "+f"(d[120]), "+f"(d[121]), "+f"(d[122]), "+f"(d[123]), "+f"(d[124]), "+f"(d[125]), "+f"(d[126]), "+f"(d[127])
    : "r"(alo), "r"(blo));
}
__device__ __forceinline__ void wg_gemm_init(float (&d)[96], uint32_t alo, uint32_t blo) {
  asm volatile("{\n.reg .pred p;\n.reg .b64 da, db;\nmov.b64 da, {%96, 0x40000040};\nmov.b64 db, {%97, 0x40000040};\nsetp.ne.b32 p, 0, 0;\n"
    "wgmma.mma_async.sync.aligned.m64n192k16.f32.bf16.bf16 {"
    "%0, %1, %2, %3, %4, %5, %6, %7, %8, %9, %10, %11, %12, %13, %14, %15, %16, %17, %18, %19, %20, %21, %22, %23, %24, %25, %26, %27, %28, %29, %30, %31, "
    "%32, %33, %34, %35, %36, %37, %38, %39, %40, %41, %42, %43, %44, %45, %46, %47, %48, %49, %50, %51, %52, %53, %54, %55, %56, %57, %58, %59, %60, %61, %62, %63, "
    "%64, %65, %66, %67, %68, %69, %70, %71, %72, %73, %74, %75, %76, %77, %78, %79, %80, %81, %82, %83, %84, %85, %86, %87, %88, %89, %90, %91, %92, %93, %94, %95}, "
    "da, db, p, 1, 1, 0, 1;\n}\n"
    : "=f"(d[0]), "=f"(d[1]), "=f"(d[2]), "=f"(d[3]), "=f"(d[4]), "=f"(d[5]), "=f"(d[6]), "=f"(d[7]), "=f"(d[8]), "=f"(d[9]), "=f"(d[10]), "=f"(d[11]), "=f"(d[12]), "=f"(d[13]), "=f"(d[14]), "=f"(d[15]),
      "=f"(d[16]), "=f"(d[17]), "=f"(d[18]), "=f"(d[19]), "=f"(d[20]), "=f"(d[21]), "=f"(d[22]), "=f"(d[23]), "=f"(d[24]), "=f"(d[25]), "=f"(d[26]), "=f"(d[27]), "=f"(d[28]), "=f"(d[29]), "=f"(d[30]), "=f"(d[31]),
      "=f"(d[32]), "=f"(d[33]), "=f"(d[34]), "=f"(d[35]), "=f"(d[36]), "=f"(d[37]), "=f"(d[38]), "=f"(d[39]), "=f"(d[40]), "=f"(d[41]), "=f"(d[42]), "=f"(d[43]), "=f"(d[44]), "=f"(d[45]), "=f"(d[46]), "=f"(d[47]),
      "=f"(d[48]), "=f"(d[49]), "=f"(d[50]), "=f"(d[51]), "=f"(d[52]), "=f"(d[53]), "=f"(d[54]), "=f"(d[55]), "=f"(d[56]), "=f"(d[57]), "=f"(d[58]), "=f"(d[59]), "=f"(d[60]), "=f"(d[61]), "=f"(d[62]), "=f"(d[63]),
      "=f"(d[64]), "=f"(d[65]), "=f"(d[66]), "=f"(d[67]), "=f"(d[68]), "=f"(d[69]), "=f"(d[70]), "=f"(d[71]), "=f"(d[72]), "=f"(d[73]), "=f"(d[74]), "=f"(d[75]), "=f"(d[76]), "=f"(d[77]), "=f"(d[78]), "=f"(d[79]),
      "=f"(d[80]), "=f"(d[81]), "=f"(d[82]), "=f"(d[83]), "=f"(d[84]), "=f"(d[85]), "=f"(d[86]), "=f"(d[87]), "=f"(d[88]), "=f"(d[89]), "=f"(d[90]), "=f"(d[91]), "=f"(d[92]), "=f"(d[93]), "=f"(d[94]), "=f"(d[95])
    : "r"(alo), "r"(blo));
}
__device__ __forceinline__ void wg_gemm_acc(float (&d)[96], uint32_t alo, uint32_t blo) {
  asm volatile("{\n.reg .pred p;\n.reg .b64 da, db;\nmov.b64 da, {%96, 0x40000040};\nmov.b64 db, {%97, 0x40000040};\nsetp.eq.b32 p, 0, 0;\n"
    "wgmma.mma_async.sync.aligned.m64n192k16.f32.bf16.bf16 {"
    "%0, %1, %2, %3, %4, %5, %6, %7, %8, %9, %10, %11, %12, %13, %14, %15, %16, %17, %18, %19, %20, %21, %22, %23, %24, %25, %26, %27, %28, %29, %30, %31, "
    "%32, %33, %34, %35, %36, %37, %38, %39, %40, %41, %42, %43, %44, %45, %46, %47, %48, %49, %50, %51, %52, %53, %54, %55, %56, %57, %58, %59, %60, %61, %62, %63, "
    "%64, %65, %66, %67, %68, %69, %70, %71, %72, %73, %74, %75, %76, %77, %78, %79, %80, %81, %82, %83, %84, %85, %86, %87, %88, %89, %90, %91, %92, %93, %94, %95}, "
    "da, db, p, 1, 1, 0, 1;\n}\n"
    : "+f"(d[0]), "+f"(d[1]), "+f"(d[2]), "+f"(d[3]), "+f"(d[4]), "+f"(d[5]), "+f"(d[6]), "+f"(d[7]), "+f"(d[8]), "+f"(d[9]), "+f"(d[10]), "+f"(d[11]), "+f"(d[12]), "+f"(d[13]), "+f"(d[14]), "+f"(d[15]),
      "+f"(d[16]), "+f"(d[17]), "+f"(d[18]), "+f"(d[19]), "+f"(d[20]), "+f"(d[21]), "+f"(d[22]), "+f"(d[23]), "+f"(d[24]), "+f"(d[25]), "+f"(d[26]), "+f"(d[27]), "+f"(d[28]), "+f"(d[29]), "+f"(d[30]), "+f"(d[31]),
      "+f"(d[32]), "+f"(d[33]), "+f"(d[34]), "+f"(d[35]), "+f"(d[36]), "+f"(d[37]), "+f"(d[38]), "+f"(d[39]), "+f"(d[40]), "+f"(d[41]), "+f"(d[42]), "+f"(d[43]), "+f"(d[44]), "+f"(d[45]), "+f"(d[46]), "+f"(d[47]),
      "+f"(d[48]), "+f"(d[49]), "+f"(d[50]), "+f"(d[51]), "+f"(d[52]), "+f"(d[53]), "+f"(d[54]), "+f"(d[55]), "+f"(d[56]), "+f"(d[57]), "+f"(d[58]), "+f"(d[59]), "+f"(d[60]), "+f"(d[61]), "+f"(d[62]), "+f"(d[63]),
      "+f"(d[64]), "+f"(d[65]), "+f"(d[66]), "+f"(d[67]), "+f"(d[68]), "+f"(d[69]), "+f"(d[70]), "+f"(d[71]), "+f"(d[72]), "+f"(d[73]), "+f"(d[74]), "+f"(d[75]), "+f"(d[76]), "+f"(d[77]), "+f"(d[78]), "+f"(d[79]),
      "+f"(d[80]), "+f"(d[81]), "+f"(d[82]), "+f"(d[83]), "+f"(d[84]), "+f"(d[85]), "+f"(d[86]), "+f"(d[87]), "+f"(d[88]), "+f"(d[89]), "+f"(d[90]), "+f"(d[91]), "+f"(d[92]), "+f"(d[93]), "+f"(d[94]), "+f"(d[95])
    : "r"(alo), "r"(blo));
}
__device__ __forceinline__ void wg_qk_init(float (&d)[64], uint32_t alo, uint32_t blo) {
  asm volatile("{\n.reg .pred p;\n.reg .b64 da, db;\nmov.b64 da, {%64, 0x40000040};\nmov.b64 db, {%65, 0x40000040};\nsetp.ne.b32 p, 0, 0;\n"
    "wgmma.mma_async.sync.aligned.m64n128k16.f32.bf16.bf16 {"
    "%0, %1, %2, %3, %4, %5, %6, %7, %8, %9, %10, %11, %12, %13, %14, %15, %16, %17, %18, %19, %20, %21, %22, %23, %24, %25, %26, %27, %28, %29, %30, %31, "
    "%32, %33, %34, %35, %36, %37, %38, %39, %40, %41, %42, %43, %44, %45, %46, %47, %48, %49, %50, %51, %52, %53, %54, %55, %56, %57, %58, %59, %60, %61, %62, %63}, "
    "da, db, p, 1, 1, 0, 0;\n}\n"
    : "=f"(d[0]), "=f"(d[1]), "=f"(d[2]), "=f"(d[3]), "=f"(d[4]), "=f"(d[5]), "=f"(d[6]), "=f"(d[7]), "=f"(d[8]), "=f"(d[9]), "=f"(d[10]), "=f"(d[11]), "=f"(d[12]), "=f"(d[13]), "=f"(d[14]), "=f"(d[15]),
      "=f"(d[16]), "=f"(d[17]), "=f"(d[18]), "=f"(d[19]), "=f"(d[20]), "=f"(d[21]), "=f"(d[22]), "=f"(d[23]), "=f"(d[24]), "=f"(d[25]), "=f"(d[26]), "=f"(d[27]), "=f"(d[28]), "=f"(d[29]), "=f"(d[30]), "=f"(d[31]),
      "=f"(d[32]), "=f"(d[33]), "=f"(d[34]), "=f"(d[35]), "=f"(d[36]), "=f"(d[37]), "=f"(d[38]), "=f"(d[39]), "=f"(d[40]), "=f"(d[41]), "=f"(d[42]), "=f"(d[43]), "=f"(d[44]), "=f"(d[45]), "=f"(d[46]), "=f"(d[47]),
      "=f"(d[48]), "=f"(d[49]), "=f"(d[50]), "=f"(d[51]), "=f"(d[52]), "=f"(d[53]), "=f"(d[54]), "=f"(d[55]), "=f"(d[56]), "=f"(d[57]), "=f"(d[58]), "=f"(d[59]), "=f"(d[60]), "=f"(d[61]), "=f"(d[62]), "=f"(d[63])
    : "r"(alo), "r"(blo));
}
__device__ __forceinline__ void wg_qk_acc(float (&d)[64], uint32_t alo, uint32_t blo) {
  asm volatile("{\n.reg .pred p;\n.reg .b64 da, db;\nmov.b64 da, {%64, 0x40000040};\nmov.b64 db, {%65, 0x40000040};\nsetp.eq.b32 p, 0, 0;\n"
    "wgmma.mma_async.sync.aligned.m64n128k16.f32.bf16.bf16 {"
    "%0, %1, %2, %3, %4, %5, %6, %7, %8, %9, %10, %11, %12, %13, %14, %15, %16, %17, %18, %19, %20, %21, %22, %23, %24, %25, %26, %27, %28, %29, %30, %31, "
    "%32, %33, %34, %35, %36, %37, %38, %39, %40, %41, %42, %43, %44, %45, %46, %47, %48, %49, %50, %51, %52, %53, %54, %55, %56, %57, %58, %59, %60, %61, %62, %63}, "
    "da, db, p, 1, 1, 0, 0;\n}\n"
    : "+f"(d[0]), "+f"(d[1]), "+f"(d[2]), "+f"(d[3]), "+f"(d[4]), "+f"(d[5]), "+f"(d[6]), "+f"(d[7]), "+f"(d[8]), "+f"(d[9]), "+f"(d[10]), "+f"(d[11]), "+f"(d[12]), "+f"(d[13]), "+f"(d[14]), "+f"(d[15]),
      "+f"(d[16]), "+f"(d[17]), "+f"(d[18]), "+f"(d[19]), "+f"(d[20]), "+f"(d[21]), "+f"(d[22]), "+f"(d[23]), "+f"(d[24]), "+f"(d[25]), "+f"(d[26]), "+f"(d[27]), "+f"(d[28]), "+f"(d[29]), "+f"(d[30]), "+f"(d[31]),
      "+f"(d[32]), "+f"(d[33]), "+f"(d[34]), "+f"(d[35]), "+f"(d[36]), "+f"(d[37]), "+f"(d[38]), "+f"(d[39]), "+f"(d[40]), "+f"(d[41]), "+f"(d[42]), "+f"(d[43]), "+f"(d[44]), "+f"(d[45]), "+f"(d[46]), "+f"(d[47]),
      "+f"(d[48]), "+f"(d[49]), "+f"(d[50]), "+f"(d[51]), "+f"(d[52]), "+f"(d[53]), "+f"(d[54]), "+f"(d[55]), "+f"(d[56]), "+f"(d[57]), "+f"(d[58]), "+f"(d[59]), "+f"(d[60]), "+f"(d[61]), "+f"(d[62]), "+f"(d[63])
    : "r"(alo), "r"(blo));
}
__device__ __forceinline__ void wg_qk64_init(float (&d)[64], uint32_t alo, uint32_t blo) {
  asm volatile("{\n.reg .pred p;\n.reg .b64 da, db;\nmov.b64 da, {%32, 0x40000040};\nmov.b64 db, {%33, 0x40000040};\nsetp.ne.b32 p, 0, 0;\n"
    "wgmma.mma_async.sync.aligned.m64n64k16.f32.bf16.bf16 {"
    "%0, %1, %2, %3, %4, %5, %6, %7, %8, %9, %10, %11, %12, %13, %14, %15, %16, %17, %18, %19, %20, %21, %22, %23, %24, %25, %26, %27, %28, %29, %30, %31}, "
    "da, db, p, 1, 1, 0, 0;\n}\n"
    : "=f"(d[0]), "=f"(d[1]), "=f"(d[2]), "=f"(d[3]), "=f"(d[4]), "=f"(d[5]), "=f"(d[6]), "=f"(d[7]), "=f"(d[8]), "=f"(d[9]), "=f"(d[10]), "=f"(d[11]), "=f"(d[12]), "=f"(d[13]), "=f"(d[14]), "=f"(d[15]),
      "=f"(d[16]), "=f"(d[17]), "=f"(d[18]), "=f"(d[19]), "=f"(d[20]), "=f"(d[21]), "=f"(d[22]), "=f"(d[23]), "=f"(d[24]), "=f"(d[25]), "=f"(d[26]), "=f"(d[27]), "=f"(d[28]), "=f"(d[29]), "=f"(d[30]), "=f"(d[31])
    : "r"(alo), "r"(blo));
}
__device__ __forceinline__ void wg_qk64_acc(float (&d)[64], uint32_t alo, uint32_t blo) {
  asm volatile("{\n.reg .pred p;\n.reg .b64 da, db;\nmov.b64 da, {%32, 0x40000040};\nmov.b64 db, {%33, 0x40000040};\nsetp.eq.b32 p, 0, 0;\n"
    "wgmma.mma_async.sync.aligned.m64n64k16.f32.bf16.bf16 {"
    "%0, %1, %2, %3, %4, %5, %6, %7, %8, %9, %10, %11, %12, %13, %14, %15, %16, %17, %18, %19, %20, %21, %22, %23, %24, %25, %26, %27, %28, %29, %30, %31}, "
    "da, db, p, 1, 1, 0, 0;\n}\n"
    : "+f"(d[0]), "+f"(d[1]), "+f"(d[2]), "+f"(d[3]), "+f"(d[4]), "+f"(d[5]), "+f"(d[6]), "+f"(d[7]), "+f"(d[8]), "+f"(d[9]), "+f"(d[10]), "+f"(d[11]), "+f"(d[12]), "+f"(d[13]), "+f"(d[14]), "+f"(d[15]),
      "+f"(d[16]), "+f"(d[17]), "+f"(d[18]), "+f"(d[19]), "+f"(d[20]), "+f"(d[21]), "+f"(d[22]), "+f"(d[23]), "+f"(d[24]), "+f"(d[25]), "+f"(d[26]), "+f"(d[27]), "+f"(d[28]), "+f"(d[29]), "+f"(d[30]), "+f"(d[31])
    : "r"(alo), "r"(blo));
}
__device__ __forceinline__ void wg_pv_init(float (&d)[64], const uint32_t* a, uint32_t blo) {
  asm volatile("{\n.reg .pred p;\n.reg .b64 da, db;\nmov.b64 db, {%68, 0x40000040};\nsetp.ne.b32 p, 0, 0;\n"
    "wgmma.mma_async.sync.aligned.m64n128k16.f32.bf16.bf16 {"
    "%0, %1, %2, %3, %4, %5, %6, %7, %8, %9, %10, %11, %12, %13, %14, %15, %16, %17, %18, %19, %20, %21, %22, %23, %24, %25, %26, %27, %28, %29, %30, %31, "
    "%32, %33, %34, %35, %36, %37, %38, %39, %40, %41, %42, %43, %44, %45, %46, %47, %48, %49, %50, %51, %52, %53, %54, %55, %56, %57, %58, %59, %60, %61, %62, %63}, "
    "{%64, %65, %66, %67}, db, p, 1, 1, 1;\n}\n"
    : "=f"(d[0]), "=f"(d[1]), "=f"(d[2]), "=f"(d[3]), "=f"(d[4]), "=f"(d[5]), "=f"(d[6]), "=f"(d[7]), "=f"(d[8]), "=f"(d[9]), "=f"(d[10]), "=f"(d[11]), "=f"(d[12]), "=f"(d[13]), "=f"(d[14]), "=f"(d[15]),
      "=f"(d[16]), "=f"(d[17]), "=f"(d[18]), "=f"(d[19]), "=f"(d[20]), "=f"(d[21]), "=f"(d[22]), "=f"(d[23]), "=f"(d[24]), "=f"(d[25]), "=f"(d[26]), "=f"(d[27]), "=f"(d[28]), "=f"(d[29]), "=f"(d[30]), "=f"(d[31]),
      "=f"(d[32]), "=f"(d[33]), "=f"(d[34]), "=f"(d[35]), "=f"(d[36]), "=f"(d[37]), "=f"(d[38]), "=f"(d[39]), "=f"(d[40]), "=f"(d[41]), "=f"(d[42]), "=f"(d[43]), "=f"(d[44]), "=f"(d[45]), "=f"(d[46]), "=f"(d[47]),
      "=f"(d[48]), "=f"(d[49]), "=f"(d[50]), "=f"(d[51]), "=f"(d[52]), "=f"(d[53]), "=f"(d[54]), "=f"(d[55]), "=f"(d[56]), "=f"(d[57]), "=f"(d[58]), "=f"(d[59]), "=f"(d[60]), "=f"(d[61]), "=f"(d[62]), "=f"(d[63])
    : "r"(a[0]), "r"(a[1]), "r"(a[2]), "r"(a[3]), "r"(blo));
}
__device__ __forceinline__ void wg_pv_acc(float (&d)[64], const uint32_t* a, uint32_t blo) {
  asm volatile("{\n.reg .pred p;\n.reg .b64 da, db;\nmov.b64 db, {%68, 0x40000040};\nsetp.eq.b32 p, 0, 0;\n"
    "wgmma.mma_async.sync.aligned.m64n128k16.f32.bf16.bf16 {"
    "%0, %1, %2, %3, %4, %5, %6, %7, %8, %9, %10, %11, %12, %13, %14, %15, %16, %17, %18, %19, %20, %21, %22, %23, %24, %25, %26, %27, %28, %29, %30, %31, "
    "%32, %33, %34, %35, %36, %37, %38, %39, %40, %41, %42, %43, %44, %45, %46, %47, %48, %49, %50, %51, %52, %53, %54, %55, %56, %57, %58, %59, %60, %61, %62, %63}, "
    "{%64, %65, %66, %67}, db, p, 1, 1, 1;\n}\n"
    : "+f"(d[0]), "+f"(d[1]), "+f"(d[2]), "+f"(d[3]), "+f"(d[4]), "+f"(d[5]), "+f"(d[6]), "+f"(d[7]), "+f"(d[8]), "+f"(d[9]), "+f"(d[10]), "+f"(d[11]), "+f"(d[12]), "+f"(d[13]), "+f"(d[14]), "+f"(d[15]),
      "+f"(d[16]), "+f"(d[17]), "+f"(d[18]), "+f"(d[19]), "+f"(d[20]), "+f"(d[21]), "+f"(d[22]), "+f"(d[23]), "+f"(d[24]), "+f"(d[25]), "+f"(d[26]), "+f"(d[27]), "+f"(d[28]), "+f"(d[29]), "+f"(d[30]), "+f"(d[31]),
      "+f"(d[32]), "+f"(d[33]), "+f"(d[34]), "+f"(d[35]), "+f"(d[36]), "+f"(d[37]), "+f"(d[38]), "+f"(d[39]), "+f"(d[40]), "+f"(d[41]), "+f"(d[42]), "+f"(d[43]), "+f"(d[44]), "+f"(d[45]), "+f"(d[46]), "+f"(d[47]),
      "+f"(d[48]), "+f"(d[49]), "+f"(d[50]), "+f"(d[51]), "+f"(d[52]), "+f"(d[53]), "+f"(d[54]), "+f"(d[55]), "+f"(d[56]), "+f"(d[57]), "+f"(d[58]), "+f"(d[59]), "+f"(d[60]), "+f"(d[61]), "+f"(d[62]), "+f"(d[63])
    : "r"(a[0]), "r"(a[1]), "r"(a[2]), "r"(a[3]), "r"(blo));
}

struct Cons {
  uint32_t sb;
  uint32_t rel;
  uint32_t p0, p1;
  uint32_t lead, round, fpar;
};

template <uint32_t OFF, uint32_t GROUP> __device__ __forceinline__ void tile_write(const uint32_t (&pk)[32], uint32_t base) {
  const uint32_t lane = threadIdx.x & 31, wq = (threadIdx.x >> 5) & 3;
  const uint32_t a = base + (wq * 16 + (lane & 15)) * 128 + (((lane >> 4) ^ (lane & 7)) << 4);
#define TW(j) stmatrix_x4<OFF + (j >> 2) * GROUP>(a ^ ((j & 3) * 32), pk[4 * j + 0], pk[4 * j + 1], pk[4 * j + 2], pk[4 * j + 3])
  TW(0); TW(1); TW(2); TW(3); TW(4); TW(5); TW(6); TW(7);
#undef TW
}
template <uint32_t OFF, uint32_t GROUP, int A0> __device__ __forceinline__ void tile_pack_write(const float (&acc)[128], uint32_t (&pk)[32], uint32_t base) {
  const uint32_t lane = threadIdx.x & 31, wq = (threadIdx.x >> 5) & 3;
  const uint32_t a = base + (wq * 16 + (lane & 15)) * 128 + (((lane >> 4) ^ (lane & 7)) << 4);
#define TW(j) \
  pk[4 * j + 0] = v_pack(acc[A0 + 8 * j + 0], acc[A0 + 8 * j + 1]); pk[4 * j + 1] = v_pack(acc[A0 + 8 * j + 2], acc[A0 + 8 * j + 3]); \
  pk[4 * j + 2] = v_pack(acc[A0 + 8 * j + 4], acc[A0 + 8 * j + 5]); pk[4 * j + 3] = v_pack(acc[A0 + 8 * j + 6], acc[A0 + 8 * j + 7]); \
  stmatrix_x4<OFF + (j >> 2) * GROUP>(a ^ ((j & 3) * 32), pk[4 * j + 0], pk[4 * j + 1], pk[4 * j + 2], pk[4 * j + 3])
  TW(0); TW(1); TW(2); TW(3); TW(4); TW(5); TW(6); TW(7);
#undef TW
}
__device__ __forceinline__ void stage_write(const uint32_t (&pk)[32], int w, const Cons& cs) {
  mbar_wait<BAR(B_STGE)>(cs.sb + w * 8, (cs.round & 1) ^ 1);
  tile_write<OFF_STG, 8192>(pk, cs.sb + w * 16384);
}
__device__ __forceinline__ void stage_publish(int w, Cons& cs) {
  fence_async_smem();
  __syncwarp();
  mbar_arrive_if<BAR(B_STGF)>(cs.sb + w * 8, (threadIdx.x & 31) == 0);
  cs.round++;
}

template <int ST, bool INIT, int NA> __device__ __forceinline__ void g_issue(float (&acc)[NA], uint32_t wa) {
  constexpr uint32_t A = dlo(OFF_A + ST * 16384, 16), B = dlo(OFF_B + ST * 32768, NA == 128 ? 8192 : 4096);
  wg_fence();
  if (INIT) wg_gemm_init(acc, A + wa, B); else wg_gemm_acc(acc, A + wa, B);
#pragma unroll
  for (int kk = 1; kk < 4; kk++) wg_gemm_acc(acc, A + wa + kk * 2, B + (NA == 128 ? kk * 128 : (kk >> 1) * 768 + (kk & 1) * 128));
  wg_commit();
}
template <int NA, class F>
__device__ __forceinline__ uint32_t gemm_tile(float (&acc)[NA], int nk4, int idx, int w, Cons& cs, uint32_t pend, const uint32_t (&pkA)[32], const uint32_t (&pkB)[32], F&& before_end) {
  const uint32_t wa = w * 512, sb = cs.sb, rel = cs.rel;
  constexpr int SA = NA == 128 ? STGA : STGAL, SBB = NA == 128 ? STGB : STGBL;
#define HOOK(n) \
  if (n == LPUBP && (pend & 8)) stage_publish(w, cs); \
  if (LHS && n == 0 && (pend & 16) && w == 0) bar_sync(5, 256); \
  if (n == SA && (pend & 1)) stage_write(pkA, w, cs); \
  if (n == SA + PUBD && (pend & 1)) { stage_publish(w, cs); pend &= 6; } \
  if (n == SBB && (pend & 2)) { stage_write(pkB, w, cs); pend = 4; } \
  if (n == SBB + PUBD && (pend & 4)) { stage_publish(w, cs); pend = 0; }
  mbar_wait<BAR(B_FULL + 0)>(sb, cs.p0);
  g_issue<0, true>(acc, wa);
  HOOK(0);
  mbar_wait<BAR(B_FULL + 1)>(sb, cs.p1);
  g_issue<1, false>(acc, wa);
  HOOK(2);
  wg_wait<1>(); T4K();
  mbar_arrive_cl<BAR(B_EMPTY + 0)>(rel);
  HOOK(3);
  mbar_wait<BAR(B_FULL + 2)>(sb, cs.p0);
  g_issue<2, false>(acc, wa);
  HOOK(4);
  wg_wait<1>(); T4K();
  mbar_arrive_cl<BAR(B_EMPTY + 1)>(rel);
  HOOK(5);
  mbar_wait<BAR(B_FULL + 3)>(sb, cs.p1);
  g_issue<3, false>(acc, wa);
  HOOK(6);
  const uint32_t ncode = item(sb, idx + 1);
  wg_wait<1>(); T4K();
  mbar_arrive_cl<BAR(B_EMPTY + 2)>(rel);
  HOOK(7);
  cs.p0 ^= 1; cs.p1 ^= 1;
  const bool final_tile = (ncode >> 9) == K_END;
  constexpr int LD = NA == 128 ? LEADN : LEADL;
#pragma unroll 1
  for (int q = 1; q < nk4; q++) {
    const bool tail = q == nk4 - 1;
    mbar_wait<BAR(B_FULL + 0)>(sb, cs.p0);
    g_issue<0, false>(acc, wa);
    HOOK(8);
    wg_wait<1>(); T4K();
    mbar_arrive_cl<BAR(B_EMPTY + 3)>(rel);
    HOOK(9);
    mbar_wait<BAR(B_FULL + 1)>(sb, cs.p1);
    uint32_t rel0 = rel;
    if (LEADF == 3 && NA == 128 && final_tile && tail && w == 1) {
      wg_wait<0>();
      mbar_arrive_cl<BAR(B_EMPTY + 0)>(rel);
      rel0 = 0;
      mbar_wait<BAR(B_LEAD)>(sb, cs.lead);
    }
    g_issue<1, false>(acc, wa);
    HOOK(10);
    wg_wait<1>(); T4K();
    mbar_arrive_cl<BAR(B_EMPTY + 0)>(rel0);
    HOOK(11);
    mbar_wait<BAR(B_FULL + 2)>(sb, cs.p0);
    uint32_t rel1 = rel;
    if (LD == 2 && tail && w == 1 && !(LEADF == 3 && NA == 128 && final_tile)) {
      if (EREL) { wg_wait<0>(); mbar_arrive_cl<BAR(B_EMPTY + 1)>(rel); rel1 = 0; }
      mbar_wait<BAR(B_LEAD)>(sb, cs.lead);
    }
    g_issue<2, false>(acc, wa);
    HOOK(12);
    wg_wait<1>(); T4K();
    mbar_arrive_cl<BAR(B_EMPTY + 1)>(rel1);
    HOOK(13);
    mbar_wait<BAR(B_FULL + 3)>(sb, cs.p1);
    if (LD == 1 && tail && w == 1) mbar_wait<BAR(B_LEAD)>(sb, cs.lead);
    g_issue<3, false>(acc, wa);
    mbar_arrive_if<BAR(B_LEAD)>(sb, tail && threadIdx.x == 128);
    HOOK(14);
    wg_wait<1>(); T4K();
    mbar_arrive_cl<BAR(B_EMPTY + 2)>(rel);
    cs.p0 ^= 1; cs.p1 ^= 1;
  }
#undef HOOK
  cs.lead ^= 1;
  before_end();
  wg_wait<0>();
  fence_regs(acc);
  T4Q(__float_as_uint(acc[0]));
  mbar_arrive_cl<BAR(B_EMPTY + 3)>(rel);
  return ncode;
}

__device__ __forceinline__ void local_probs(bool first, const float (&S)[3][4], uint32_t (&pb)[4]) {
  const int lane = threadIdx.x & 31, g = lane >> 2, t = lane & 3;
  const bool c0 = 2 * t > g, c1 = 2 * t + 1 > g;
  float x0 = c0 ? S[0][0] : S[1][0], x1 = c1 ? S[0][1] : S[1][1], y0 = c0 ? S[1][2] : S[2][2], y1 = c1 ? S[1][3] : S[2][3];
  if (first && c0) x0 = -INFINITY;
  if (first && c1) x1 = -INFINITY;
  float m0 = fmaxf(x0, x1), m1 = fmaxf(y0, y1);
  if (LSH & 1) {
    m0 = fmaxf(fmaxf(m0, __shfl_xor_sync(0xffffffffu, m0, 1)), fmaxf(__shfl_xor_sync(0xffffffffu, m0, 2), __shfl_xor_sync(0xffffffffu, m0, 3)));
    m1 = fmaxf(fmaxf(m1, __shfl_xor_sync(0xffffffffu, m1, 1)), fmaxf(__shfl_xor_sync(0xffffffffu, m1, 2), __shfl_xor_sync(0xffffffffu, m1, 3)));
  } else {
    m0 = fmaxf(m0, __shfl_xor_sync(0xffffffffu, m0, 1)); m1 = fmaxf(m1, __shfl_xor_sync(0xffffffffu, m1, 1));
    m0 = fmaxf(m0, __shfl_xor_sync(0xffffffffu, m0, 2)); m1 = fmaxf(m1, __shfl_xor_sync(0xffffffffu, m1, 2));
  }
  constexpr float C = 0.17677669529663687f * 1.4426950408889634f;
  const float b0 = -m0 * C, b1 = -m1 * C;
  x0 = ex2(fmaf(x0, C, b0)); x1 = ex2(fmaf(x1, C, b0)); y0 = ex2(fmaf(y0, C, b1)); y1 = ex2(fmaf(y1, C, b1));
  auto qs = [](float v) { return (LSH & 2) ? (v + __shfl_xor_sync(0xffffffffu, v, 1)) + (__shfl_xor_sync(0xffffffffu, v, 2) + __shfl_xor_sync(0xffffffffu, v, 3)) : quad_sum(v); };
  const float l0 = rcp(qs(x0 + x1)), l1 = rcp(qs(y0 + y1));
  const uint32_t px = pack_bf16(x0 * l0, x1 * l0), py = pack_bf16(y0 * l1, y1 * l1);
  const uint32_t m = (c0 ? 0xffffu : 0u) | (c1 ? 0xffff0000u : 0u);
  pb[0] = px & m; pb[1] = px & ~m; pb[2] = py & m; pb[3] = py & ~m;
}
struct Loc { uint32_t xa, ra, oa; };
__device__ __forceinline__ Loc local_prepare(uint32_t code, int w, Cons& cs) {
  const uint32_t lane = threadIdx.x & 31, wq = (threadIdx.x >> 5) & 3;
  const bool has_halo = (code & 15) != 0;
  Loc l;
  l.xa = cs.sb + OFF_STG + 8192 + w * 16384 + wq * 2048 + lane * 8;
  l.ra = l.xa - (wq == 0 ? 16384 - 3 * 2048 : 2048);
  if (w + wq == 0) l.ra = has_halo ? cs.sb + OFF_HALO + lane * 8 : l.xa;
  l.oa = cs.sb + w * 16384 + (wq * 16 + (lane & 7)) * 128 + (((lane >> 3) ^ (lane & 7)) << 4);
  asm volatile("{\n.reg .pred p;\nsetp.eq.u32 p, %0, 0;\n@p st.shared.u32 [%1], %2;\n}\n" ::"r"(l.xa), "r"(l.ra), "r"(l.oa) : "memory");
  mbar_wait<BAR(B_STGE)>(cs.sb + w * 8, (cs.round & 1) ^ 1);
  if (has_halo && w == 0) mbar_wait<BAR(B_HFULL)>(cs.sb, cs.fpar >> 1);
  cs.fpar ^= has_halo ? 2 : 0;
  return l;
}
__device__ __forceinline__ void local_epilogue(const float (&acc)[96], uint32_t code, int w, Cons& cs, const Loc& l) {
  const uint32_t cw = (threadIdx.x >> 5) - 4;
  const bool has_halo = (code & 15) != 0;
  uint32_t kf[3][8], vt[3][8];
#pragma unroll
  for (int j = 0; j < 8; j++) { kf[2][j] = pack_bf16(acc[32 + 4 * j + 2], acc[32 + 4 * j + 3]); vt[2][j] = transpose8(pack_bf16(acc[64 + 4 * j + 2], acc[64 + 4 * j + 3])); }
  sts64<0>(l.xa, &kf[2][0]); sts64<256>(l.xa, &kf[2][2]); sts64<512>(l.xa, &kf[2][4]); sts64<768>(l.xa, &kf[2][6]);
  sts64<1024>(l.xa, &vt[2][0]); sts64<1280>(l.xa, &vt[2][2]); sts64<1536>(l.xa, &vt[2][4]); sts64<1792>(l.xa, &vt[2][6]);
  if (cw == 3) bar_arrive(4, 160);
  uint32_t q[8][2];
#pragma unroll
  for (int j = 0; j < 8; j++) {
    q[j][0] = pack_bf16(acc[4 * j], acc[4 * j + 1]); q[j][1] = pack_bf16(acc[4 * j + 2], acc[4 * j + 3]);
    kf[1][j] = pack_bf16(acc[32 + 4 * j], acc[32 + 4 * j + 1]);
    if (!LVL) vt[1][j] = transpose8(pack_bf16(acc[64 + 4 * j], acc[64 + 4 * j + 1]));
  }
  bar_sync(3 + w, 128 + 32 * w);
  uint32_t z[4];
  lds128<OFF_FILLS + 16>(z, cs.sb);
  lds64<0>(&kf[0][0], l.ra); lds64<512>(&kf[0][4], l.ra); lds64<256>(&kf[0][2], l.ra); lds64<768>(&kf[0][6], l.ra);
  lds64<1024>(&vt[0][0], l.ra); lds64<1280>(&vt[0][2], l.ra); lds64<1536>(&vt[0][4], l.ra); lds64<1792>(&vt[0][6], l.ra);
  float S[2][3][4];
#pragma unroll
  for (int n = 2; n >= 0; n--)
#pragma unroll
    for (int u = 0; u < 2; u++) mma16816z(S[u][n], q[4 * u][0], q[4 * u][1], q[4 * u + 1][0], q[4 * u + 1][1], kf[n][4 * u], kf[n][4 * u + 1], z);
#pragma unroll
  for (int n = 2; n >= 0; n--)
#pragma unroll
    for (int u = 0; u < 2; u++) mma16816(S[u][n], q[4 * u + 2][0], q[4 * u + 2][1], q[4 * u + 3][0], q[4 * u + 3][1], kf[n][4 * u + 2], kf[n][4 * u + 3]);
  if (LVL) {
#pragma unroll
    for (int j = 0; j < 8; j++) vt[1][j] = transpose8(pack_bf16(acc[64 + 4 * j], acc[64 + 4 * j + 1]));
  }
  uint32_t pb[2][4];
#pragma unroll
  for (int u = 0; u < 2; u++) local_probs(cw == 0 && !has_halo, S[u], pb[u]);
  const uint32_t oa = l.oa;
#pragma unroll
  for (int u = 0; u < 2; u++)
#pragma unroll
    for (int hf = 0; hf < 2; hf++) {
      float O[2][4];
#pragma unroll
      for (int mt = 0; mt < 2; mt++) {
        O[mt][0] = O[mt][1] = O[mt][2] = O[mt][3] = 0.f;
        mma16816(O[mt], vt[hf][4 * u + 2 * mt], vt[hf][4 * u + 2 * mt + 1], vt[hf + 1][4 * u + 2 * mt], vt[hf + 1][4 * u + 2 * mt + 1], pb[u][2 * hf], pb[u][2 * hf + 1]);
      }
      const uint32_t o0 = pack_bf16(O[0][0], O[0][1]), o1 = pack_bf16(O[0][2], O[0][3]), o2 = pack_bf16(O[1][0], O[1][1]), o3 = pack_bf16(O[1][2], O[1][3]);
      if (hf == 0) stmatrix_x4_trans<OFF_STG>(oa ^ (u * 64), o0, o1, o2, o3); else stmatrix_x4_trans<OFF_STG + 1024>(oa ^ (u * 64), o0, o1, o2, o3);
    }
  mbar_arrive_if<BAR(B_HEMPTY)>(cs.sb, has_halo && threadIdx.x == 128);
}

constexpr float SCALE_LOG2 = 0.08838834764831845f * 1.4426950408889634f;
#define SUM_LO 8.673617379884035e-19f
#define SUM_HI 1152921504606846976.f
template <int J0> __device__ __forceinline__ void causal_mask(float (&S)[64], int r) {
#pragma unroll
  for (int j = 0; j < 8; j++) {
    if (8 * j > r) S[4 * (J0 + j) + 0] = -INFINITY;
    if (8 * j + 1 > r) S[4 * (J0 + j) + 1] = -INFINITY;
    if (8 * j - 8 > r) S[4 * (J0 + j) + 2] = -INFINITY;
    if (8 * j - 7 > r) S[4 * (J0 + j) + 3] = -INFINITY;
  }
}
__device__ __forceinline__ float v_ex2(float x) { float y; asm volatile("ex2.approx.ftz.f32 %0, %1;" : "=f"(y) : "f"(x)); return y; }
__device__ __forceinline__ float v_add(float a, float b) { float y; asm volatile("add.f32 %0, %1, %2;" : "=f"(y) : "f"(a), "f"(b)); return y; }
__device__ __forceinline__ float v_mul(float a, float b) { float y; asm volatile("mul.f32 %0, %1, %2;" : "=f"(y) : "f"(a), "f"(b)); return y; }
template <int MJ> __device__ __forceinline__ float exp_el(float x, int j, int e, int r) {
  float p = v_ex2(x);
  if (j >= MJ) asm volatile("{\n.reg .pred q;\nsetp.lt.s32 q, %1, %2;\n@q mov.b32 %0, 0f00000000;\n}\n" : "+f"(p) : "r"(r), "r"(8 * (j - MJ) + (e & 1) - 4 * (e & 2)));
  return p;
}
template <int J0, int J1, int MJ = 16> __device__ __forceinline__ void exp_inplace(float (&S)[64], float& l0, float& l1, int r = 0) {
#pragma unroll
  for (int j = J0; j < J1; j++) {
#pragma unroll
    for (int e = 0; e < 4; e++) S[4 * j + e] = exp_el<MJ>(S[4 * j + e], j, e, r);
    l0 = v_add(l0, S[4 * j + 0]); l1 = v_add(l1, S[4 * j + 2]); l0 = v_add(l0, S[4 * j + 1]); l1 = v_add(l1, S[4 * j + 3]);
  }
}
template <int JS, int MJ, bool OUT>
__device__ __forceinline__ void exp_pack(float (&S)[64], uint32_t (&P)[32], float& l0, float& l1, int r, const float (&O)[64], float a0, float a1, uint32_t (&pk)[32]) {
#pragma unroll
  for (int j = JS; j < 16; j++) {
    const float p0 = exp_el<MJ>(S[4 * j + 0], j, 0, r), p1 = exp_el<MJ>(S[4 * j + 1], j, 1, r), p2 = exp_el<MJ>(S[4 * j + 2], j, 2, r), p3 = exp_el<MJ>(S[4 * j + 3], j, 3, r);
#pragma unroll
    for (int k = (j - JS) * JS / (16 - JS); k < (j + 1 - JS) * JS / (16 - JS); k++) { P[2 * k] = v_pack(S[4 * k + 0], S[4 * k + 1]); P[2 * k + 1] = v_pack(S[4 * k + 2], S[4 * k + 3]); }
    if (OUT) {
#pragma unroll
      for (int k = (j - JS) * 16 / (16 - JS); k < (j + 1 - JS) * 16 / (16 - JS); k++) {
        pk[2 * k] = v_pack(v_mul(O[4 * k + 0], a0), v_mul(O[4 * k + 1], a0)); pk[2 * k + 1] = v_pack(v_mul(O[4 * k + 2], a1), v_mul(O[4 * k + 3], a1));
      }
    }
    l0 = v_add(l0, p0); l1 = v_add(l1, p2); l0 = v_add(l0, p1); l1 = v_add(l1, p3);
    P[2 * j] = v_pack(p0, p1); P[2 * j + 1] = v_pack(p2, p3);
  }
}
__device__ __forceinline__ void pin_after(float a, float b) {
  asm volatile("{\n.reg .pred p;\nsetp.eq.u32 p, %0, 0xffffffff;\n@p st.shared.b32 [%1], %1;\n}\n" ::"r"(__float_as_uint(a)), "r"(__float_as_uint(b)) : "memory");
}
template <bool HALF> __device__ __forceinline__ void issue_qk(float (&S)[64], uint32_t qlo, uint32_t klo) {
  wg_fence();
  if (HALF) wg_qk64_init(S, qlo, klo); else wg_qk_init(S, qlo, klo);
#pragma unroll
  for (int kk = 1; kk < 8; kk++) {
    const uint32_t off = ((kk >> 2) * 16384 + (kk & 3) * 32) >> 4;
    if (HALF) wg_qk64_acc(S, qlo + off, klo + off); else wg_qk_acc(S, qlo + off, klo + off);
  }
  wg_commit();
}
template <int NK, int ACC> __device__ __forceinline__ void issue_pv(float (&O)[64], const uint32_t (&P)[32], uint32_t vlo) {
  wg_fence();
  if (ACC) wg_pv_acc(O, &P[0], vlo); else wg_pv_init(O, &P[0], vlo);
#pragma unroll
  for (int kk = 1; kk < NK; kk++) wg_pv_acc(O, &P[4 * kk], vlo + kk * 128);
  wg_commit();
}
__device__ __forceinline__ uint32_t row_norm(float l0, float l1, float& a0, float& a1) {
  const float q0 = quad_sum(l0), q1 = quad_sum(l1);
  a0 = rcp(q0); a1 = rcp(q1);
  return __reduce_or_sync(0xffffffffu, (q0 >= SUM_LO && q0 <= SUM_HI && q1 >= SUM_LO && q1 <= SUM_HI) ? 0u : 1u);
}
__device__ __forceinline__ void slow_item(float (&O)[64], float& a0, float& a1, int head, int tile, uint32_t qbase, int w) {
  const int lane = threadIdx.x & 31, g = lane >> 2, t = lane & 3;
  const int rw = w * 64 + (int)__reduce_or_sync(0xffffffffu, (threadIdx.x >> 1) & 48);
  const int row0 = tile * 128 + rw;
  const uint32_t qa_ = qbase + (rw + g) * 128 + ((t ^ g) << 4);
  const __nv_bfloat16* kp = g_kv + ((size_t)head * SEQ + g) * 256 + 8 * t;
  const __nv_bfloat16* vp = g_kv + ((size_t)head * SEQ + 2 * t) * 256 + 128 + g;
  float m0 = -INFINITY, m1 = -INFINITY, l0 = 0.f, l1 = 0.f;
#pragma unroll
  for (int i = 0; i < 64; i++) O[i] = 0.f;
#pragma unroll 1
  for (int key0 = 0; key0 < row0 + 16; key0 += 16) {
    float c[2][4] = {{0.f, 0.f, 0.f, 0.f}, {0.f, 0.f, 0.f, 0.f}};
#pragma unroll 1
    for (int cc = 0; cc < 4; cc++) {
      uint32_t qa[4], qb[4];
      const uint32_t a = (qa_ ^ ((cc & 1) * 64)) + (cc >> 1) * 16384;
      lds128<0>(qa, a); lds128<1024>(qb, a);
#pragma unroll
      for (int n = 0; n < 2; n++) {
        const uint4 kf = ldg128(kp + (size_t)(key0 + 8 * n) * 256 + cc * 32);
        mma16816(c[n], qa[0], qb[0], qa[1], qb[1], kf.x, kf.y);
        mma16816(c[n], qa[2], qb[2], qa[3], qb[3], kf.z, kf.w);
      }
    }
#pragma unroll
    for (int n = 0; n < 2; n++)
#pragma unroll
      for (int e = 0; e < 4; e++)
        if (key0 + 8 * n + 2 * t + (e & 1) > row0 + g + (e >> 1) * 8) c[n][e] = -INFINITY;
    float x0 = fmaxf(fmaxf(c[0][0], c[0][1]), fmaxf(c[1][0], c[1][1])), x1 = fmaxf(fmaxf(c[0][2], c[0][3]), fmaxf(c[1][2], c[1][3]));
    x0 = fmaxf(x0, __shfl_xor_sync(0xffffffffu, x0, 1)); x1 = fmaxf(x1, __shfl_xor_sync(0xffffffffu, x1, 1));
    x0 = fmaxf(x0, __shfl_xor_sync(0xffffffffu, x0, 2)); x1 = fmaxf(x1, __shfl_xor_sync(0xffffffffu, x1, 2));
    const float n0 = fmaxf(m0, x0), n1 = fmaxf(m1, x1);
    const float r0 = ex2(m0 - n0), r1 = ex2(m1 - n1);
    m0 = n0; m1 = n1;
#pragma unroll
    for (int n = 0; n < 2; n++) { c[n][0] = ex2(c[n][0] - n0); c[n][1] = ex2(c[n][1] - n0); c[n][2] = ex2(c[n][2] - n1); c[n][3] = ex2(c[n][3] - n1); }
    l0 = l0 * r0 + ((c[0][0] + c[0][1]) + (c[1][0] + c[1][1]));
    l1 = l1 * r1 + ((c[0][2] + c[0][3]) + (c[1][2] + c[1][3]));
    const uint32_t p0 = pack_bf16(c[0][0], c[0][1]), p1 = pack_bf16(c[0][2], c[0][3]), p2 = pack_bf16(c[1][0], c[1][1]), p3 = pack_bf16(c[1][2], c[1][3]);
#pragma unroll
    for (int j = 0; j < 16; j++) {
      const __nv_bfloat16* v = vp + (size_t)key0 * 256 + j * 8;
      const uint32_t b0 = ldg16(v) | (ldg16(v + 256) << 16), b1 = ldg16(v + 8 * 256) | (ldg16(v + 9 * 256) << 16);
      float o[4] = {O[4 * j] * r0, O[4 * j + 1] * r0, O[4 * j + 2] * r1, O[4 * j + 3] * r1};
      mma16816(o, p0, p1, p2, p3, b0, b1);
      O[4 * j] = o[0]; O[4 * j + 1] = o[1]; O[4 * j + 2] = o[2]; O[4 * j + 3] = o[3];
    }
  }
  a0 = rcp(quad_sum(l0)); a1 = rcp(quad_sum(l1));
}
__device__ __forceinline__ void att_output(const float (&O)[64], float a0, float a1, uint32_t (&pk)[32]) {
#pragma unroll
  for (int k = 0; k < 16; k++) { pk[2 * k] = v_pack(v_mul(O[4 * k + 0], a0), v_mul(O[4 * k + 1], a0)); pk[2 * k + 1] = v_pack(v_mul(O[4 * k + 2], a1), v_mul(O[4 * k + 3], a1)); }
}
template <int J1> __device__ __forceinline__ void exp_stage(float (&S)[64], float& l0, float& l1, const uint32_t (&P)[32], int w, const Cons& cs, uint32_t on) {
  const uint32_t lane = threadIdx.x & 31, wq = (threadIdx.x >> 5) & 3;
  const uint32_t a = cs.sb + w * 16384 + (wq * 16 + (lane & 15)) * 128 + (((lane >> 4) ^ (lane & 7)) << 4);
#define ES(c) \
  exp_inplace<c * J1 / 8, (c + 1) * J1 / 8>(S, l0, l1); \
  stmatrix_x4_after<OFF_STG + (c >> 2) * 8192>(a ^ ((c & 3) * 32), P[4 * c + 0], P[4 * c + 1], P[4 * c + 2], P[4 * c + 3], (c & 1) ? l1 : l0, on)
  ES(0); ES(1); ES(2); ES(3); ES(4); ES(5); ES(6); ES(7);
#undef ES
}
struct Att { uint32_t qd, kd, vd, c8, cb, xc, xp, pub; };
__device__ __forceinline__ void att_advance(Att& t) {
  constexpr uint32_t SLOT = 32768 >> 4;
  t.kd ^= SLOT; t.vd ^= SLOT; t.c8 ^= 8; t.cb ^= 8;
  const uint32_t x = t.xc; t.xc = t.xp ^ 1; t.xp = x;
}
template <bool SECOND>
__device__ __forceinline__ uint32_t diag_step(float (&S)[64], float (&O)[64], uint32_t (&P)[32], uint32_t (&pk)[32], float& l0, float& l1, uint32_t& unsafe, Att& t, int r, int w, Cons& cs) {
  constexpr int JD = SECOND ? JDIAG2 : JDIAG;
  const uint32_t sb = cs.sb;
  float a0 = 0.f, a1 = 0.f;
  uint32_t ready;
  auto sums = [&]() {
    unsafe = row_norm(l0, l1, a0, a1);
    mbar_arrive_if<BAR(B_QEMPTY)>(sb, (threadIdx.x & 31) == 0 && !unsafe);
    l0 = l1 = 0.f;
  };
  auto look_ahead = [&]() { ready = mbar_test<BAR(B_FULL)>(t.cb, t.xc); if (!SECOND) ready &= mbar_test<BAR(B_QFULL)>(sb, cs.fpar & 1); };
  if (w == 1) {
    bar_sync(2, 256);
    issue_qk<false>(S, t.qd, t.kd);
    if (!SECOND && t.pub) { stage_publish(w, cs); t.pub = 0; }
    mbar_wait<BAR(B_FULL + 2)>(t.cb ^ 8, t.xp);
    issue_pv<8, 1>(O, P, t.vd);
    bar_arrive(1, 256);
    att_advance(t);
    wg_wait<1>();
    fence_regs(S);
    T4Q(__float_as_uint(S[0]));
    mbar_arrive_cl<BAR(B_EMPTY)>(cs.rel, t.c8 ^ 8);
    if (SECOND) sums();
    exp_inplace<0, JD, 8>(S, l0, l1, r);
    pin_after(l0, l1);
    wg_wait<0>();
    fence_regs(O);
    fence_regs(P);
    mbar_arrive_cl<BAR(B_EMPTY + 2)>(cs.rel, t.c8);
    look_ahead();
    exp_pack<JD, 8, SECOND>(S, P, l0, l1, r, O, a0, a1, pk);
  } else {
    bar_sync(1, 256);
    issue_qk<true>(S, t.qd, t.kd);
    mbar_wait<BAR(B_FULL + 2)>(t.cb ^ 8, t.xp);
    issue_pv<SECOND ? 4 : 8, 1>(O, P, t.vd);
    bar_arrive(2, 256);
    if (!SECOND && t.pub) { stage_publish(w, cs); t.pub = 0; }
    att_advance(t);
    if (SECOND) sums();
    wg_wait<1>();
    fence_regs<0, 32>(S);
    T4Q(__float_as_uint(S[0]));
    mbar_arrive_cl<BAR(B_EMPTY)>(cs.rel, t.c8 ^ 8);
    exp_inplace<0, 8, 0>(S, l0, l1, r);
    pin_after(l0, l1);
    wg_wait<0>();
    fence_regs(O);
    fence_regs(P);
    mbar_arrive_cl<BAR(B_EMPTY + 2)>(cs.rel, t.c8);
    look_ahead();
#pragma unroll
    for (int k = 0; k < 8; k++) { P[2 * k] = v_pack(S[4 * k + 0], S[4 * k + 1]); P[2 * k + 1] = v_pack(S[4 * k + 2], S[4 * k + 3]); }
    if (SECOND) att_output(O, a0, a1, pk);
  }
  return __reduce_or_sync(0xffffffffu, ready ^ 1);
}
__device__ __forceinline__ void attention(uint32_t code, uint32_t rank, int idx, int w, Cons& cs, uint32_t (&P)[32], uint32_t (&pk)[32]) {
  const int lane = threadIdx.x & 31, wq = (threadIdx.x >> 5) & 3;
  constexpr int JS = JSPLIT, JE = JEDGE;
  const uint32_t sb = cs.sb;
  const int y = (code & 15) * 2 + rank;
  const int r = wq * 16 + (lane >> 2) - 2 * (lane & 3);
  float O[64], S[64];
  float l0 = 0.f, l1 = 0.f;
  Att t = {dlo(OFF_A, 16) + w * 512, dlo(OFF_B, 16), dlo(OFF_B + 98304, 16384), 0, sb, cs.p0, cs.p1, 0};
  uint32_t unsafe = 0, late;
  int ns;
  auto stage_step = [&](uint32_t on) {
    att_advance(t);
    wg_wait<1>();
    fence_regs(S);
    T4Q(__float_as_uint(S[0]));
    mbar_arrive_cl<BAR(B_EMPTY)>(cs.rel, t.c8 ^ 8);
    exp_stage<JE>(S, l0, l1, pk, w, cs, on);
    pin_after(l0, l1);
    wg_wait<0>();
    fence_regs(O);
    fence_regs(P);
    mbar_arrive_cl<BAR(B_EMPTY + 2)>(cs.rel, t.c8);
    const uint32_t ready = mbar_test<BAR(B_FULL)>(t.cb, t.xc);
    exp_pack<JE, 16, false>(S, P, l0, l1, r, O, 0.f, 0.f, pk);
    late = __reduce_or_sync(0xffffffffu, ready ^ 1);
  };
  bar_sync(3 - w, 128 + 128 * w);
  if (y >= 2) {
    const uint32_t todo = y >= 2 * MEARLY;
    issue_qk<false>(O, t.qd, dlo(OFF_B + 32768, 16));
    mbar_wait<BAR(B_FULL)>(sb, t.xc);
    issue_qk<false>(S, t.qd, dlo(OFF_B, 16));
    bar_arrive(1 + (w ^ 1), 256);
    T4X(0);
    wg_wait<1>();
    fence_regs(O);
    T4Q(0);
    mbar_arrive_cl<BAR(B_EMPTY + 1)>(cs.rel);
    exp_stage<JP>(O, l0, l1, pk, w, cs, todo & (w ^ 1));
    pin_after(l0, l1);
    const uint32_t rd = mbar_test<BAR(B_FULL + 3)>(sb, t.xp);
    exp_pack<JP, 16, false>(O, P, l0, l1, r, O, 0.f, 0.f, pk);
    if (UNLIKELY(__reduce_or_sync(0xffffffffu, rd ^ 1))) mbar_wait<BAR(B_FULL + 3)>(sb, t.xp);
    bar_sync(1 + w, 256);
    issue_pv<8, 0>(O, P, t.vd);
    bar_arrive(1 + (w ^ 1), 256);
    stage_step(todo & w);
    t.pub = todo;
    ns = y - 2;
  } else {
    issue_qk<false>(S, t.qd, dlo(OFF_B + 32768, 16));
    bar_arrive(1 + (w ^ 1), 256);
    T4X(0);
    wg_wait<0>();
    fence_regs(S);
    T4Q(__float_as_uint(S[0]));
    mbar_arrive_cl<BAR(B_EMPTY + 1)>(cs.rel);
    causal_mask<0>(S, r + 64 * w + 128 * y);
    causal_mask<8>(S, r + 64 * w + 128 * y - 64);
    exp_pack<0, 16, false>(S, P, l0, l1, r, S, 0.f, 0.f, pk);
#pragma unroll
    for (int i = 0; i < 64; i++) O[i] = 0.f;
    late = 1;
    ns = 0;
  }
#pragma unroll 1
  for (uint32_t head = 0;; head++) {
    while (ns > 0) {
      if (UNLIKELY(late)) mbar_wait<BAR(B_FULL)>(t.cb, t.xc);
      bar_sync(1 + w, 256);
      issue_qk<false>(S, t.qd, t.kd);
      if (t.pub) { stage_publish(w, cs); t.pub = 0; }
      mbar_wait<BAR(B_FULL + 2)>(t.cb ^ 8, t.xp);
      issue_pv<8, 1>(O, P, t.vd);
      bar_arrive(1 + (w ^ 1), 256);
      ns--;
      att_advance(t);
      wg_wait<1>();
      fence_regs(S);
      T4Q(__float_as_uint(S[0]));
      mbar_arrive_cl<BAR(B_EMPTY)>(cs.rel, t.c8 ^ 8);
      exp_inplace<0, JS>(S, l0, l1);
      pin_after(l0, l1);
      wg_wait<0>();
      fence_regs(O);
      fence_regs(P);
      mbar_arrive_cl<BAR(B_EMPTY + 2)>(cs.rel, t.c8);
      const uint32_t rd = mbar_test<BAR(B_FULL)>(t.cb, t.xc);
      exp_pack<JS, 16, false>(S, P, l0, l1, 0, O, 0.f, 0.f, pk);
      late = __reduce_or_sync(0xffffffffu, rd ^ 1);
    }
    if (head == 0) {
      if (y != 0) {
        if (UNLIKELY(late)) mbar_wait<BAR(B_FULL)>(t.cb, t.xc);
        late = diag_step<false>(S, O, P, pk, l0, l1, unsafe, t, r, w, cs);
      }
      t.qd += 32768 >> 4;
      TRW(idx, 4);
      if (UNLIKELY(late)) { mbar_wait<BAR(B_QFULL)>(sb, cs.fpar & 1); mbar_wait<BAR(B_FULL)>(t.cb, t.xc); }
      late = diag_step<true>(S, O, P, pk, l0, l1, unsafe, t, r, w, cs);
    } else {
      bar_sync(1 + w, 256);
      mbar_wait<BAR(B_FULL + 2)>(t.cb ^ 8, t.xp);
      if (y != 1 || w) issue_pv<8, 1>(O, P, t.vd); else issue_pv<4, 1>(O, P, t.vd);
      if (w == 0) bar_arrive(2, 256);
      if (t.pub) stage_publish(w, cs);
      float a0, a1;
      unsafe = row_norm(l0, l1, a0, a1);
      mbar_arrive_if<BAR(B_QEMPTY + 1)>(sb, lane == 0 && !unsafe);
      wg_wait<0>();
      fence_regs(O);
      fence_regs(P);
      mbar_arrive_cl<BAR(B_EMPTY + 2)>(cs.rel, t.c8 ^ 8);
      att_output(O, a0, a1, pk);
    }
    if (UNLIKELY(unsafe)) {
      float a0, a1;
      slow_item(S, a0, a1, ((code >> 4) & 31) * 2 + head, y ^ head, sb + OFF_A + head * 32768, w);
      __syncwarp();
      mbar_arrive_if<BAR(B_QEMPTY)>(sb + head * 8, lane == 0);
      att_output(S, a0, a1, pk);
    }
    if (head) break;
    if (y != 1) {
      if (UNLIKELY(late)) mbar_wait<BAR(B_FULL)>(t.cb, t.xc);
      bar_sync(1 + w, 256);
      issue_qk<false>(S, t.qd, t.kd);
      mbar_wait<BAR(B_STGE)>(sb + w * 8, (cs.round & 1) ^ 1);
      mbar_wait<BAR(B_FULL + 2)>(t.cb ^ 8, t.xp);
      if (w == 0) issue_pv<4, 0>(O, P, t.vd); else issue_pv<8, 0>(O, P, t.vd);
      bar_arrive(1 + (w ^ 1), 256);
      stage_step(1);
      t.pub = 1;
      ns = (y ^ 1) - 1;
    } else {
      stage_write(pk, w, cs);
      t.pub = 1;
#pragma unroll
      for (int i = 0; i < 64; i++) O[i] = 0.f;
    }
  }
  cs.p1 = t.xp ^ 1; cs.p0 = t.xc;
  cs.fpar ^= 1;
}

struct Src { const CUtensorMap *ma, *mb; int a0, a1, b0, b1, b2; uint32_t hb; };
__device__ __forceinline__ Src gemm_src(const Params& p, uint32_t code, uint32_t rank, uint32_t h) {
  const int kind = code >> 9, x = (code >> 4) & 31, m = code & 15;
  Src s;
  s.ma = &p.maps[M_AX + kind];
  s.mb = &p.maps[(kind == K_KV && h) ? M_WUV : M_WQKV + kind];
  if (kind == K_QL) { s.a0 = rank * 1024; s.a1 = m * 128; s.b0 = x * 64; s.b1 = h * 32; s.b2 = 0; s.hb = 12288; }
  else { s.a0 = 0; s.a1 = (2 * m + rank) * 128; s.b0 = 0; s.b1 = 0; s.b2 = kind == K_KV ? x * 2 : x * 4 + h * 2; s.hb = 16384; }
  return s;
}
__global__ void __cluster_dims__(2, 1, 1) __launch_bounds__(384, 1) mega_kernel(const __grid_constant__ Params p) {
  extern __shared__ __align__(1024) uint8_t smem_raw[];
  const uint32_t sb = smem_u32(smem_raw), sb0 = sb;
  const uint32_t bid = blockIdx.x, rank = bid & 1;
  const int warp = __shfl_sync(0xffffffffu, threadIdx.x >> 5, 0);
  auto early_load = [&](uint32_t code0, int s0, int s1) {
    const Src u = gemm_src(p, code0, rank, 0), v = gemm_src(p, code0, rank, 1);
#pragma unroll
    for (int s = s0; s < s1; s++) {
      const uint32_t bar = sb + BAR(B_FULL) + s * 8;
      if (elect_one()) {
        mbar_expect_tx<0>(bar, 16384 + 2 * u.hb);
        tma_load_2d(sb + OFF_A + s * 16384, u.ma, u.a0 + s * 64, u.a1, bar);
        tma_load_3d(sb + OFF_B + s * 32768, u.mb, u.b0, u.b1 + s * 64, u.b2, bar);
        tma_load_3d(sb + OFF_B + s * 32768 + u.hb, v.mb, v.b0, v.b1 + s * 64, v.b2, bar);
      }
    }
  };
#define BI(b) mbar_init<BAR(b)>(sb, bar_count(b))
  static_assert(B_COUNT == 25, "barrier set-up");
  if (warp == 0) {
    const uint32_t c0 = p.sched[bid >> 1][threadIdx.x & 1];
    if (elect_one()) {
      BI(0); BI(1); BI(2); BI(3);
      asm volatile("fence.mbarrier_init.release.cluster;" ::: "memory");
    }
    __syncwarp();
    early_load(__shfl_sync(0xffffffffu, c0, 0) & 4095, 0, EARLYN);
  }
  if (threadIdx.x == 32 || threadIdx.x == 64 || threadIdx.x == 96) {
    if (threadIdx.x == 32) { BI(4); BI(5); BI(6); BI(7); BI(8); BI(9); BI(21); }
    else if (threadIdx.x == 64) { BI(10); BI(11); BI(12); BI(13); BI(14); BI(15); BI(22); }
    else {
      BI(16); BI(17); BI(18); BI(19); BI(20); BI(23); BI(24);
      asm volatile("st.shared.u32 [%0+%2], %1;\nst.shared.v4.u32 [%0+%3], {%1, %1, %1, %1};" ::"r"(sb), "r"(0), "n"(OFF_FILLS), "n"(OFF_FILLS + 16) : "memory");
      if ((sb & 0xffffffu) != SB) __trap();
    }
    asm volatile("fence.mbarrier_init.release.cluster;" ::: "memory");
  }
#undef BI
  if (warp == 4) {
    const int i = threadIdx.x - 128;
    if (i < MAX_ITEMS / 4) {
      const uint4 v = *reinterpret_cast<const uint4*>(&p.sched[bid >> 1][4 * i]);
      asm volatile("st.shared.v4.u32 [%0+%5], {%1, %2, %3, %4};" ::"r"(sb + i * 16), "r"(v.x), "r"(v.y), "r"(v.z), "r"(v.w), "n"(OFF_LIST) : "memory");
    }
    asm volatile("st.shared.v2.u32 [%0+%2], {%1, %1};" ::"r"(sb + i * 8), "r"(0), "n"(OFF_MASK) : "memory");
  }
  bar_sync(0, 384);
  cluster_arrive_relaxed();
  const int wg = warp >> 2;
  if (wg == 0) {
    reg_dealloc<REG_PROD>();
    if (EARLYN < 4 && warp == 0) early_load(item(sb, 0), EARLYN, 4);
    cluster_wait();
    const int lane = threadIdx.x & 31;
    auto need = [&](uint32_t& have, int i, int b) {
      if (!((have >> b) & 1)) {
        uint32_t n = 0;
        while (have = __reduce_or_sync(0xffffffffu, lds_acquire<OFF_MASK>(sb + i * 4)), !((have >> b) & 1)) { __nanosleep(32); if (++n > (1u << 22)) __trap(); }
        fence_async_glob();
      }
    };
    if (warp == 0) {
      uint32_t e0 = 0, e1 = 0;
      uint32_t qe = 0, after_att = 0, fills = 0;
      const uint64_t pol_first = policy_evict_first(), pol_normal = POL_NORMAL;
      for (int idx = 0;; idx++) {
        const uint32_t full = item_full(sb, idx), code = full & 4095;
        const int kind = code >> 9, x = (code >> 4) & 31, m = code & 15, y = 2 * m + rank;
        if (kind == K_END) break;
        const uint32_t last = full & (((LASTUSE & (kind >= K_OA ? 4 : 1)) ? 0x3000u : 0u) | ((LASTUSE & 2) ? 0xffff0000u : 0u));
        {
          const Src u = gemm_src(p, code, rank, rank);
          const uint64_t pa = (last & 0x1000) ? pol_first : pol_normal, pb = (last & 0x2000) ? pol_first : pol_normal;
          const int nk = kind == K_KV ? 8 : kind == K_OB ? 64 : 16;
          uint32_t have = kind >= K_OA ? 0u : 0xffffffffu;
#pragma unroll 1
          for (int k = idx == 0 ? 4 : 0; k < nk; k++) {
            const uint32_t s = k & 3;
            int kk = k;
            if (k >= 64 - 4 * HLATE) { const int j = (k >> 1) - (32 - 2 * HLATE); kk = (32 - 2 * HLATE + (j < HLATE ? 2 * j : 2 * (j - HLATE) + 1)) * 2 + (k & 1); }
            need(have, (kind == K_OA ? F_QL : F_CTX) + y, kind == K_OA ? k : kk >> 1);
            if (after_att && !(k & 1)) {
              mbar_wait<BAR(B_QEMPTY)>(sb + k * 4, qe);
              if (k == 2) { after_att = 0; qe ^= 1; }
            }
            fill_gemm(sb + s * 8, (s & 1) ? e1 : e0, 16384 + 2 * u.hb, sb + OFF_B + s * 32768 + rank * u.hb, u.mb, u.b0, u.b1 + kk * 64, u.b2, sb + OFF_A + s * 16384, u.ma, u.a0 + kk * 64, u.a1, pb, pa);
            asm volatile("st.volatile.shared.u32 [%0+%2], %1;" ::"r"(sb), "r"(++fills), "n"(OFF_FILLS) : "memory");
            if (s == 3) { e0 ^= 1; e1 ^= 1; }
          }
        }
        if (kind == K_QF) {
          uint32_t have = 0, xc = e1, xp = e0 ^ 1;
#pragma unroll 1
          for (int j = 0; j < 8 * m + 8; j++) {
            const int i = j >> 1, v = j & 1;
            if (v ? i == 0 : i == 4 * m + 3) continue;
            const int ib = i - v;
            if (i == 2 * m + 1 + rank && !v) have = 0;
            const int h = 2 * x + (ib >= 2 * m + 1 + (int)rank), blk = ib <= 2 * m + 1 ? ib : 4 * m + 2 - ib;
            const int row = KVSLOT(h) * SEQ + blk * 128;
            if (!v) need(have, F_KV + h, blk);
            const uint32_t b = 2 * v + ((ib + 1) & 1);
            const uint32_t dst = sb + OFF_B + b * 32768;
            const bool own = ib == 2 * m + 1;
            const uint64_t pol = ((last >> (16 + (h & 1) * 8 + (blk >> 1))) & 1) ? pol_first : pol_normal;
            fill_kv(sb + b * 8, v ? xp : xc, dst + rank * 16384, &p.maps[M_KV_LD], (2 * v + rank) * 64, row, own ? 1 + rank : 3, pol);
            if (own) tma_load_2d_h(dst + (rank ^ 1) * 16384, &p.maps[M_KV_LD], (2 * v + (rank ^ 1)) * 64, row, sb + BAR(B_FULL) + b * 8, pol);
            if (v || i == 0) { const uint32_t t = xc; xc = xp ^ 1; xp = t; }
          }
          e0 ^= 1;
          after_att = 1;
        }
      }
    } else if (warp == 2) {
      const uint32_t epoch = g_flags.epoch[bid];
      const uint64_t full = (lane >> 3) == 2 ? ~0ull : 0x0000ffff0000ffffull, flip = 0ull - (epoch & 1);
      uint64_t seen = 0;
      uint32_t tries = 0, hp = 1, hcode;
      int hidx = -1;
      auto next_halo = [&]() { do hcode = item(sb, ++hidx); while ((hcode >> 9) != K_END && ((hcode >> 9) != K_QL || (hcode & 15) == 0)); };
      next_halo();
      while (true) {
        const bool all = __all_sync(0xffffffffu, seen == full);
        if (all && (hcode >> 9) == K_END) break;
        if (!all) {
          uint64_t v;
          asm volatile("ld.acquire.gpu.global.u64 %0, [%1];" : "=l"(v) : "l"(&g_flags.m[2 * lane]) : "memory");
          v = (v ^ flip) & full;
          if (v != seen) { seen = v; asm volatile("st.release.cta.shared::cta.u64 [%0+%2], %1;" ::"r"(sb + lane * 8), "l"(v), "n"(OFF_MASK) : "memory"); }
        }
        if ((hcode >> 9) != K_END) {
          const int x = (hcode >> 4) & 31, m = hcode & 15;
          bool there = __any_sync(0xffffffffu, lane == F_QL / 2 + m - 1 && ((seen >> (32 * rank + x)) & 1));
          if (there && __all_sync(0xffffffffu, mbar_test<BAR(B_HEMPTY)>(sb, hp))) {
            __syncwarp();
            fence_async_glob();
            if (elect_one()) mbar_expect_tx<BAR(B_HFULL)>(sb, 2048);
            bulk_load(sb + OFF_HALO, g_halo + ((2 * m + rank - 2) * 16 + x) * 2048, 2048, sb + BAR(B_HFULL));
            hp ^= 1;
            next_halo();
          }
        }
        __nanosleep(WATCH_NS);
        if (++tries > (1u << 20)) __trap();
      }
      if (lane == 0) g_flags.epoch[bid] = epoch + 1;
    } else if (warp == 3) {
      uint32_t n = 0;
      for (int idx = 0; RELW; idx++) {
        const uint32_t code = item(sb, idx);
        const int kind = code >> 9, x = (code >> 4) & 31, y = 2 * (code & 15) + rank;
        if (kind == K_END) break;
        if (kind > K_KV) continue;
#pragma unroll 1
        for (int r = 0; r <= (kind == K_QF); r++, n++) {
          mbar_wait_long<BAR(B_RELF)>(sb + (n & 1) * 8, (n >> 1) & 1);
          mbar_arrive_if<BAR(B_RELE)>(sb + (n & 1) * 8, lane == 0);
          flag_toggle(&g_flags.m[kind == K_QL ? F_QL + y : kind == K_KV ? F_KV + x : F_CTX + (y ^ r)], 1u << (kind == K_QL ? x : kind == K_KV ? y : 2 * x + r));
          TRC(idx, 12 + (kind == K_KV ? 1 : r));
        }
      }
    } else {
      {
        uint32_t round = 0, fpar = 0, nrel = 0;
        const uint32_t rb = mapa(sb, rank ^ 1);
        const uint64_t pol_first = policy_evict_first(), pol_normal = POL_NORMAL;
        auto pace = [&]() {
          uint32_t c0, c, t0, t;
          asm volatile("ld.volatile.shared.u32 %0, [%1+%2];" : "=r"(c0) : "r"(sb), "n"(OFF_FILLS) : "memory");
          asm volatile("mov.u32 %0, %clock;" : "=r"(t0));
          do {
            asm volatile("ld.volatile.shared.u32 %0, [%1+%2];" : "=r"(c) : "r"(sb), "n"(OFF_FILLS) : "memory");
            asm volatile("mov.u32 %0, %clock;" : "=r"(t));
          } while (__all_sync(0xffffffffu, c == c0 && t - t0 < PACE_MAX));
        };
        for (int idx = 0;; idx++) {
          const uint32_t code = item(sb, idx);
          const int kind = code >> 9, x = (code >> 4) & 31, m = code & 15, y = 2 * m + rank;
          if (kind == K_END) break;
          const bool last = (item(sb, idx + 1) >> 9) == K_END;
          if (kind == K_QF) {
            if (elect_one()) mbar_expect_tx<BAR(B_QFULL)>(sb, 32768);
            mbar_wait_long<BAR(B_QX)>(sb, fpar);
#pragma unroll 1
            for (int v = 0; v < 2; v++) {
              mbar_wait<BAR(B_STGF)>(sb + v * 8, round & 1);
              bulk_send(rb + OFF_A + 32768 + v * 8192, sb + OFF_STG + v * 16384, 8192, rb + BAR(B_QFULL));
              bulk_send(rb + OFF_A + 49152 + v * 8192, sb + OFF_STG + v * 16384 + 8192, 8192, rb + BAR(B_QFULL));
            }
            mbar_wait<BAR(B_QFULL)>(sb, fpar);
            mbar_arrive_cl<BAR(B_STGE)>(lane < 2 ? rb : 0, lane * 8);
            round++; fpar ^= 1;
          }
          const CUtensorMap* mc = &p.maps[M_OA_ST + kind];
          const uint64_t pol = (((HINTS & 1) && kind >= K_OA) || ((HINTS & 2) && kind == K_QF) || ((HINTS & 4) && kind == K_QL) || ((HINTS & 8) && kind == K_KV)) ? pol_first : pol_normal;
          int row = kind == K_KV ? KVSLOT(x) * SEQ + y * 128 : kind == K_OA ? m * 128 : y * 128;
          int cg = kind == K_QL ? x : kind == K_QF ? x * 4 : kind == K_KV ? 0 : kind == K_OA ? rank * 32 + x * 4 : 16 + x * 4;
          const int nr = kind == K_QL ? 1 : 2;
#pragma unroll 1
          for (int r = 0; r < nr; r++) {
            mbar_wait_long<BAR(B_STGF)>(sb, round & 1);
            if (last && kind >= K_KV) {
              TRC(idx + 1, 6);
              tma_store_3d(mc, sb + OFF_STG, 0, row, cg, pol);
              mbar_wait<BAR(B_FIN)>(sb, 0);
              TRC(idx + 1, 7);
              tma_store_3d(mc, sb + OFF_B, 0, row, cg + 2, pol);
              mbar_wait<BAR(B_STGF + 1)>(sb, round & 1);
              TRC(idx + 1, 8);
              tma_store_3d(mc, sb + OFF_STG + 16384, 0, row + 64, cg, pol);
              mbar_wait<BAR(B_FIN + 1)>(sb, 0);
              TRC(idx + 1, 9);
              tma_store_3d(mc, sb + OFF_B + 16384, 0, row + 64, cg + 2, pol);
              bulk_commit();
              r = 1;
            } else {
              const bool paced = !last && (kind >= K_KV || r == 1);
              if (paced) pace();
              tma_store_3d(mc, sb + OFF_STG, 0, row, cg, pol);
              bulk_commit();
              mbar_wait<BAR(B_STGF + 1)>(sb, round & 1);
              if (paced) pace();
              tma_store_3d(mc, sb + OFF_STG + 16384, 0, row + 64, cg, pol);
              if (kind == K_QL) bulk_store(g_halo + (y * 16 + x) * 2048, sb + OFF_STG + 16384 + 8192 + 3 * 2048, 2048);
              bulk_commit();
              bulk_wait_read<1>();
              mbar_arrive_if<BAR(B_STGE)>(sb, lane == 0);
              bulk_wait_read<0>();
              mbar_arrive_if<BAR(B_STGE + 1)>(sb, lane == 0);
              round++;
            }
            if (kind == K_QF || (kind <= K_KV && r == nr - 1)) {
              bulk_wait_all();
              if (RELW) {
                mbar_wait<BAR(B_RELE)>(sb + (nrel & 1) * 8, ((nrel >> 1) & 1) ^ 1);
                __syncwarp();
                mbar_arrive_if<BAR(B_RELF)>(sb + (nrel & 1) * 8, lane == 0);
                nrel++;
              } else {
                flag_toggle(&g_flags.m[kind == K_QL ? F_QL + y : kind == K_KV ? F_KV + x : F_CTX + (y ^ r)], 1u << (kind == K_QL ? x : kind == K_KV ? y : 2 * x + r));
                TRC(idx, 12 + r);
              }
            }
            cg += 2;
            if (kind == K_QF) row ^= 128;
          }
        }
        bulk_wait_all();
      }
      cluster_arrive_relaxed();
      cluster_wait();
    }
  } else {
    reg_alloc<REG_CONS>();
    cluster_wait();
    const int w = wg - 1;
    Cons cs;
    cs.sb = SBU ? __reduce_or_sync(0xffffffffu, sb0) : sb0;
    const uint32_t sb = cs.sb;
    cs.rel = (threadIdx.x & 127) == 0 ? sb : (threadIdx.x & 127) == 1 ? mapa(sb, rank ^ 1) : 0;
    cs.p0 = cs.p1 = cs.lead = cs.round = cs.fpar = 0;
    uint32_t pkA[32], pkB[32], pend = 0;
#pragma unroll
    for (int i = 0; i < 32; i++) pkA[i] = pkB[i] = 0;
    uint32_t code = item(sb, 0);
    int idx = 0;
    do {
      TRW(idx, 0);
      const int kind = code >> 9;
      uint32_t ncode;
      if (kind == K_QL) {
        float acc[96];
        Loc l;
        ncode = gemm_tile(acc, 4, idx, w, cs, pend, pkA, pkB, [&] { l = local_prepare(code, w, cs); });
        TRW(idx, 2);
        local_epilogue(acc, code, w, cs, l);
        pend = 24;
        if (LHS && w == 1 && (ncode >> 9) != K_END) bar_arrive(5, 256);
        if (!LPUB || (ncode >> 9) >= K_OA) { stage_publish(w, cs); pend = 16; }
      } else {
        float acc[128];
        ncode = gemm_tile(acc, kind == K_KV ? 2 : kind == K_OB ? 16 : 4, idx, w, cs, pend, pkA, pkB, [] {});
        TRW(idx, 2);
        if (kind == K_QF) {
          mbar_arrive_cl<BAR(B_QX)>((threadIdx.x & 1) ? cs.rel : 0);
          tile_pack_write<OFF_A, 16384, 0>(acc, pkB, sb + w * 8192);
#pragma unroll
          for (int i = 0; i < 32; i++) pkA[i] = v_pack(acc[64 + 2 * i], acc[64 + 2 * i + 1]);
          T4X(pkA[31]);
          mbar_wait<BAR(B_STGE)>(sb + w * 8, (cs.round & 1) ^ 1);
          if ((code & 15) < MEARLY) { tile_write<OFF_STG, 8192>(pkA, sb + w * 16384); stage_publish(w, cs); }
          mbar_wait<BAR(B_FULL + 1)>(sb, cs.p1);
          T4X(0);
          fence_async_smem();
          attention(code, rank, idx, w, cs, pkB, pkA);
          pend = 1;
        } else {
          if (kind == K_KV) {
#pragma unroll
            for (int i = 0; i < 64; i++) acc[i] *= SCALE_LOG2;
          }
#pragma unroll
          for (int i = 0; i < 32; i++) pkA[i] = pack_bf16(acc[2 * i], acc[2 * i + 1]);
#pragma unroll
          for (int i = 0; i < 32; i++) pkB[i] = pack_bf16(acc[64 + 2 * i], acc[64 + 2 * i + 1]);
          pend = 3;
        }
      }
      code = ncode;
      idx++;
    } while ((code >> 9) != K_END);
    TRW(idx, 0);
    if (pend & 1) { stage_write(pkA, w, cs); stage_publish(w, cs); }
    if (pend & 2) {
      mbar_wait<BAR(B_EMPTY)>(sb, cs.p0 ^ 1);
      tile_write<OFF_B, 8192>(pkB, sb + w * 16384);
      fence_async_smem();
      __syncwarp();
      mbar_arrive_if<BAR(B_FIN)>(sb + w * 8, (threadIdx.x & 31) == 0);
    }
    cluster_arrive();
  }
}

typedef CUresult (*EncodeFn)(CUtensorMap*, CUtensorMapDataType, cuuint32_t, void*, const cuuint64_t*, const cuuint64_t*, const cuuint32_t*,
                             const cuuint32_t*, CUtensorMapInterleave, CUtensorMapSwizzle, CUtensorMapL2promotion, CUtensorMapFloatOOBfill);

void make_map_2d(EncodeFn enc, CUtensorMap* tm, const void* ptr, uint64_t cols, uint64_t rows) {
  cuuint64_t dims[2] = {cols, rows};
  cuuint64_t str[1] = {cols * 2};
  cuuint32_t box[2] = {64, 128};
  cuuint32_t es[2] = {1, 1};
  enc(tm, CU_TENSOR_MAP_DATA_TYPE_BFLOAT16, 2, const_cast<void*>(ptr), dims, str, box, es, CU_TENSOR_MAP_INTERLEAVE_NONE, CU_TENSOR_MAP_SWIZZLE_128B,
      CU_TENSOR_MAP_L2_PROMOTION_L2_256B, CU_TENSOR_MAP_FLOAT_OOB_FILL_NONE);
}
void make_map_3d(EncodeFn enc, CUtensorMap* tm, const void* ptr, uint64_t cols, uint64_t rows, uint64_t part, uint32_t br, uint32_t bg) {
  cuuint64_t dims[3] = {part, rows, cols / part};
  cuuint64_t str[2] = {cols * 2, part * 2};
  cuuint32_t box[3] = {64, br, bg};
  cuuint32_t es[3] = {1, 1, 1};
  enc(tm, CU_TENSOR_MAP_DATA_TYPE_BFLOAT16, 3, const_cast<void*>(ptr), dims, str, box, es, CU_TENSOR_MAP_INTERLEAVE_NONE, CU_TENSOR_MAP_SWIZZLE_128B,
      CU_TENSOR_MAP_L2_PROMOTION_L2_256B, CU_TENSOR_MAP_FLOAT_OOB_FILL_NONE);
}

static const uint32_t h_sched[NPAIR][MAX_ITEMS] = {
  {0x400,0xff800207,0x554,0x564,0x566,0x1e02c4,0x20a7,0x625,0xe00,0xe00,0xe00,0xe00,0xe00,0xe00,0xe00,0xe00,0xe00,0xe00,0xe00,0xe00},
  {0x420,0x454,0x2,0x83,0x25,0xb6,0x4f0,0x2a5,0x25d0,0x202f1,0x636,0xe00,0xe00,0xe00,0xe00,0xe00,0xe00,0xe00,0xe00,0xe00},
  {0x440,0x200,0xe3,0x55,0x520,0x4d4,0x524,0xfff002a7,0x2037,0x30f7,0xe00,0xe00,0xe00,0xe00,0xe00,0xe00,0xe00,0xe00,0xe00,0xe00},
  {0x460,0x206,0x32281,0x2c2,0x202e1,0x603,0xe00,0xe00,0xe00,0xe00,0xe00,0xe00,0xe00,0xe00,0xe00,0xe00,0xe00,0xe00,0xe00,0xe00},
  {0x410,0x1,0x92,0x24,0xd5,0x40252,0x202a1,0x830,0xe00,0xe00,0xe00,0xe00,0xe00,0xe00,0xe00,0xe00,0xe00,0xe00,0xe00,0xe00},
  {0x430,0x474,0x12,0x93,0x4c1,0x4e1,0x4e3,0x4d5,0x513,0x536,0x583,0x2a0,0x5f3,0x815,0xe00,0xe00,0xe00,0xe00,0xe00,0xe00},
  {0x450,0x205,0x510,0x512,0x534,0x584,0x2547,0x574,0x2d3,0x20d7,0x616,0xe00,0xe00,0xe00,0xe00,0xe00,0xe00,0xe00,0xe00,0xe00},
  {0x470,0x406,0x485,0x4a1,0x486,0x497,0x4a5,0xa6,0x180284,0x1002f4,0x634,0xe00,0xe00,0xe00,0xe00,0xe00,0xe00,0xe00,0xe00,0xe00},
  {0x401,0x11,0x244,0x2a4,0x812,0xe00,0xe00,0xe00,0xe00,0xe00,0xe00,0xe00,0xe00,0xe00,0xe00,0xe00,0xe00,0xe00,0xe00,0xe00},
  {0x0,0xb1,0x33,0xd4,0x36,0x24c7,0x505,0x526,0x563,0x546,0x5e3,0x596,0x5f6,0x816,0xe00,0xe00,0xe00,0xe00,0xe00,0xe00},
  {0x421,0x201,0x94,0x276,0x5d2,0x837,0xe00,0xe00,0xe00,0xe00,0xe00,0xe00,0xe00,0xe00,0xe00,0xe00,0xe00,0xe00,0xe00,0xe00},
  {0x441,0x21,0xa2,0x34,0xe5,0x285,0x1002e4,0x613,0xe00,0xe00,0xe00,0xe00,0xe00,0xe00,0xe00,0xe00,0xe00,0xe00,0xe00,0xe00},
  {0x10,0x224,0x4d7,0x515,0x544,0x5c0,0x585,0x577,0x2002e5,0x633,0xe00,0xe00,0xe00,0xe00,0xe00,0xe00,0xe00,0xe00,0xe00,0xe00},
  {0x461,0x203,0x76,0x523,0x506,0x802a3,0x822,0xe00,0xe00,0xe00,0xe00,0xe00,0xe00,0xe00,0xe00,0xe00,0xe00,0xe00,0xe00,0xe00},
  {0x480,0x210,0xf3,0x4c2,0xffc00277,0x802e3,0x622,0xe00,0xe00,0xe00,0xe00,0xe00,0xe00,0xe00,0xe00,0xe00,0xe00,0xe00,0xe00,0xe00},
  {0x20,0x233,0x4b3,0x260,0x290,0x5c6,0x5b6,0x800,0xe00,0xe00,0xe00,0xe00,0xe00,0xe00,0xe00,0xe00,0xe00,0xe00,0xe00,0xe00},
  {0x411,0x31,0xb2,0x256,0x586,0x590,0x2594,0x803,0xe00,0xe00,0xe00,0xe00,0xe00,0xe00,0xe00,0xe00,0xe00,0xe00,0xe00,0xe00},
  {0x431,0x426,0xff800247,0x4002c6,0x2077,0x614,0xe00,0xe00,0xe00,0xe00,0xe00,0xe00,0xe00,0xe00,0xe00,0xe00,0xe00,0xe00,0xe00,0xe00},
  {0x451,0x41,0xc2,0xff800257,0x592,0x1802d4,0x600,0xe00,0xe00,0xe00,0xe00,0xe00,0xe00,0xe00,0xe00,0xe00,0xe00,0xe00,0xe00,0xe00},
  {0x471,0x446,0x466,0x2456,0x2467,0x4a3,0x4c3,0x4b4,0x296,0x15f1,0x35f0,0x2017,0x2067,0x632,0xe00,0xe00,0xe00,0xe00,0xe00,0xe00},
  {0x490,0x484,0x22,0xa3,0x35,0xc6,0x40272,0x4002e6,0x623,0xe00,0xe00,0xe00,0xe00,0xe00,0xe00,0xe00,0xe00,0xe00,0xe00,0xe00},
  {0x402,0x465,0x32,0x476,0x495,0x75,0x521,0x4d3,0x525,0x2517,0x5e0,0x5a2,0x5c4,0x2002f5,0x604,0xe00,0xe00,0xe00,0xe00,0xe00},
  {0x30,0x400226,0x80293,0x834,0xe00,0xe00,0xe00,0xe00,0xe00,0xe00,0xe00,0xe00,0xe00,0xe00,0xe00,0xe00,0xe00,0xe00,0xe00,0xe00},
  {0x422,0x211,0xa4,0x500,0x502,0xffe00297,0x322d1,0x631,0xe00,0xe00,0xe00,0xe00,0xe00,0xe00,0xe00,0xe00,0xe00,0xe00,0xe00,0xe00},
  {0x40,0x2447,0x82,0x44,0xf5,0xe6,0x4f5,0x535,0x553,0x808002d7,0x611,0xe00,0xe00,0xe00,0xe00,0xe00,0xe00,0xe00,0xe00,0xe00},
  {0x442,0x416,0x42,0xb3,0x200255,0x5a3,0x5a5,0x5b7,0x813,0xe00,0xe00,0xe00,0xe00,0xe00,0xe00,0xe00,0xe00,0xe00,0xe00,0xe00},
  {0x462,0x220,0x4,0x65,0x4c5,0x522,0x541,0x514,0x545,0x573,0x5c3,0x5e5,0x5d6,0x806,0xe00,0xe00,0xe00,0xe00,0xe00,0xe00},
  {0x481,0x436,0x52,0xc3,0x45,0xd6,0x32261,0x5c2,0x4002f6,0x624,0xe00,0xe00,0xe00,0xe00,0xe00,0xe00,0xe00,0xe00,0xe00,0xe00},
  {0x412,0x204,0xffe00287,0x402f2,0x637,0xe00,0xe00,0xe00,0xe00,0xe00,0xe00,0xe00,0xe00,0xe00,0xe00,0xe00,0xe00,0xe00,0xe00,0xe00},
  {0x50,0xc1,0x43,0xe4,0x46,0x4e5,0x24e7,0x543,0x533,0x5c1,0x2567,0x593,0x5b5,0x833,0xe00,0xe00,0xe00,0xe00,0xe00,0xe00},
  {0x432,0x4a0,0x62,0xd3,0x4a4,0x200265,0x576,0x5d7,0x804,0xe00,0xe00,0xe00,0xe00,0xe00,0xe00,0xe00,0xe00,0xe00,0xe00,0xe00},
  {0x452,0x455,0x241,0xc5,0x286,0x831,0xe00,0xe00,0xe00,0xe00,0xe00,0xe00,0xe00,0xe00,0xe00,0xe00,0xe00,0xe00,0xe00,0xe00},
  {0x472,0x51,0x245,0x562,0x550,0x808002e7,0x607,0xe00,0xe00,0xe00,0xe00,0xe00,0xe00,0xe00,0xe00,0xe00,0xe00,0xe00,0xe00,0xe00},
  {0x403,0x61,0xd2,0x4a2,0x2496,0x4a6,0x501,0x250,0x537,0x565,0x2587,0x5e6,0x5b1,0x827,0xe00,0xe00,0xe00,0xe00,0xe00,0xe00},
  {0x423,0x71,0x243,0x4e6,0x100294,0x821,0xe00,0xe00,0xe00,0xe00,0xe00,0xe00,0xe00,0xe00,0xe00,0xe00,0xe00,0xe00,0xe00,0xe00},
  {0x443,0x202,0x85,0x200275,0x5d4,0x820,0xe00,0xe00,0xe00,0xe00,0xe00,0xe00,0xe00,0xe00,0xe00,0xe00,0xe00,0xe00,0xe00,0xe00},
  {0x482,0x212,0x95,0x80263,0x5a4,0x2575,0x5d5,0x836,0xe00,0xe00,0xe00,0xe00,0xe00,0xe00,0xe00,0xe00,0xe00,0xe00,0xe00,0xe00},
  {0x413,0x213,0x86,0x540,0x511,0x530,0x402a2,0x832,0xe00,0xe00,0xe00,0xe00,0xe00,0xe00,0xe00,0xe00,0xe00,0xe00,0xe00,0xe00},
  {0x433,0x216,0x516,0x532,0x572,0x2002c5,0x20b7,0x635,0xe00,0xe00,0xe00,0xe00,0xe00,0xe00,0xe00,0xe00,0xe00,0xe00,0xe00,0xe00},
  {0x60,0xd1,0x53,0xf4,0x24a7,0x4d0,0x504,0x280,0x808002f7,0x626,0xe00,0xe00,0xe00,0xe00,0xe00,0xe00,0xe00,0xe00,0xe00,0xe00},
  {0x453,0x222,0xa5,0x4c6,0x273,0x595,0x5b0,0x802,0xe00,0xe00,0xe00,0xe00,0xe00,0xe00,0xe00,0xe00,0xe00,0xe00,0xe00,0xe00},
  {0x70,0x240,0x2477,0xff800267,0x5f2,0x835,0xe00,0xe00,0xe00,0xe00,0xe00,0xe00,0xe00,0xe00,0xe00,0xe00,0xe00,0xe00,0xe00,0xe00},
  {0x491,0x475,0x72,0x494,0x2487,0x100254,0x5e2,0x5e4,0x25e7,0x5d1,0x812f3,0x627,0xe00,0xe00,0xe00,0xe00,0xe00,0xe00,0xe00,0xe00},
  {0x80,0xe1,0x63,0x5,0x56,0x503,0x4f3,0x561,0x531,0x5e1,0x591,0x5a6,0x5b2,0x826,0xe00,0xe00,0xe00,0xe00,0xe00,0xe00},
  {0x492,0x214,0x4d6,0x4f6,0x24f4,0x808002c7,0x20c7,0x606,0xe00,0xe00,0xe00,0xe00,0xe00,0xe00,0xe00,0xe00,0xe00,0xe00,0xe00,0xe00},
  {0x90,0x236,0x292,0x5b3,0x824,0xe00,0xe00,0xe00,0xe00,0xe00,0xe00,0xe00,0xe00,0xe00,0xe00,0xe00,0xe00,0xe00,0xe00,0xe00},
  {0x404,0x223,0x96,0x100274,0x5f4,0x807,0xe00,0xe00,0xe00,0xe00,0xe00,0xe00,0xe00,0xe00,0xe00,0xe00,0xe00,0xe00,0xe00,0xe00},
  {0x424,0x221,0xb4,0x4b6,0x4b0,0x283,0x5c7,0x5d3,0x825,0xe00,0xe00,0xe00,0xe00,0xe00,0xe00,0xe00,0xe00,0xe00,0xe00,0xe00},
  {0x444,0x231,0xc4,0x80253,0x556,0x4002d6,0x1630,0xe00,0xe00,0xe00,0xe00,0xe00,0xe00,0xe00,0xe00,0xe00,0xe00,0xe00,0xe00,0xe00},
  {0xa0,0x225,0x542,0x2507,0x555,0x571,0x2c3,0x132f0,0x621,0xe00,0xe00,0xe00,0xe00,0xe00,0xe00,0xe00,0xe00,0xe00,0xe00,0xe00},
  {0x463,0x81,0xe2,0x54,0x6,0x40262,0x2b1,0x817,0xe00,0xe00,0xe00,0xe00,0xe00,0xe00,0xe00,0xe00,0xe00,0xe00,0xe00,0xe00},
  {0x414,0x493,0x2417,0x3,0x4c0,0x4e0,0x100264,0x2c1,0x402d2,0x601,0xe00,0xe00,0xe00,0xe00,0xe00,0xe00,0xe00,0xe00,0xe00,0xe00},
  {0x434,0x407,0x2437,0x13,0x74,0x4c4,0x4b5,0x24b1,0x4f7,0x581,0x5a0,0x551,0x122b0,0x811,0xe00,0xe00,0xe00,0xe00,0xe00,0xe00},
  {0x473,0xff800217,0x582,0x552,0x3e02b5,0x2097,0x615,0xe00,0xe00,0xe00,0xe00,0xe00,0xe00,0xe00,0xe00,0xe00,0xe00,0xe00,0xe00,0xe00},
  {0x405,0x230,0x14,0x266,0x2002d5,0x612,0xe00,0xe00,0xe00,0xe00,0xe00,0xe00,0xe00,0xe00,0xe00,0xe00,0xe00,0xe00,0xe00,0xe00},
  {0xb0,0xf1,0x73,0x15,0x66,0x10f6,0x2a6,0x2007,0x2047,0x620,0xe00,0xe00,0xe00,0xe00,0xe00,0xe00,0xe00,0xe00,0xe00,0xe00},
  {0xc0,0x234,0x295,0x823,0xe00,0xe00,0xe00,0xe00,0xe00,0xe00,0xe00,0xe00,0xe00,0xe00,0xe00,0xe00,0xe00,0xe00,0xe00,0xe00},
  {0xd0,0x242,0x26,0x4d2,0x4f2,0x580,0x2b3,0x2d0,0x2027,0x20e7,0xe00,0xe00,0xe00,0xe00,0xe00,0xe00,0xe00,0xe00,0xe00,0xe00},
  {0x425,0x215,0x20271,0x570,0x597,0x122c0,0x402e2,0x617,0xe00,0xe00,0xe00,0xe00,0xe00,0xe00,0xe00,0xe00,0xe00,0xe00,0xe00,0xe00},
  {0xe0,0xff800237,0x32291,0x5b4,0x810,0xe00,0xe00,0xe00,0xe00,0xe00,0xe00,0xe00,0xe00,0xe00,0xe00,0xe00,0xe00,0xe00,0xe00,0xe00},
  {0x445,0x427,0x457,0x23,0x84,0x4e2,0x4b7,0x20251,0x5a1,0x2557,0x5c5,0x5f7,0x814,0xe00,0xe00,0xe00,0xe00,0xe00,0xe00,0xe00},
  {0x483,0x232,0xb5,0x4e4,0x4d1,0x40282,0x5a7,0x5f5,0x805,0xe00,0xe00,0xe00,0xe00,0xe00,0xe00,0xe00,0xe00,0xe00,0xe00,0xe00},
  {0x464,0x91,0xf2,0x64,0x16,0x4b2,0x4f1,0x560,0x808002b7,0x2057,0x602,0xe00,0xe00,0xe00,0xe00,0xe00,0xe00,0xe00,0xe00,0xe00},
  {0x415,0xff800227,0x2527,0x404002b6,0x2087,0x605,0xe00,0xe00,0xe00,0xe00,0xe00,0xe00,0xe00,0xe00,0xe00,0xe00,0xe00,0xe00,0xe00,0xe00},
  {0xf0,0x235,0x12270,0x2b4,0x122e0,0x610,0xe00,0xe00,0xe00,0xe00,0xe00,0xe00,0xe00,0xe00,0xe00,0xe00,0xe00,0xe00,0xe00,0xe00},
  {0x435,0xa1,0x400246,0x2b2,0x801,0xe00,0xe00,0xe00,0xe00,0xe00,0xe00,0xe00,0xe00,0xe00,0xe00,0xe00,0xe00,0xe00,0xe00,0xe00},
};

struct HostState { bool init; Params p; void* out; const void* in[9]; };
HostState g_hs;

void build_state(void* const* d_in, void* d_out) {
  void* fn = nullptr;
  cudaDriverEntryPointQueryResult qr;
  cudaGetDriverEntryPoint("cuTensorMapEncodeTiled", &fn, cudaEnableDefault, &qr);
  EncodeFn enc = (EncodeFn)fn;
  void *kv, *ctx, *oA;
  cudaGetSymbolAddress(&kv, g_kv);
  cudaGetSymbolAddress(&ctx, g_ctx);
  cudaGetSymbolAddress(&oA, g_oA);
  Params& p = g_hs.p;
  make_map_2d(enc, &p.maps[M_AX], d_in[0], 2048, SEQ / 2);
  make_map_2d(enc, &p.maps[M_BX], d_in[3], 1024, SEQ);
  make_map_2d(enc, &p.maps[M_CKV], d_in[4], 512, SEQ);
  make_map_2d(enc, &p.maps[M_OA], oA, 1024, SEQ);
  make_map_2d(enc, &p.maps[M_CTX], ctx, 4096, SEQ);
  make_map_3d(enc, &p.maps[M_WQKV], d_in[1], 3072, 1024, 1024, 32, 3);
  make_map_3d(enc, &p.maps[M_WQ], d_in[5], 4096, 1024, 64, 64, 2);
  make_map_3d(enc, &p.maps[M_WUK], d_in[6], 4096, 512, 64, 64, 2);
  make_map_3d(enc, &p.maps[M_WUV], d_in[7], 4096, 512, 64, 64, 2);
  make_map_3d(enc, &p.maps[M_WOA], d_in[2], 1024, 1024, 64, 64, 2);
  make_map_3d(enc, &p.maps[M_WOB], d_in[8], 1024, 4096, 64, 64, 2);
  make_map_2d(enc, &p.maps[M_KV_LD], kv, 256, 32 * SEQ);
  make_map_3d(enc, &p.maps[M_OA_ST], oA, 1024, SEQ, 64, 64, 1);
  make_map_3d(enc, &p.maps[M_CTX_ST], ctx, 4096, SEQ, 64, 64, 2);
  make_map_3d(enc, &p.maps[M_KV_ST], kv, 256, 32 * SEQ, 64, 64, 2);
  make_map_3d(enc, &p.maps[M_OUTA_ST], d_out, 4096, SEQ / 2, 64, 64, 2);
  make_map_3d(enc, &p.maps[M_OUTB_ST], d_out, 2048, SEQ, 64, 64, 2);
  for (int c = 0; c < NPAIR; c++)
    for (int i = 0; i < MAX_ITEMS; i++) p.sched[c][i] = h_sched[c][i];
  cudaFuncSetAttribute(mega_kernel, cudaFuncAttributeMaxDynamicSharedMemorySize, SMEM_BYTES);
}

}

extern "C" void kernel_launch(void* const* d_in, const int* in_sizes, int n_in, void* d_out, int out_size) {
  (void)in_sizes; (void)n_in; (void)out_size;
  bool same = g_hs.init && g_hs.out == d_out;
  for (int i = 0; i < 9 && same; i++) same = (g_hs.in[i] == d_in[i]);
  if (!same) {
    build_state(d_in, d_out);
    g_hs.init = true; g_hs.out = d_out;
    for (int i = 0; i < 9; i++) g_hs.in[i] = d_in[i];
  }
  mega_kernel<<<NCTA, 384, SMEM_BYTES, cudaStreamPerThread>>>(g_hs.p);
}
```

```cpp
#include <cuda_runtime.h>
#include <cuda_bf16.h>
#include <cuda.h>
#include <stdint.h>

namespace {

constexpr int SEQ = 2048;
constexpr int NCTA = 132, NPAIR = 66;
constexpr int MAX_ITEMS = 20;

__device__ __align__(1024) __nv_bfloat16 g_kv[32 * SEQ * 256];
__device__ __align__(1024) __nv_bfloat16 g_ctx[SEQ * 4096];
__device__ __align__(1024) __nv_bfloat16 g_oA[SEQ * 1024];
__device__ __align__(1024) uint8_t g_halo[16 * 16 * 2048];
struct Flags { uint32_t m[64]; uint32_t epoch[NCTA]; };
__device__ __align__(128) Flags g_flags;
enum { F_KV = 0, F_CTX = 32, F_QL = 48 };

enum { K_QL = 0, K_QF = 1, K_KV = 2, K_OA = 3, K_OB = 4, K_END = 7 };
enum { M_AX = 0, M_BX, M_CKV, M_OA, M_CTX, M_WQKV, M_WQ, M_WUK, M_WOA, M_WOB, M_WUV, M_KV_LD, M_OA_ST, M_CTX_ST, M_KV_ST, M_OUTA_ST, M_OUTB_ST, M_COUNT };

struct Params {
  CUtensorMap maps[M_COUNT];
  alignas(16) uint32_t sched[NPAIR][MAX_ITEMS];
};


constexpr uint32_t SB = 1024;
constexpr uint32_t OFF_A = 0;
constexpr uint32_t OFF_B = 65536;
constexpr uint32_t OFF_STG = 196608;
constexpr uint32_t OFF_HALO = 229376;
constexpr uint32_t OFF_BAR = 231424;
constexpr uint32_t OFF_MASK = OFF_BAR + 256;
constexpr uint32_t OFF_LIST = OFF_BAR + 512;
constexpr uint32_t OFF_FILLS = OFF_BAR + 608;
constexpr uint32_t SMEM_BYTES = OFF_BAR + 640;
enum { B_FULL = 0, B_EMPTY = 4, B_QEMPTY = 8, B_STGE = 10, B_STGF = 12, B_FIN = 14, B_QFULL = 16, B_QX = 17, B_LEAD = 18, B_HFULL = 19, B_HEMPTY = 20, B_RELF = 21, B_RELE = 23, B_COUNT = 25 };
__host__ __device__ constexpr uint32_t BAR(int b) { return OFF_BAR + b * 8; }
__host__ __device__ constexpr int bar_count(int b) { return b < B_EMPTY ? 1 : b < B_QEMPTY ? 4 : b < B_STGE ? 8 : b < B_STGF ? 1 : b < B_QFULL ? 4 : b == B_QX ? 2 : 1; }
constexpr int REG_CONS = 232, REG_PROD = 40;
constexpr int PACE_MAX = 1100;
constexpr int WATCH_NS = 250;
constexpr int EARLYN = 3;
constexpr int HLATE = 3;
constexpr int STGA = 3, STGB = 8, STGAL = 4, STGBL = 12;
constexpr int JSPLIT = 14, JEDGE = 14, JP = 14, JDIAG = 10, JDIAG2 = 8;

__device__ __forceinline__ uint32_t smem_u32(const void* p) { return (uint32_t)__cvta_generic_to_shared(p); }
__device__ __forceinline__ void wg_fence() { asm volatile("wgmma.fence.sync.aligned;" ::: "memory"); }
__device__ __forceinline__ void wg_commit() { asm volatile("wgmma.commit_group.sync.aligned;" ::: "memory"); }
template <int N> __device__ __forceinline__ void wg_wait() { asm volatile("wgmma.wait_group.sync.aligned %0;" ::"n"(N) : "memory"); }
__device__ __forceinline__ uint64_t desc(uint32_t lo) { uint64_t d; asm volatile("mov.b64 %0, {%1, 0x40000040};" : "=l"(d) : "r"(lo)); return d; }
__host__ __device__ constexpr uint32_t dlo(uint32_t off, uint32_t lbo) { return (off >> 4) | ((lbo >> 4) << 16); }
template <uint32_t O> __device__ __forceinline__ void mbar_init(uint32_t a, uint32_t cnt) { asm volatile("mbarrier.init.shared::cta.b64 [%0+%2], %1;" ::"r"(a), "r"(cnt), "n"(O) : "memory"); }
template <uint32_t O> __device__ __forceinline__ void mbar_expect_tx(uint32_t a, uint32_t bytes) { asm volatile("mbarrier.arrive.expect_tx.shared::cta.b64 _, [%0+%2], %1;" ::"r"(a), "r"(bytes), "n"(O) : "memory"); }
template <uint32_t O> __device__ __forceinline__ void mbar_arrive_if(uint32_t a, bool pred) {
  asm volatile("{\n.reg .pred p;\nsetp.ne.u32 p, %1, 0;\n@p mbarrier.arrive.shared::cta.b64 _, [%0+%2];\n}\n" ::"r"(a), "r"((uint32_t)pred), "n"(O) : "memory");
}
template <uint32_t O> __device__ __forceinline__ void mbar_arrive_cl(uint32_t a, uint32_t off = 0) {
  asm volatile("{\n.reg .pred p;\nsetp.ne.u32 p, %2, 0;\n@p mbarrier.arrive.shared::cluster.b64 _, [%0+%1];\n}\n" ::"r"(a + off), "n"(O), "r"(a) : "memory");
}
template <uint32_t O> __device__ __forceinline__ bool mbar_test(uint32_t a, uint32_t parity) {
  uint32_t ok;
  asm volatile("{\n.reg .pred p;\nmbarrier.test_wait.parity.shared::cta.b64 p, [%1+%3], %2;\nselp.u32 %0, 1, 0, p;\n}\n" : "=r"(ok) : "r"(a), "r"(parity), "n"(O) : "memory");
  return ok;
}
template <uint32_t O> __device__ __forceinline__ void mbar_wait(uint32_t a, uint32_t parity) {
  asm volatile("{\n.reg .pred p;\nWAIT_%=:\nmbarrier.try_wait.parity.shared::cta.b64 p, [%0+%2], %1;\n@!p bra WAIT_%=;\n}\n" ::"r"(a), "r"(parity), "n"(O) : "memory");
}
template <uint32_t O> __device__ __forceinline__ void mbar_wait_b(uint32_t a, uint32_t parity) {
  asm volatile("{\n.reg .pred p, q;\n.reg .u32 n;\nmov.u32 n, 0;\nWAIT_%=:\nadd.u32 n, n, 1;\nmbarrier.try_wait.parity.shared::cta.b64 p, [%0+%2], %1;\n"
               "setp.lt.u32 q, n, 4194304;\nand.pred q, q, !p;\n@q bra WAIT_%=;\n@!p st.shared.u32 [%0+1], n;\n}\n" ::"r"(a), "r"(parity), "n"(O) : "memory");
}
template <uint32_t O> __device__ __forceinline__ void mbar_wait_long(uint32_t a, uint32_t parity) {
  asm volatile("{\n.reg .pred p, q;\n.reg .u32 n;\nmov.u32 n, 0;\nWAIT_%=:\nadd.u32 n, n, 1;\nmbarrier.try_wait.parity.shared::cta.b64 p, [%0+%2], %1, 4000;\n"
               "setp.lt.u32 q, n, 524288;\nand.pred q, q, !p;\n@q bra WAIT_%=;\n@!p st.shared.u32 [%0+1], n;\n}\n" ::"r"(a), "r"(parity), "n"(O) : "memory");
}
__device__ __forceinline__ void tma_load_2d(uint32_t dst, const CUtensorMap* tm, int c0, int c1, uint32_t bar) {
  asm volatile("cp.async.bulk.tensor.2d.shared::cluster.global.mbarrier::complete_tx::bytes [%0], [%1, {%3, %4}], [%2];" ::"r"(dst), "l"(tm), "r"(bar), "r"(c0), "r"(c1) : "memory");
}
__device__ __forceinline__ void tma_load_3d(uint32_t dst, const CUtensorMap* tm, int c0, int c1, int c2, uint32_t bar) {
  asm volatile("cp.async.bulk.tensor.3d.shared::cluster.global.mbarrier::complete_tx::bytes [%0], [%1, {%3, %4, %5}], [%2];" ::"r"(dst), "l"(tm), "r"(bar), "r"(c0), "r"(c1), "r"(c2) : "memory");
}
#define FILL_HEAD "{\n.reg .pred p, q;\n.reg .u32 n;\nmov.u32 n, 0;\nWAIT_%=:\nadd.u32 n, n, 1;\nmbarrier.try_wait.parity.shared::cta.b64 p, [%0+%1], %3;\n" \
                  "setp.lt.u32 q, n, 4194304;\nand.pred q, q, !p;\n@q bra WAIT_%=;\n@!p st.shared.u32 [%0+1], n;\nelect.sync _|p, 0xffffffff;\n" \
                  "@p mbarrier.arrive.expect_tx.shared::cta.b64 _, [%2], %4;\n"
__device__ __forceinline__ void fill_gemm(uint32_t bb, uint32_t parity, uint32_t bytes, uint32_t dstb, const CUtensorMap* mb, int b0, int b1, int b2, uint32_t dsta, const CUtensorMap* ma, int a0, int a1, uint64_t pb, uint64_t pa) {
  asm volatile(FILL_HEAD
               "@p cp.async.bulk.tensor.3d.shared::cluster.global.mbarrier::complete_tx::bytes.multicast::cluster.L2::cache_hint [%5], [%6, {%7, %8, %9}], [%2], %14, %15;\n"
               "@p cp.async.bulk.tensor.2d.shared::cluster.global.mbarrier::complete_tx::bytes.L2::cache_hint [%10], [%11, {%12, %13}], [%2], %16;\n}\n"
               ::"r"(bb), "n"(BAR(B_EMPTY)), "r"(bb + BAR(B_FULL)), "r"(parity), "r"(bytes), "r"(dstb), "l"(mb), "r"(b0), "r"(b1), "r"(b2), "r"(dsta), "l"(ma), "r"(a0), "r"(a1), "h"((uint16_t)3), "l"(pb), "l"(pa) : "memory");
}
__device__ __forceinline__ void fill_kv(uint32_t bb, uint32_t parity, uint32_t dst, const CUtensorMap* m, int c0, int c1, uint16_t mask, uint64_t pol) {
  asm volatile(FILL_HEAD
               "@p cp.async.bulk.tensor.2d.shared::cluster.global.mbarrier::complete_tx::bytes.multicast::cluster.L2::cache_hint [%5], [%6, {%7, %8}], [%2], %9, %10;\n}\n"
               ::"r"(bb), "n"(BAR(B_EMPTY)), "r"(bb + BAR(B_FULL)), "r"(parity), "r"(32768), "r"(dst), "l"(m), "r"(c0), "r"(c1), "h"(mask), "l"(pol) : "memory");
}
__device__ __forceinline__ void tma_load_2d_h(uint32_t dst, const CUtensorMap* tm, int c0, int c1, uint32_t bar, uint64_t pol) {
  asm volatile("{\n.reg .pred p;\nelect.sync _|p, 0xffffffff;\n@p cp.async.bulk.tensor.2d.shared::cluster.global.mbarrier::complete_tx::bytes.L2::cache_hint [%0], [%1, {%3, %4}], [%2], %5;\n}\n" ::"r"(dst), "l"(tm), "r"(bar), "r"(c0), "r"(c1), "l"(pol) : "memory");
}
__device__ __forceinline__ void tma_store_3d(const CUtensorMap* tm, uint32_t src, int c0, int c1, int c2, uint64_t pol) {
  asm volatile("{\n.reg .pred p;\nelect.sync _|p, 0xffffffff;\n@p cp.async.bulk.tensor.3d.global.shared::cta.bulk_group.L2::cache_hint [%0, {%2, %3, %4}], [%1], %5;\n}\n" ::"l"(tm), "r"(src), "r"(c0), "r"(c1), "r"(c2), "l"(pol) : "memory");
}
__device__ __forceinline__ void bulk_load(uint32_t dst, const void* src, uint32_t bytes, uint32_t bar) {
  asm volatile("{\n.reg .pred p;\nelect.sync _|p, 0xffffffff;\n@p cp.async.bulk.shared::cluster.global.mbarrier::complete_tx::bytes [%0], [%1], %2, [%3];\n}\n" ::"r"(dst), "l"(src), "r"(bytes), "r"(bar) : "memory");
}
__device__ __forceinline__ void bulk_store(void* dst, uint32_t src, uint32_t bytes) {
  asm volatile("{\n.reg .pred p;\nelect.sync _|p, 0xffffffff;\n@p cp.async.bulk.global.shared::cta.bulk_group [%0], [%1], %2;\n}\n" ::"l"(dst), "r"(src), "r"(bytes) : "memory");
}
__device__ __forceinline__ void bulk_send(uint32_t dst, uint32_t src, uint32_t bytes, uint32_t bar) {
  asm volatile("{\n.reg .pred p;\nelect.sync _|p, 0xffffffff;\n@p cp.async.bulk.shared::cluster.shared::cta.mbarrier::complete_tx::bytes [%0], [%1], %2, [%3];\n}\n" ::"r"(dst), "r"(src), "r"(bytes), "r"(bar) : "memory");
}
__device__ __forceinline__ uint64_t policy_evict_first() { uint64_t p; asm volatile("createpolicy.fractional.L2::evict_first.b64 %0, 1.0;" : "=l"(p)); return p; }
constexpr uint64_t POL_NORMAL = 0x1000000000000000ull;
__device__ __forceinline__ uint32_t mapa(uint32_t addr, uint32_t rank) { uint32_t r; asm("mapa.shared::cluster.u32 %0, %1, %2;" : "=r"(r) : "r"(addr), "r"(rank)); return r; }
__device__ __forceinline__ void cluster_arrive_relaxed() { asm volatile("barrier.cluster.arrive.relaxed.aligned;" ::: "memory"); }
__device__ __forceinline__ void cluster_arrive() { asm volatile("barrier.cluster.arrive.release.aligned;" ::: "memory"); }
__device__ __forceinline__ void cluster_wait() { asm volatile("barrier.cluster.wait.acquire.aligned;" ::: "memory"); }
__device__ __forceinline__ void bulk_commit() { asm volatile("cp.async.bulk.commit_group;" ::: "memory"); }
template <int N> __device__ __forceinline__ void bulk_wait_read() { asm volatile("cp.async.bulk.wait_group.read %0;" ::"n"(N) : "memory"); }
__device__ __forceinline__ void bulk_wait_all() { asm volatile("cp.async.bulk.wait_group 0;" ::: "memory"); }
__device__ __forceinline__ void fence_async_smem() { asm volatile("fence.proxy.async.shared::cta;" ::: "memory"); }
__device__ __forceinline__ void fence_async_glob() { asm volatile("fence.proxy.async.global;" ::: "memory"); }
__device__ __forceinline__ void flag_toggle(uint32_t* p, uint32_t v) { asm volatile("{\n.reg .pred p;\nelect.sync _|p, 0xffffffff;\n@p red.release.gpu.global.xor.b32 [%0], %1;\n}\n" ::"l"(p), "r"(v) : "memory"); }
template <uint32_t O> __device__ __forceinline__ uint32_t lds_acquire(uint32_t a) { uint32_t v; asm volatile("ld.acquire.cta.shared::cta.u32 %0, [%1+%2];" : "=r"(v) : "r"(a), "n"(O) : "memory"); return v; }
__device__ __forceinline__ uint32_t item_full(uint32_t sb, int idx) {
  uint32_t c;
  asm volatile("ld.shared.u32 %0, [%1+%2];" : "=r"(c) : "r"(sb + idx * 4), "n"(OFF_LIST));
  return __reduce_or_sync(0xffffffffu, c);
}
__device__ __forceinline__ uint32_t item(uint32_t sb, int idx) { return item_full(sb, idx) & 4095; }
template <int N> __device__ __forceinline__ void reg_alloc() { asm volatile("setmaxnreg.inc.sync.aligned.u32 %0;" ::"n"(N)); }
template <int N> __device__ __forceinline__ void reg_dealloc() { asm volatile("setmaxnreg.dec.sync.aligned.u32 %0;" ::"n"(N)); }
template <int I0, int I1, int N> __device__ __forceinline__ void fence_regs(float (&d)[N]) {
#pragma unroll
  for (int i = I0; i < I1; i++) asm volatile("" : "+f"(d[i])::"memory");
}
template <int N> __device__ __forceinline__ void fence_regs(float (&d)[N]) { fence_regs<0, N, N>(d); }
template <int N> __device__ __forceinline__ void fence_regs(uint32_t (&d)[N]) {
#pragma unroll
  for (int i = 0; i < N; i++) asm volatile("" : "+r"(d[i])::"memory");
}
__device__ __forceinline__ uint32_t pack_bf16(float lo, float hi) { uint32_t r; asm("cvt.rn.bf16x2.f32 %0, %1, %2;" : "=r"(r) : "f"(hi), "f"(lo)); return r; }
__device__ __forceinline__ uint32_t v_pack(float lo, float hi) { uint32_t r; asm volatile("cvt.rn.bf16x2.f32 %0, %1, %2;" : "=r"(r) : "f"(hi), "f"(lo)); return r; }
template <uint32_t O> __device__ __forceinline__ void stmatrix_x4(uint32_t a, uint32_t r0, uint32_t r1, uint32_t r2, uint32_t r3) {
  asm volatile("stmatrix.sync.aligned.m8n8.x4.shared.b16 [%0+%5], {%1, %2, %3, %4};" ::"r"(a), "r"(r0), "r"(r1), "r"(r2), "r"(r3), "n"(O) : "memory");
}
template <uint32_t O> __device__ __forceinline__ void stmatrix_x4_after(uint32_t a, uint32_t r0, uint32_t r1, uint32_t r2, uint32_t r3, float dep, uint32_t on) {
  asm volatile("{\n.reg .pred p, q;\n.reg .u32 a;\nsetp.ne.u32 p, %7, 0;\nsetp.ne.u32 q, %6, 0xffffffff;\nselp.u32 a, %0, 0, q;\n@p stmatrix.sync.aligned.m8n8.x4.shared.b16 [a+%5], {%1, %2, %3, %4};\n}\n"
               ::"r"(a), "r"(r0), "r"(r1), "r"(r2), "r"(r3), "n"(O), "r"(__float_as_uint(dep)), "r"(on) : "memory");
}
template <uint32_t O> __device__ __forceinline__ void stmatrix_x4_trans(uint32_t a, uint32_t r0, uint32_t r1, uint32_t r2, uint32_t r3) {
  asm volatile("stmatrix.sync.aligned.m8n8.x4.trans.shared.b16 [%0+%5], {%1, %2, %3, %4};" ::"r"(a), "r"(r0), "r"(r1), "r"(r2), "r"(r3), "n"(O) : "memory");
}
template <uint32_t O> __device__ __forceinline__ void sts64(uint32_t a, const uint32_t* r) { asm volatile("st.shared.v2.u32 [%0+%3], {%1, %2};" ::"r"(a), "r"(r[0]), "r"(r[1]), "n"(O) : "memory"); }
template <uint32_t O> __device__ __forceinline__ void lds64(uint32_t* r, uint32_t a) { asm volatile("ld.shared.v2.u32 {%0, %1}, [%2+%3];" : "=r"(r[0]), "=r"(r[1]) : "r"(a), "n"(O) : "memory"); }
template <uint32_t O> __device__ __forceinline__ void lds128(uint32_t* r, uint32_t a) { asm volatile("ld.shared.v4.u32 {%0, %1, %2, %3}, [%4+%5];" : "=r"(r[0]), "=r"(r[1]), "=r"(r[2]), "=r"(r[3]) : "r"(a), "n"(O) : "memory"); }
__device__ __forceinline__ uint32_t transpose8(uint32_t a) { uint32_t d; asm volatile("movmatrix.sync.aligned.m8n8.trans.b16 %0, %1;" : "=r"(d) : "r"(a)); return d; }
__device__ __forceinline__ float ex2(float x) { float y; asm("ex2.approx.ftz.f32 %0, %1;" : "=f"(y) : "f"(x)); return y; }
__device__ __forceinline__ float rcp(float x) { float y; asm("rcp.approx.ftz.f32 %0, %1;" : "=f"(y) : "f"(x)); return y; }
__device__ __forceinline__ void bar_sync(int id, int n) { asm volatile("bar.sync %0, %1;" ::"r"(id), "r"(n) : "memory"); }
__device__ __forceinline__ void bar_arrive(int id, int n) { asm volatile("bar.arrive %0, %1;" ::"r"(id), "r"(n) : "memory"); }
__device__ __forceinline__ void mma16816(float (&c)[4], uint32_t a0, uint32_t a1, uint32_t a2, uint32_t a3, uint32_t b0, uint32_t b1) {
  asm("mma.sync.aligned.m16n8k16.row.col.f32.bf16.bf16.f32 {%0, %1, %2, %3}, {%4, %5, %6, %7}, {%8, %9}, {%0, %1, %2, %3};"
      : "+f"(c[0]), "+f"(c[1]), "+f"(c[2]), "+f"(c[3]) : "r"(a0), "r"(a1), "r"(a2), "r"(a3), "r"(b0), "r"(b1));
}
__device__ __forceinline__ void mma16816z(float (&c)[4], uint32_t a0, uint32_t a1, uint32_t a2, uint32_t a3, uint32_t b0, uint32_t b1, const uint32_t (&z)[4]) {
  asm("mma.sync.aligned.m16n8k16.row.col.f32.bf16.bf16.f32 {%0, %1, %2, %3}, {%4, %5, %6, %7}, {%8, %9}, {%10, %11, %12, %13};"
      : "=f"(c[0]), "=f"(c[1]), "=f"(c[2]), "=f"(c[3]) : "r"(a0), "r"(a1), "r"(a2), "r"(a3), "r"(b0), "r"(b1),
        "f"(__uint_as_float(z[0])), "f"(__uint_as_float(z[1])), "f"(__uint_as_float(z[2])), "f"(__uint_as_float(z[3])));
}
__device__ __forceinline__ uint4 ldg128(const void* p) { uint4 v; asm volatile("ld.global.cg.v4.u32 {%0, %1, %2, %3}, [%4];" : "=r"(v.x), "=r"(v.y), "=r"(v.z), "=r"(v.w) : "l"(p) : "memory"); return v; }
__device__ __forceinline__ uint32_t ldg16(const void* p) { uint16_t v; asm volatile("ld.global.cg.u16 %0, [%1];" : "=h"(v) : "l"(p) : "memory"); return v; }
__device__ __forceinline__ float quad_sum(float v) {
  v += __shfl_xor_sync(0xffffffffu, v, 1);
  v += __shfl_xor_sync(0xffffffffu, v, 2);
  return v;
}
__device__ __forceinline__ bool elect_one() { uint32_t p; asm volatile("{\n.reg .pred p;\nelect.sync _|p, 0xffffffff;\nselp.u32 %0, 1, 0, p;\n}\n" : "=r"(p)); return p; }
#define UNLIKELY(x) __builtin_expect(!!(x), 0)

template <int OA, int OB> __device__ __forceinline__ void wg_gemm_init(float (&d)[128], uint64_t da, uint64_t db) {
  asm volatile("{\n.reg .pred p;\n.reg .b64 da, db;\nadd.s64 da, %128, %129;\nadd.s64 db, %130, %131;\nsetp.ne.b32 p, 0, 0;\n"
    "wgmma.mma_async.sync.aligned.m64n256k16.f32.bf16.bf16 {"
    "%0, %1, %2, %3, %4, %5, %6, %7, %8, %9, %10, %11, %12, %13, %14, %15, %16, %17, %18, %19, %20, %21, %22, %23, %24, %25, %26, %27, %28, %29, %30, %31, "
    "%32, %33, %34, %35, %36, %37, %38, %39, %40, %41, %42, %43, %44, %45, %46, %47, %48, %49, %50, %51, %52, %53, %54, %55, %56, %57, %58, %59, %60, %61, %62, %63, "
    "%64, %65, %66, %67, %68, %69, %70, %71, %72, %73, %74, %75, %76, %77, %78, %79, %80, %81, %82, %83, %84, %85, %86, %87, %88, %89, %90, %91, %92, %93, %94, %95, "
    "%96, %97, %98, %99, %100, %101, %102, %103, %104, %105, %106, %107, %108, %109, %110, %111, %112, %113, %114, %115, %116, %117, %118, %119, %120, %121, %122, %123, %124, %125, %126, %127}, "
    "da, db, p, 1, 1, 0, 1;\n}\n"
    : "=f"(d[0]), "=f"(d[1]), "=f"(d[2]), "=f"(d[3]), "=f"(d[4]), "=f"(d[5]), "=f"(d[6]), "=f"(d[7]), "=f"(d[8]), "=f"(d[9]), "=f"(d[10]), "=f"(d[11]), "=f"(d[12]), "=f"(d[13]), "=f"(d[14]), "=f"(d[15]),
      "=f"(d[16]), "=f"(d[17]), "=f"(d[18]), "=f"(d[19]), "=f"(d[20]), "=f"(d[21]), "=f"(d[22]), "=f"(d[23]), "=f"(d[24]), "=f"(d[25]), "=f"(d[26]), "=f"(d[27]), "=f"(d[28]), "=f"(d[29]), "=f"(d[30]), "=f"(d[31]),
      "=f"(d[32]), "=f"(d[33]), "=f"(d[34]), "=f"(d[35]), "=f"(d[36]), "=f"(d[37]), "=f"(d[38]), "=f"(d[39]), "=f"(d[40]), "=f"(d[41]), "=f"(d[42]), "=f"(d[43]), "=f"(d[44]), "=f"(d[45]), "=f"(d[46]), "=f"(d[47]),
      "=f"(d[48]), "=f"(d[49]), "=f"(d[50]), "=f"(d[51]), "=f"(d[52]), "=f"(d[53]), "=f"(d[54]), "=f"(d[55]), "=f"(d[56]), "=f"(d[57]), "=f"(d[58]), "=f"(d[59]), "=f"(d[60]), "=f"(d[61]), "=f"(d[62]), "=f"(d[63]),
      "=f"(d[64]), "=f"(d[65]), "=f"(d[66]), "=f"(d[67]), "=f"(d[68]), "=f"(d[69]), "=f"(d[70]), "=f"(d[71]), "=f"(d[72]), "=f"(d[73]), "=f"(d[74]), "=f"(d[75]), "=f"(d[76]), "=f"(d[77]), "=f"(d[78]), "=f"(d[79]),
      "=f"(d[80]), "=f"(d[81]), "=f"(d[82]), "=f"(d[83]), "=f"(d[84]), "=f"(d[85]), "=f"(d[86]), "=f"(d[87]), "=f"(d[88]), "=f"(d[89]), "=f"(d[90]), "=f"(d[91]), "=f"(d[92]), "=f"(d[93]), "=f"(d[94]), "=f"(d[95]),
      "=f"(d[96]), "=f"(d[97]), "=f"(d[98]), "=f"(d[99]), "=f"(d[100]), "=f"(d[101]), "=f"(d[102]), "=f"(d[103]), "=f"(d[104]), "=f"(d[105]), "=f"(d[106]), "=f"(d[107]), "=f"(d[108]), "=f"(d[109]), "=f"(d[110]), "=f"(d[111]),
      "=f"(d[112]), "=f"(d[113]), "=f"(d[114]), "=f"(d[115]), "=f"(d[116]), "=f"(d[117]), "=f"(d[118]), "=f"(d[119]), "=f"(d[120]), "=f"(d[121]), "=f"(d[122]), "=f"(d[123]), "=f"(d[124]), "=f"(d[125]), "=f"(d[126]), "=f"(d[127])
    : "l"(da), "n"(OA), "l"(db), "n"(OB));
}
template <int OA, int OB> __device__ __forceinline__ void wg_gemm_acc(float (&d)[128], uint64_t da, uint64_t db) {
  asm volatile("{\n.reg .pred p;\n.reg .b64 da, db;\nadd.s64 da, %128, %129;\nadd.s64 db, %130, %131;\nsetp.eq.b32 p, 0, 0;\n"
    "wgmma.mma_async.sync.aligned.m64n256k16.f32.bf16.bf16 {"
    "%0, %1, %2, %3, %4, %5, %6, %7, %8, %9, %10, %11, %12, %13, %14, %15, %16, %17, %18, %19, %20, %21, %22, %23, %24, %25, %26, %27, %28, %29, %30, %31, "
    "%32, %33, %34, %35, %36, %37, %38, %39, %40, %41, %42, %43, %44, %45, %46, %47, %48, %49, %50, %51, %52, %53, %54, %55, %56, %57, %58, %59, %60, %61, %62, %63, "
    "%64, %65, %66, %67, %68, %69, %70, %71, %72, %73, %74, %75, %76, %77, %78, %79, %80, %81, %82, %83, %84, %85, %86, %87, %88, %89, %90, %91, %92, %93, %94, %95, "
    "%96, %97, %98, %99, %100, %101, %102, %103, %104, %105, %106, %107, %108, %109, %110, %111, %112, %113, %114, %115, %116, %117, %118, %119, %120, %121, %122, %123, %124, %125, %126, %127}, "
    "da, db, p, 1, 1, 0, 1;\n}\n"
    : "+f"(d[0]), "+f"(d[1]), "+f"(d[2]), "+f"(d[3]), "+f"(d[4]), "+f"(d[5]), "+f"(d[6]), "+f"(d[7]), "+f"(d[8]), "+f"(d[9]), "+f"(d[10]), "+f"(d[11]), "+f"(d[12]), "+f"(d[13]), "+f"(d[14]), "+f"(d[15]),
      "+f"(d[16]), "+f"(d[17]), "+f"(d[18]), "+f"(d[19]), "+f"(d[20]), "+f"(d[21]), "+f"(d[22]), "+f"(d[23]), "+f"(d[24]), "+f"(d[25]), "+f"(d[26]), "+f"(d[27]), "+f"(d[28]), "+f"(d[29]), "+f"(d[30]), "+f"(d[31]),
      "+f"(d[32]), "+f"(d[33]), "+f"(d[34]), "+f"(d[35]), "+f"(d[36]), "+f"(d[37]), "+f"(d[38]), "+f"(d[39]), "+f"(d[40]), "+f"(d[41]), "+f"(d[42]), "+f"(d[43]), "+f"(d[44]), "+f"(d[45]), "+f"(d[46]), "+f"(d[47]),
      "+f"(d[48]), "+f"(d[49]), "+f"(d[50]), "+f"(d[51]), "+f"(d[52]), "+f"(d[53]), "+f"(d[54]), "+f"(d[55]), "+f"(d[56]), "+f"(d[57]), "+f"(d[58]), "+f"(d[59]), "+f"(d[60]), "+f"(d[61]), "+f"(d[62]), "+f"(d[63]),
      "+f"(d[64]), "+f"(d[65]), "+f"(d[66]), "+f"(d[67]), "+f"(d[68]), "+f"(d[69]), "+f"(d[70]), "+f"(d[71]), "+f"(d[72]), "+f"(d[73]), "+f"(d[74]), "+f"(d[75]), "+f"(d[76]), "+f"(d[77]), "+f"(d[78]), "+f"(d[79]),
      "+f"(d[80]), "+f"(d[81]), "+f"(d[82]), "+f"(d[83]), "+f"(d[84]), "+f"(d[85]), "+f"(d[86]), "+f"(d[87]), "+f"(d[88]), "+f"(d[89]), "+f"(d[90]), "+f"(d[91]), "+f"(d[92]), "+f"(d[93]), "+f"(d[94]), "+f"(d[95]),
      "+f"(d[96]), "+f"(d[97]), "+f"(d[98]), "+f"(d[99]), "+f"(d[100]), "+f"(d[101]), "+f"(d[102]), "+f"(d[103]), "+f"(d[104]), "+f"(d[105]), "+f"(d[106]), "+f"(d[107]), "+f"(d[108]), "+f"(d[109]), "+f"(d[110]), "+f"(d[111]),
      "+f"(d[112]), "+f"(d[113]), "+f"(d[114]), "+f"(d[115]), "+f"(d[116]), "+f"(d[117]), "+f"(d[118]), "+f"(d[119]), "+f"(d[120]), "+f"(d[121]), "+f"(d[122]), "+f"(d[123]), "+f"(d[124]), "+f"(d[125]), "+f"(d[126]), "+f"(d[127])
    : "l"(da), "n"(OA), "l"(db), "n"(OB));
}
template <int OA, int OB> __device__ __forceinline__ void wg_gemm_init(float (&d)[96], uint64_t da, uint64_t db) {
  asm volatile("{\n.reg .pred p;\n.reg .b64 da, db;\nadd.s64 da, %96, %97;\nadd.s64 db, %98, %99;\nsetp.ne.b32 p, 0, 0;\n"
    "wgmma.mma_async.sync.aligned.m64n192k16.f32.bf16.bf16 {"
    "%0, %1, %2, %3, %4, %5, %6, %7, %8, %9, %10, %11, %12, %13, %14, %15, %16, %17, %18, %19, %20, %21, %22, %23, %24, %25, %26, %27, %28, %29, %30, %31, "
    "%32, %33, %34, %35, %36, %37, %38, %39, %40, %41, %42, %43, %44, %45, %46, %47, %48, %49, %50, %51, %52, %53, %54, %55, %56, %57, %58, %59, %60, %61, %62, %63, "
    "%64, %65, %66, %67, %68, %69, %70, %71, %72, %73, %74, %75, %76, %77, %78, %79, %80, %81, %82, %83, %84, %85, %86, %87, %88, %89, %90, %91, %92, %93, %94, %95}, "
    "da, db, p, 1, 1, 0, 1;\n}\n"
    : "=f"(d[0]), "=f"(d[1]), "=f"(d[2]), "=f"(d[3]), "=f"(d[4]), "=f"(d[5]), "=f"(d[6]), "=f"(d[7]), "=f"(d[8]), "=f"(d[9]), "=f"(d[10]), "=f"(d[11]), "=f"(d[12]), "=f"(d[13]), "=f"(d[14]), "=f"(d[15]),
      "=f"(d[16]), "=f"(d[17]), "=f"(d[18]), "=f"(d[19]), "=f"(d[20]), "=f"(d[21]), "=f"(d[22]), "=f"(d[23]), "=f"(d[24]), "=f"(d[25]), "=f"(d[26]), "=f"(d[27]), "=f"(d[28]), "=f"(d[29]), "=f"(d[30]), "=f"(d[31]),
      "=f"(d[32]), "=f"(d[33]), "=f"(d[34]), "=f"(d[35]), "=f"(d[36]), "=f"(d[37]), "=f"(d[38]), "=f"(d[39]), "=f"(d[40]), "=f"(d[41]), "=f"(d[42]), "=f"(d[43]), "=f"(d[44]), "=f"(d[45]), "=f"(d[46]), "=f"(d[47]),
      "=f"(d[48]), "=f"(d[49]), "=f"(d[50]), "=f"(d[51]), "=f"(d[52]), "=f"(d[53]), "=f"(d[54]), "=f"(d[55]), "=f"(d[56]), "=f"(d[57]), "=f"(d[58]), "=f"(d[59]), "=f"(d[60]), "=f"(d[61]), "=f"(d[62]), "=f"(d[63]),
      "=f"(d[64]), "=f"(d[65]), "=f"(d[66]), "=f"(d[67]), "=f"(d[68]), "=f"(d[69]), "=f"(d[70]), "=f"(d[71]), "=f"(d[72]), "=f"(d[73]), "=f"(d[74]), "=f"(d[75]), "=f"(d[76]), "=f"(d[77]), "=f"(d[78]), "=f"(d[79]),
      "=f"(d[80]), "=f"(d[81]), "=f"(d[82]), "=f"(d[83]), "=f"(d[84]), "=f"(d[85]), "=f"(d[86]), "=f"(d[87]), "=f"(d[88]), "=f"(d[89]), "=f"(d[90]), "=f"(d[91]), "=f"(d[92]), "=f"(d[93]), "=f"(d[94]), "=f"(d[95])
    : "l"(da), "n"(OA), "l"(db), "n"(OB));
}
template <int OA, int OB> __device__ __forceinline__ void wg_gemm_acc(float (&d)[96], uint64_t da, uint64_t db) {
  asm volatile("{\n.reg .pred p;\n.reg .b64 da, db;\nadd.s64 da, %96, %97;\nadd.s64 db, %98, %99;\nsetp.eq.b32 p, 0, 0;\n"
    "wgmma.mma_async.sync.aligned.m64n192k16.f32.bf16.bf16 {"
    "%0, %1, %2, %3, %4, %5, %6, %7, %8, %9, %10, %11, %12, %13, %14, %15, %16, %17, %18, %19, %20, %21, %22, %23, %24, %25, %26, %27, %28, %29, %30, %31, "
    "%32, %33, %34, %35, %36, %37, %38, %39, %40, %41, %42, %43, %44, %45, %46, %47, %48, %49, %50, %51, %52, %53, %54, %55, %56, %57, %58, %59, %60, %61, %62, %63, "
    "%64, %65, %66, %67, %68, %69, %70, %71, %72, %73, %74, %75, %76, %77, %78, %79, %80, %81, %82, %83, %84, %85, %86, %87, %88, %89, %90, %91, %92, %93, %94, %95}, "
    "da, db, p, 1, 1, 0, 1;\n}\n"
    : "+f"(d[0]), "+f"(d[1]), "+f"(d[2]), "+f"(d[3]), "+f"(d[4]), "+f"(d[5]), "+f"(d[6]), "+f"(d[7]), "+f"(d[8]), "+f"(d[9]), "+f"(d[10]), "+f"(d[11]), "+f"(d[12]), "+f"(d[13]), "+f"(d[14]), "+f"(d[15]),
      "+f"(d[16]), "+f"(d[17]), "+f"(d[18]), "+f"(d[19]), "+f"(d[20]), "+f"(d[21]), "+f"(d[22]), "+f"(d[23]), "+f"(d[24]), "+f"(d[25]), "+f"(d[26]), "+f"(d[27]), "+f"(d[28]), "+f"(d[29]), "+f"(d[30]), "+f"(d[31]),
      "+f"(d[32]), "+f"(d[33]), "+f"(d[34]), "+f"(d[35]), "+f"(d[36]), "+f"(d[37]), "+f"(d[38]), "+f"(d[39]), "+f"(d[40]), "+f"(d[41]), "+f"(d[42]), "+f"(d[43]), "+f"(d[44]), "+f"(d[45]), "+f"(d[46]), "+f"(d[47]),
      "+f"(d[48]), "+f"(d[49]), "+f"(d[50]), "+f"(d[51]), "+f"(d[52]), "+f"(d[53]), "+f"(d[54]), "+f"(d[55]), "+f"(d[56]), "+f"(d[57]), "+f"(d[58]), "+f"(d[59]), "+f"(d[60]), "+f"(d[61]), "+f"(d[62]), "+f"(d[63]),
      "+f"(d[64]), "+f"(d[65]), "+f"(d[66]), "+f"(d[67]), "+f"(d[68]), "+f"(d[69]), "+f"(d[70]), "+f"(d[71]), "+f"(d[72]), "+f"(d[73]), "+f"(d[74]), "+f"(d[75]), "+f"(d[76]), "+f"(d[77]), "+f"(d[78]), "+f"(d[79]),
      "+f"(d[80]), "+f"(d[81]), "+f"(d[82]), "+f"(d[83]), "+f"(d[84]), "+f"(d[85]), "+f"(d[86]), "+f"(d[87]), "+f"(d[88]), "+f"(d[89]), "+f"(d[90]), "+f"(d[91]), "+f"(d[92]), "+f"(d[93]), "+f"(d[94]), "+f"(d[95])
    : "l"(da), "n"(OA), "l"(db), "n"(OB));
}
template <int OA, int OB> __device__ __forceinline__ void wg_qk_init(float (&d)[64], uint64_t da, uint64_t db) {
  asm volatile("{\n.reg .pred p;\n.reg .b64 da, db;\nadd.s64 da, %64, %65;\nadd.s64 db, %66, %67;\nsetp.ne.b32 p, 0, 0;\n"
    "wgmma.mma_async.sync.aligned.m64n128k16.f32.bf16.bf16 {"
    "%0, %1, %2, %3, %4, %5, %6, %7, %8, %9, %10, %11, %12, %13, %14, %15, %16, %17, %18, %19, %20, %21, %22, %23, %24, %25, %26, %27, %28, %29, %30, %31, "
    "%32, %33, %34, %35, %36, %37, %38, %39, %40, %41, %42, %43, %44, %45, %46, %47, %48, %49, %50, %51, %52, %53, %54, %55, %56, %57, %58, %59, %60, %61, %62, %63}, "
    "da, db, p, 1, 1, 0, 0;\n}\n"
    : "=f"(d[0]), "=f"(d[1]), "=f"(d[2]), "=f"(d[3]), "=f"(d[4]), "=f"(d[5]), "=f"(d[6]), "=f"(d[7]), "=f"(d[8]), "=f"(d[9]), "=f"(d[10]), "=f"(d[11]), "=f"(d[12]), "=f"(d[13]), "=f"(d[14]), "=f"(d[15]),
      "=f"(d[16]), "=f"(d[17]), "=f"(d[18]), "=f"(d[19]), "=f"(d[20]), "=f"(d[21]), "=f"(d[22]), "=f"(d[23]), "=f"(d[24]), "=f"(d[25]), "=f"(d[26]), "=f"(d[27]), "=f"(d[28]), "=f"(d[29]), "=f"(d[30]), "=f"(d[31]),
      "=f"(d[32]), "=f"(d[33]), "=f"(d[34]), "=f"(d[35]), "=f"(d[36]), "=f"(d[37]), "=f"(d[38]), "=f"(d[39]), "=f"(d[40]), "=f"(d[41]), "=f"(d[42]), "=f"(d[43]), "=f"(d[44]), "=f"(d[45]), "=f"(d[46]), "=f"(d[47]),
      "=f"(d[48]), "=f"(d[49]), "=f"(d[50]), "=f"(d[51]), "=f"(d[52]), "=f"(d[53]), "=f"(d[54]), "=f"(d[55]), "=f"(d[56]), "=f"(d[57]), "=f"(d[58]), "=f"(d[59]), "=f"(d[60]), "=f"(d[61]), "=f"(d[62]), "=f"(d[63])
    : "l"(da), "n"(OA), "l"(db), "n"(OB));
}
template <int OA, int OB> __device__ __forceinline__ void wg_qk_acc(float (&d)[64], uint64_t da, uint64_t db) {
  asm volatile("{\n.reg .pred p;\n.reg .b64 da, db;\nadd.s64 da, %64, %65;\nadd.s64 db, %66, %67;\nsetp.eq.b32 p, 0, 0;\n"
    "wgmma.mma_async.sync.aligned.m64n128k16.f32.bf16.bf16 {"
    "%0, %1, %2, %3, %4, %5, %6, %7, %8, %9, %10, %11, %12, %13, %14, %15, %16, %17, %18, %19, %20, %21, %22, %23, %24, %25, %26, %27, %28, %29, %30, %31, "
    "%32, %33, %34, %35, %36, %37, %38, %39, %40, %41, %42, %43, %44, %45, %46, %47, %48, %49, %50, %51, %52, %53, %54, %55, %56, %57, %58, %59, %60, %61, %62, %63}, "
    "da, db, p, 1, 1, 0, 0;\n}\n"
    : "+f"(d[0]), "+f"(d[1]), "+f"(d[2]), "+f"(d[3]), "+f"(d[4]), "+f"(d[5]), "+f"(d[6]), "+f"(d[7]), "+f"(d[8]), "+f"(d[9]), "+f"(d[10]), "+f"(d[11]), "+f"(d[12]), "+f"(d[13]), "+f"(d[14]), "+f"(d[15]),
      "+f"(d[16]), "+f"(d[17]), "+f"(d[18]), "+f"(d[19]), "+f"(d[20]), "+f"(d[21]), "+f"(d[22]), "+f"(d[23]), "+f"(d[24]), "+f"(d[25]), "+f"(d[26]), "+f"(d[27]), "+f"(d[28]), "+f"(d[29]), "+f"(d[30]), "+f"(d[31]),
      "+f"(d[32]), "+f"(d[33]), "+f"(d[34]), "+f"(d[35]), "+f"(d[36]), "+f"(d[37]), "+f"(d[38]), "+f"(d[39]), "+f"(d[40]), "+f"(d[41]), "+f"(d[42]), "+f"(d[43]), "+f"(d[44]), "+f"(d[45]), "+f"(d[46]), "+f"(d[47]),
      "+f"(d[48]), "+f"(d[49]), "+f"(d[50]), "+f"(d[51]), "+f"(d[52]), "+f"(d[53]), "+f"(d[54]), "+f"(d[55]), "+f"(d[56]), "+f"(d[57]), "+f"(d[58]), "+f"(d[59]), "+f"(d[60]), "+f"(d[61]), "+f"(d[62]), "+f"(d[63])
    : "l"(da), "n"(OA), "l"(db), "n"(OB));
}
template <int OA, int OB> __device__ __forceinline__ void wg_qk64_init(float (&d)[64], uint64_t da, uint64_t db) {
  asm volatile("{\n.reg .pred p;\n.reg .b64 da, db;\nadd.s64 da, %32, %33;\nadd.s64 db, %34, %35;\nsetp.ne.b32 p, 0, 0;\n"
    "wgmma.mma_async.sync.aligned.m64n64k16.f32.bf16.bf16 {"
    "%0, %1, %2, %3, %4, %5, %6, %7, %8, %9, %10, %11, %12, %13, %14, %15, %16, %17, %18, %19, %20, %21, %22, %23, %24, %25, %26, %27, %28, %29, %30, %31}, "
    "da, db, p, 1, 1, 0, 0;\n}\n"
    : "=f"(d[0]), "=f"(d[1]), "=f"(d[2]), "=f"(d[3]), "=f"(d[4]), "=f"(d[5]), "=f"(d[6]), "=f"(d[7]), "=f"(d[8]), "=f"(d[9]), "=f"(d[10]), "=f"(d[11]), "=f"(d[12]), "=f"(d[13]), "=f"(d[14]), "=f"(d[15]),
      "=f"(d[16]), "=f"(d[17]), "=f"(d[18]), "=f"(d[19]), "=f"(d[20]), "=f"(d[21]), "=f"(d[22]), "=f"(d[23]), "=f"(d[24]), "=f"(d[25]), "=f"(d[26]), "=f"(d[27]), "=f"(d[28]), "=f"(d[29]), "=f"(d[30]), "=f"(d[31])
    : "l"(da), "n"(OA), "l"(db), "n"(OB));
}
template <int OA, int OB> __device__ __forceinline__ void wg_qk64_acc(float (&d)[64], uint64_t da, uint64_t db) {
  asm volatile("{\n.reg .pred p;\n.reg .b64 da, db;\nadd.s64 da, %32, %33;\nadd.s64 db, %34, %35;\nsetp.eq.b32 p, 0, 0;\n"
    "wgmma.mma_async.sync.aligned.m64n64k16.f32.bf16.bf16 {"
    "%0, %1, %2, %3, %4, %5, %6, %7, %8, %9, %10, %11, %12, %13, %14, %15, %16, %17, %18, %19, %20, %21, %22, %23, %24, %25, %26, %27, %28, %29, %30, %31}, "
    "da, db, p, 1, 1, 0, 0;\n}\n"
    : "+f"(d[0]), "+f"(d[1]), "+f"(d[2]), "+f"(d[3]), "+f"(d[4]), "+f"(d[5]), "+f"(d[6]), "+f"(d[7]), "+f"(d[8]), "+f"(d[9]), "+f"(d[10]), "+f"(d[11]), "+f"(d[12]), "+f"(d[13]), "+f"(d[14]), "+f"(d[15]),
      "+f"(d[16]), "+f"(d[17]), "+f"(d[18]), "+f"(d[19]), "+f"(d[20]), "+f"(d[21]), "+f"(d[22]), "+f"(d[23]), "+f"(d[24]), "+f"(d[25]), "+f"(d[26]), "+f"(d[27]), "+f"(d[28]), "+f"(d[29]), "+f"(d[30]), "+f"(d[31])
    : "l"(da), "n"(OA), "l"(db), "n"(OB));
}
template <int OB> __device__ __forceinline__ void wg_pv_init(float (&d)[64], const uint32_t* a, uint64_t db) {
  asm volatile("{\n.reg .pred p;\n.reg .b64 da, db;\nadd.s64 db, %68, %69;\nsetp.ne.b32 p, 0, 0;\n"
    "wgmma.mma_async.sync.aligned.m64n128k16.f32.bf16.bf16 {"
    "%0, %1, %2, %3, %4, %5, %6, %7, %8, %9, %10, %11, %12, %13, %14, %15, %16, %17, %18, %19, %20, %21, %22, %23, %24, %25, %26, %27, %28, %29, %30, %31, "
    "%32, %33, %34, %35, %36, %37, %38, %39, %40, %41, %42, %43, %44, %45, %46, %47, %48, %49, %50, %51, %52, %53, %54, %55, %56, %57, %58, %59, %60, %61, %62, %63}, "
    "{%64, %65, %66, %67}, db, p, 1, 1, 1;\n}\n"
    : "=f"(d[0]), "=f"(d[1]), "=f"(d[2]), "=f"(d[3]), "=f"(d[4]), "=f"(d[5]), "=f"(d[6]), "=f"(d[7]), "=f"(d[8]), "=f"(d[9]), "=f"(d[10]), "=f"(d[11]), "=f"(d[12]), "=f"(d[13]), "=f"(d[14]), "=f"(d[15]),
      "=f"(d[16]), "=f"(d[17]), "=f"(d[18]), "=f"(d[19]), "=f"(d[20]), "=f"(d[21]), "=f"(d[22]), "=f"(d[23]), "=f"(d[24]), "=f"(d[25]), "=f"(d[26]), "=f"(d[27]), "=f"(d[28]), "=f"(d[29]), "=f"(d[30]), "=f"(d[31]),
      "=f"(d[32]), "=f"(d[33]), "=f"(d[34]), "=f"(d[35]), "=f"(d[36]), "=f"(d[37]), "=f"(d[38]), "=f"(d[39]), "=f"(d[40]), "=f"(d[41]), "=f"(d[42]), "=f"(d[43]), "=f"(d[44]), "=f"(d[45]), "=f"(d[46]), "=f"(d[47]),
      "=f"(d[48]), "=f"(d[49]), "=f"(d[50]), "=f"(d[51]), "=f"(d[52]), "=f"(d[53]), "=f"(d[54]), "=f"(d[55]), "=f"(d[56]), "=f"(d[57]), "=f"(d[58]), "=f"(d[59]), "=f"(d[60]), "=f"(d[61]), "=f"(d[62]), "=f"(d[63])
    : "r"(a[0]), "r"(a[1]), "r"(a[2]), "r"(a[3]), "l"(db), "n"(OB));
}
template <int OB> __device__ __forceinline__ void wg_pv_acc(float (&d)[64], const uint32_t* a, uint64_t db) {
  asm volatile("{\n.reg .pred p;\n.reg .b64 da, db;\nadd.s64 db, %68, %69;\nsetp.eq.b32 p, 0, 0;\n"
    "wgmma.mma_async.sync.aligned.m64n128k16.f32.bf16.bf16 {"
    "%0, %1, %2, %3, %4, %5, %6, %7, %8, %9, %10, %11, %12, %13, %14, %15, %16, %17, %18, %19, %20, %21, %22, %23, %24, %25, %26, %27, %28, %29, %30, %31, "
    "%32, %33, %34, %35, %36, %37, %38, %39, %40, %41, %42, %43, %44, %45, %46, %47, %48, %49, %50, %51, %52, %53, %54, %55, %56, %57, %58, %59, %60, %61, %62, %63}, "
    "{%64, %65, %66, %67}, db, p, 1, 1, 1;\n}\n"
    : "+f"(d[0]), "+f"(d[1]), "+f"(d[2]), "+f"(d[3]), "+f"(d[4]), "+f"(d[5]), "+f"(d[6]), "+f"(d[7]), "+f"(d[8]), "+f"(d[9]), "+f"(d[10]), "+f"(d[11]), "+f"(d[12]), "+f"(d[13]), "+f"(d[14]), "+f"(d[15]),
      "+f"(d[16]), "+f"(d[17]), "+f"(d[18]), "+f"(d[19]), "+f"(d[20]), "+f"(d[21]), "+f"(d[22]), "+f"(d[23]), "+f"(d[24]), "+f"(d[25]), "+f"(d[26]), "+f"(d[27]), "+f"(d[28]), "+f"(d[29]), "+f"(d[30]), "+f"(d[31]),
      "+f"(d[32]), "+f"(d[33]), "+f"(d[34]), "+f"(d[35]), "+f"(d[36]), "+f"(d[37]), "+f"(d[38]), "+f"(d[39]), "+f"(d[40]), "+f"(d[41]), "+f"(d[42]), "+f"(d[43]), "+f"(d[44]), "+f"(d[45]), "+f"(d[46]), "+f"(d[47]),
      "+f"(d[48]), "+f"(d[49]), "+f"(d[50]), "+f"(d[51]), "+f"(d[52]), "+f"(d[53]), "+f"(d[54]), "+f"(d[55]), "+f"(d[56]), "+f"(d[57]), "+f"(d[58]), "+f"(d[59]), "+f"(d[60]), "+f"(d[61]), "+f"(d[62]), "+f"(d[63])
    : "r"(a[0]), "r"(a[1]), "r"(a[2]), "r"(a[3]), "l"(db), "n"(OB));
}

struct Cons {
  uint32_t d0, da;
  uint32_t sb;
  uint32_t rel;
  uint32_t p0, p1;
  uint32_t lead, round, fpar;
};

template <uint32_t OFF, uint32_t GROUP> __device__ __forceinline__ void tile_write(const uint32_t (&pk)[32], uint32_t base) {
  const uint32_t lane = threadIdx.x & 31, wq = (threadIdx.x >> 5) & 3;
  const uint32_t a = base + (wq * 16 + (lane & 15)) * 128 + (((lane >> 4) ^ (lane & 7)) << 4);
#define TW(j) stmatrix_x4<OFF + (j >> 2) * GROUP>(a ^ ((j & 3) * 32), pk[4 * j + 0], pk[4 * j + 1], pk[4 * j + 2], pk[4 * j + 3])
  TW(0); TW(1); TW(2); TW(3); TW(4); TW(5); TW(6); TW(7);
#undef TW
}
template <uint32_t OFF, uint32_t GROUP, int A0> __device__ __forceinline__ void tile_pack_write(const float (&acc)[128], uint32_t (&pk)[32], uint32_t base) {
  const uint32_t lane = threadIdx.x & 31, wq = (threadIdx.x >> 5) & 3;
  const uint32_t a = base + (wq * 16 + (lane & 15)) * 128 + (((lane >> 4) ^ (lane & 7)) << 4);
#define TW(j) \
  pk[4 * j + 0] = v_pack(acc[A0 + 8 * j + 0], acc[A0 + 8 * j + 1]); pk[4 * j + 1] = v_pack(acc[A0 + 8 * j + 2], acc[A0 + 8 * j + 3]); \
  pk[4 * j + 2] = v_pack(acc[A0 + 8 * j + 4], acc[A0 + 8 * j + 5]); pk[4 * j + 3] = v_pack(acc[A0 + 8 * j + 6], acc[A0 + 8 * j + 7]); \
  stmatrix_x4<OFF + (j >> 2) * GROUP>(a ^ ((j & 3) * 32), pk[4 * j + 0], pk[4 * j + 1], pk[4 * j + 2], pk[4 * j + 3])
  TW(0); TW(1); TW(2); TW(3); TW(4); TW(5); TW(6); TW(7);
#undef TW
}
__device__ __forceinline__ void stage_write(const uint32_t (&pk)[32], int w, const Cons& cs) {
  mbar_wait<BAR(B_STGE)>(cs.sb + w * 8, (cs.round & 1) ^ 1);
  tile_write<OFF_STG, 8192>(pk, cs.sb + w * 16384);
}
__device__ __forceinline__ void stage_publish(int w, Cons& cs) {
  fence_async_smem();
  __syncwarp();
  mbar_arrive_if<BAR(B_STGF)>(cs.sb + w * 8, (threadIdx.x & 31) == 0);
  cs.round++;
}

template <int ST, bool INIT, bool FIRST = INIT, int NA> __device__ __forceinline__ void g_issue(float (&acc)[NA], const Cons& cs) {
  constexpr int B2 = NA == 128 ? 256 : 768, Z = FIRST ? 128 : 0;
  uint32_t a, b;
  asm volatile("add.u32 %0, %2, %4;\nadd.u32 %1, %3, %5;" : "=r"(a), "=r"(b) : "r"(cs.da), "r"(cs.d0), "n"(dlo(OFF_A + ST * 16384, NA + (FIRST ? 16 : 0))), "n"(dlo(OFF_B + ST * 32768, NA == 128 ? 8192 : 4096) + Z));
  const uint64_t A = desc(a), B = desc(b);
  wg_fence();
  if (INIT) wg_gemm_init<0, -Z>(acc, A, B); else wg_gemm_acc<0, -Z>(acc, A, B);
  wg_gemm_acc<2, 128 - Z>(acc, A, B);
  wg_gemm_acc<4, B2 - Z>(acc, A, B);
  wg_gemm_acc<6, B2 + 128 - Z>(acc, A, B);
  wg_commit();
}
template <int NA, class F>
__device__ __forceinline__ uint32_t gemm_tile(float (&acc)[NA], int nk4, int idx, int w, Cons& cs, uint32_t pend, const uint32_t (&pkA)[32], const uint32_t (&pkB)[32], F&& before_end) {
  const uint32_t sb = cs.sb, rel = cs.rel;
  constexpr int SA = NA == 128 ? STGA : STGAL, SBB = NA == 128 ? STGB : STGBL;
#define HOOK(n) \
  if (n == 0 && (pend & 8)) stage_publish(w, cs); \
  if (n == 0 && (pend & 16) && w == 0) bar_sync(5, 256); \
  if (n == SA && (pend & 1)) stage_write(pkA, w, cs); \
  if (n == SA + 1 && (pend & 1)) { stage_publish(w, cs); pend &= 6; } \
  if (n == SBB && (pend & 2)) { stage_write(pkB, w, cs); pend = 4; } \
  if (n == SBB + 1 && (pend & 4)) { stage_publish(w, cs); pend = 0; }
  mbar_wait<BAR(B_FULL + 0)>(sb, cs.p0);
  g_issue<0, true>(acc, cs);
  HOOK(0);
  mbar_wait<BAR(B_FULL + 1)>(sb, cs.p1);
  g_issue<1, false, true>(acc, cs);
  HOOK(2);
  wg_wait<1>();
  mbar_arrive_cl<BAR(B_EMPTY + 0)>(rel);
  HOOK(3);
  mbar_wait<BAR(B_FULL + 2)>(sb, cs.p0);
  g_issue<2, false, true>(acc, cs);
  HOOK(4);
  wg_wait<1>();
  mbar_arrive_cl<BAR(B_EMPTY + 1)>(rel);
  HOOK(5);
  mbar_wait<BAR(B_FULL + 3)>(sb, cs.p1);
  g_issue<3, false, true>(acc, cs);
  HOOK(6);
  const uint32_t ncode = item(sb, idx + 1);
  wg_wait<1>();
  mbar_arrive_cl<BAR(B_EMPTY + 2)>(rel);
  HOOK(7);
  cs.p0 ^= 1; cs.p1 ^= 1;
  const bool final_tile = NA == 128 && (ncode >> 9) == K_END;
#pragma unroll 1
  for (int q = 1; q < nk4; q++) {
    const bool tail = q == nk4 - 1;
    mbar_wait<BAR(B_FULL + 0)>(sb, cs.p0);
    g_issue<0, false>(acc, cs);
    HOOK(8);
    wg_wait<1>();
    mbar_arrive_cl<BAR(B_EMPTY + 3)>(rel);
    HOOK(9);
    mbar_wait<BAR(B_FULL + 1)>(sb, cs.p1);
    uint32_t rel0 = rel;
    if (final_tile && tail && w == 1) {
      wg_wait<0>();
      mbar_arrive_cl<BAR(B_EMPTY + 0)>(rel);
      rel0 = 0;
      mbar_wait<BAR(B_LEAD)>(sb, cs.lead);
    }
    g_issue<1, false>(acc, cs);
    HOOK(10);
    wg_wait<1>();
    mbar_arrive_cl<BAR(B_EMPTY + 0)>(rel0);
    HOOK(11);
    mbar_wait<BAR(B_FULL + 2)>(sb, cs.p0);
    uint32_t rel1 = rel;
    if (!final_tile && tail && w == 1) {
      wg_wait<0>();
      mbar_arrive_cl<BAR(B_EMPTY + 1)>(rel);
      rel1 = 0;
      mbar_wait<BAR(B_LEAD)>(sb, cs.lead);
    }
    g_issue<2, false>(acc, cs);
    HOOK(12);
    wg_wait<1>();
    mbar_arrive_cl<BAR(B_EMPTY + 1)>(rel1);
    HOOK(13);
    mbar_wait<BAR(B_FULL + 3)>(sb, cs.p1);
    g_issue<3, false>(acc, cs);
    mbar_arrive_if<BAR(B_LEAD)>(sb, tail && threadIdx.x == 128);
    HOOK(14);
    wg_wait<1>();
    mbar_arrive_cl<BAR(B_EMPTY + 2)>(rel);
    cs.p0 ^= 1; cs.p1 ^= 1;
  }
#undef HOOK
  cs.lead ^= 1;
  before_end();
  wg_wait<0>();
  fence_regs(acc);
  mbar_arrive_cl<BAR(B_EMPTY + 3)>(rel);
  return ncode;
}

__device__ __forceinline__ void local_probs(bool first, const float (&S)[3][4], uint32_t (&pb)[4]) {
  const int lane = threadIdx.x & 31, g = lane >> 2, t = lane & 3;
  const bool c0 = 2 * t > g, c1 = 2 * t + 1 > g;
  float x0 = c0 ? S[0][0] : S[1][0], x1 = c1 ? S[0][1] : S[1][1], y0 = c0 ? S[1][2] : S[2][2], y1 = c1 ? S[1][3] : S[2][3];
  if (first && c0) x0 = -INFINITY;
  if (first && c1) x1 = -INFINITY;
  float m0 = fmaxf(x0, x1), m1 = fmaxf(y0, y1);
  m0 = fmaxf(fmaxf(m0, __shfl_xor_sync(0xffffffffu, m0, 1)), fmaxf(__shfl_xor_sync(0xffffffffu, m0, 2), __shfl_xor_sync(0xffffffffu, m0, 3)));
  m1 = fmaxf(fmaxf(m1, __shfl_xor_sync(0xffffffffu, m1, 1)), fmaxf(__shfl_xor_sync(0xffffffffu, m1, 2), __shfl_xor_sync(0xffffffffu, m1, 3)));
  constexpr float C = 0.17677669529663687f * 1.4426950408889634f;
  const float b0 = -m0 * C, b1 = -m1 * C;
  x0 = ex2(fmaf(x0, C, b0)); x1 = ex2(fmaf(x1, C, b0)); y0 = ex2(fmaf(y0, C, b1)); y1 = ex2(fmaf(y1, C, b1));
  const float l0 = rcp(quad_sum(x0 + x1)), l1 = rcp(quad_sum(y0 + y1));
  const uint32_t px = pack_bf16(x0 * l0, x1 * l0), py = pack_bf16(y0 * l1, y1 * l1);
  const uint32_t m = (c0 ? 0xffffu : 0u) | (c1 ? 0xffff0000u : 0u);
  pb[0] = px & m; pb[1] = px & ~m; pb[2] = py & m; pb[3] = py & ~m;
}
struct Loc { uint32_t xa, ra, oa; };
__device__ __forceinline__ Loc local_prepare(uint32_t code, int w, Cons& cs) {
  const uint32_t lane = threadIdx.x & 31, wq = (threadIdx.x >> 5) & 3;
  const bool has_halo = (code & 15) != 0;
  Loc l;
  l.xa = cs.sb + OFF_STG + 8192 + w * 16384 + wq * 2048 + lane * 8;
  l.ra = l.xa - (wq == 0 ? 16384 - 3 * 2048 : 2048);
  if (w + wq == 0) l.ra = has_halo ? cs.sb + OFF_HALO + lane * 8 : l.xa;
  l.oa = cs.sb + w * 16384 + (wq * 16 + (lane & 7)) * 128 + (((lane >> 3) ^ (lane & 7)) << 4);
  asm volatile("{\n.reg .pred p;\nsetp.eq.u32 p, %0, 0;\n@p st.shared.u32 [%1], %2;\n}\n" ::"r"(l.xa), "r"(l.ra), "r"(l.oa) : "memory");
  mbar_wait<BAR(B_STGE)>(cs.sb + w * 8, (cs.round & 1) ^ 1);
  if (has_halo && w == 0) mbar_wait<BAR(B_HFULL)>(cs.sb, cs.fpar >> 1);
  cs.fpar ^= has_halo ? 2 : 0;
  return l;
}
__device__ __forceinline__ void local_epilogue(const float (&acc)[96], uint32_t code, int w, Cons& cs, const Loc& l) {
  const uint32_t cw = (threadIdx.x >> 5) - 4;
  const bool has_halo = (code & 15) != 0;
  uint32_t kf[3][8], vt[3][8];
#pragma unroll
  for (int j = 0; j < 8; j++) { kf[2][j] = pack_bf16(acc[32 + 4 * j + 2], acc[32 + 4 * j + 3]); vt[2][j] = transpose8(pack_bf16(acc[64 + 4 * j + 2], acc[64 + 4 * j + 3])); }
  sts64<0>(l.xa, &kf[2][0]); sts64<256>(l.xa, &kf[2][2]); sts64<512>(l.xa, &kf[2][4]); sts64<768>(l.xa, &kf[2][6]);
  sts64<1024>(l.xa, &vt[2][0]); sts64<1280>(l.xa, &vt[2][2]); sts64<1536>(l.xa, &vt[2][4]); sts64<1792>(l.xa, &vt[2][6]);
  if (cw == 3) bar_arrive(4, 160);
  uint32_t q[8][2];
#pragma unroll
  for (int j = 0; j < 8; j++) {
    q[j][0] = pack_bf16(acc[4 * j], acc[4 * j + 1]); q[j][1] = pack_bf16(acc[4 * j + 2], acc[4 * j + 3]);
    kf[1][j] = pack_bf16(acc[32 + 4 * j], acc[32 + 4 * j + 1]);
  }
  bar_sync(3 + w, 128 + 32 * w);
  uint32_t z[4];
  lds128<OFF_FILLS + 16>(z, cs.sb);
  lds64<0>(&kf[0][0], l.ra); lds64<512>(&kf[0][4], l.ra); lds64<256>(&kf[0][2], l.ra); lds64<768>(&kf[0][6], l.ra);
  lds64<1024>(&vt[0][0], l.ra); lds64<1280>(&vt[0][2], l.ra); lds64<1536>(&vt[0][4], l.ra); lds64<1792>(&vt[0][6], l.ra);
  float S[2][3][4];
#pragma unroll
  for (int n = 2; n >= 0; n--)
#pragma unroll
    for (int u = 0; u < 2; u++) mma16816z(S[u][n], q[4 * u][0], q[4 * u][1], q[4 * u + 1][0], q[4 * u + 1][1], kf[n][4 * u], kf[n][4 * u + 1], z);
#pragma unroll
  for (int n = 2; n >= 0; n--)
#pragma unroll
    for (int u = 0; u < 2; u++) mma16816(S[u][n], q[4 * u + 2][0], q[4 * u + 2][1], q[4 * u + 3][0], q[4 * u + 3][1], kf[n][4 * u + 2], kf[n][4 * u + 3]);
#pragma unroll
  for (int j = 0; j < 8; j++) vt[1][j] = transpose8(pack_bf16(acc[64 + 4 * j], acc[64 + 4 * j + 1]));
  uint32_t pb[2][4];
#pragma unroll
  for (int u = 0; u < 2; u++) local_probs(cw == 0 && !has_halo, S[u], pb[u]);
  const uint32_t oa = l.oa;
#pragma unroll
  for (int u = 0; u < 2; u++)
#pragma unroll
    for (int hf = 0; hf < 2; hf++) {
      float O[2][4];
#pragma unroll
      for (int mt = 0; mt < 2; mt++) {
        O[mt][0] = O[mt][1] = O[mt][2] = O[mt][3] = 0.f;
        mma16816(O[mt], vt[hf][4 * u + 2 * mt], vt[hf][4 * u + 2 * mt + 1], vt[hf + 1][4 * u + 2 * mt], vt[hf + 1][4 * u + 2 * mt + 1], pb[u][2 * hf], pb[u][2 * hf + 1]);
      }
      const uint32_t o0 = pack_bf16(O[0][0], O[0][1]), o1 = pack_bf16(O[0][2], O[0][3]), o2 = pack_bf16(O[1][0], O[1][1]), o3 = pack_bf16(O[1][2], O[1][3]);
      if (hf == 0) stmatrix_x4_trans<OFF_STG>(oa ^ (u * 64), o0, o1, o2, o3); else stmatrix_x4_trans<OFF_STG + 1024>(oa ^ (u * 64), o0, o1, o2, o3);
    }
  mbar_arrive_if<BAR(B_HEMPTY)>(cs.sb, has_halo && threadIdx.x == 128);
}

constexpr float SCALE_LOG2 = 0.08838834764831845f * 1.4426950408889634f;
#define SUM_LO 8.673617379884035e-19f
#define SUM_HI 1152921504606846976.f
template <int J0> __device__ __forceinline__ void causal_mask(float (&S)[64], int r) {
#pragma unroll
  for (int j = 0; j < 8; j++) {
    if (8 * j > r) S[4 * (J0 + j) + 0] = -INFINITY;
    if (8 * j + 1 > r) S[4 * (J0 + j) + 1] = -INFINITY;
    if (8 * j - 8 > r) S[4 * (J0 + j) + 2] = -INFINITY;
    if (8 * j - 7 > r) S[4 * (J0 + j) + 3] = -INFINITY;
  }
}
__device__ __forceinline__ float v_ex2(float x) { float y; asm volatile("ex2.approx.ftz.f32 %0, %1;" : "=f"(y) : "f"(x)); return y; }
__device__ __forceinline__ float v_add(float a, float b) { float y; asm volatile("add.f32 %0, %1, %2;" : "=f"(y) : "f"(a), "f"(b)); return y; }
__device__ __forceinline__ float v_mul(float a, float b) { float y; asm volatile("mul.f32 %0, %1, %2;" : "=f"(y) : "f"(a), "f"(b)); return y; }
template <int MJ> __device__ __forceinline__ float exp_el(float x, int j, int e, int r) {
  float p = v_ex2(x);
  if (j >= MJ) asm volatile("{\n.reg .pred q;\nsetp.lt.s32 q, %1, %2;\n@q mov.b32 %0, 0f00000000;\n}\n" : "+f"(p) : "r"(r), "r"(8 * (j - MJ) + (e & 1) - 4 * (e & 2)));
  return p;
}
template <int J0, int J1, int MJ = 16> __device__ __forceinline__ void exp_inplace(float (&S)[64], float& l0, float& l1, int r = 0) {
#pragma unroll
  for (int j = J0; j < J1; j++) {
#pragma unroll
    for (int e = 0; e < 4; e++) S[4 * j + e] = exp_el<MJ>(S[4 * j + e], j, e, r);
    l0 = v_add(l0, S[4 * j + 0]); l1 = v_add(l1, S[4 * j + 2]); l0 = v_add(l0, S[4 * j + 1]); l1 = v_add(l1, S[4 * j + 3]);
  }
}
template <int JS, int MJ, bool OUT>
__device__ __forceinline__ void exp_pack(float (&S)[64], uint32_t (&P)[32], float& l0, float& l1, int r, const float (&O)[64], float a0, float a1, uint32_t (&pk)[32]) {
#pragma unroll
  for (int j = JS; j < 16; j++) {
    const float p0 = exp_el<MJ>(S[4 * j + 0], j, 0, r), p1 = exp_el<MJ>(S[4 * j + 1], j, 1, r), p2 = exp_el<MJ>(S[4 * j + 2], j, 2, r), p3 = exp_el<MJ>(S[4 * j + 3], j, 3, r);
#pragma unroll
    for (int k = (j - JS) * JS / (16 - JS); k < (j + 1 - JS) * JS / (16 - JS); k++) { P[2 * k] = v_pack(S[4 * k + 0], S[4 * k + 1]); P[2 * k + 1] = v_pack(S[4 * k + 2], S[4 * k + 3]); }
    if (OUT) {
#pragma unroll
      for (int k = (j - JS) * 16 / (16 - JS); k < (j + 1 - JS) * 16 / (16 - JS); k++) {
        pk[2 * k] = v_pack(v_mul(O[4 * k + 0], a0), v_mul(O[4 * k + 1], a0)); pk[2 * k + 1] = v_pack(v_mul(O[4 * k + 2], a1), v_mul(O[4 * k + 3], a1));
      }
    }
    l0 = v_add(l0, p0); l1 = v_add(l1, p2); l0 = v_add(l0, p1); l1 = v_add(l1, p3);
    P[2 * j] = v_pack(p0, p1); P[2 * j + 1] = v_pack(p2, p3);
  }
}
__device__ __forceinline__ void pin_after(float a, float b) {
  asm volatile("{\n.reg .pred p;\nsetp.eq.u32 p, %0, 0xffffffff;\n@p st.shared.b32 [%1], %1;\n}\n" ::"r"(__float_as_uint(a)), "r"(__float_as_uint(b)) : "memory");
}
template <bool HALF, int SITE> __device__ __forceinline__ void issue_qk(float (&S)[64], uint32_t qlo, uint32_t klo) {
  uint32_t q, k;
  asm volatile("add.u32 %0, %2, %4;\nadd.u32 %1, %3, %4;" : "=r"(q), "=r"(k) : "r"(qlo), "r"(klo), "n"(SITE << 16));
  const uint64_t qd = desc(q), kd = desc(k);
  wg_fence();
  if (HALF) wg_qk64_init<0, 0>(S, qd, kd); else wg_qk_init<0, 0>(S, qd, kd);
#define QK(o) if (HALF) wg_qk64_acc<o, o>(S, qd, kd); else wg_qk_acc<o, o>(S, qd, kd)
  QK(2); QK(4); QK(6); QK(1024); QK(1026); QK(1028); QK(1030);
#undef QK
  wg_commit();
}
template <int NK, int ACC, int SITE> __device__ __forceinline__ void issue_pv(float (&O)[64], const uint32_t (&P)[32], uint32_t vlo) {
  constexpr int Z = 128 * SITE;
  uint32_t v;
  asm volatile("add.u32 %0, %1, %2;" : "=r"(v) : "r"(vlo), "n"(Z));
  const uint64_t vd = desc(v);
  wg_fence();
  if (ACC) wg_pv_acc<-Z>(O, &P[0], vd); else wg_pv_init<-Z>(O, &P[0], vd);
  wg_pv_acc<128 - Z>(O, &P[4], vd); wg_pv_acc<256 - Z>(O, &P[8], vd); wg_pv_acc<384 - Z>(O, &P[12], vd);
  if (NK == 8) { wg_pv_acc<512 - Z>(O, &P[16], vd); wg_pv_acc<640 - Z>(O, &P[20], vd); wg_pv_acc<768 - Z>(O, &P[24], vd); wg_pv_acc<896 - Z>(O, &P[28], vd); }
  wg_commit();
}
__device__ __forceinline__ uint32_t row_norm(float l0, float l1, float& a0, float& a1) {
  const float q0 = quad_sum(l0), q1 = quad_sum(l1);
  a0 = rcp(q0); a1 = rcp(q1);
  return __reduce_or_sync(0xffffffffu, (q0 >= SUM_LO && q0 <= SUM_HI && q1 >= SUM_LO && q1 <= SUM_HI) ? 0u : 1u);
}
__device__ __forceinline__ void slow_item(float (&O)[64], float& a0, float& a1, int head, int tile, uint32_t qbase, int w) {
  const int lane = threadIdx.x & 31, g = lane >> 2, t = lane & 3;
  const int rw = w * 64 + (int)__reduce_or_sync(0xffffffffu, (threadIdx.x >> 1) & 48);
  const int row0 = tile * 128 + rw;
  const uint32_t qa_ = qbase + (rw + g) * 128 + ((t ^ g) << 4);
  const __nv_bfloat16* kp = g_kv + ((size_t)head * SEQ + g) * 256 + 8 * t;
  const __nv_bfloat16* vp = g_kv + ((size_t)head * SEQ + 2 * t) * 256 + 128 + g;
  float m0 = -INFINITY, m1 = -INFINITY, l0 = 0.f, l1 = 0.f;
#pragma unroll
  for (int i = 0; i < 64; i++) O[i] = 0.f;
#pragma unroll 1
  for (int key0 = 0; key0 < row0 + 16; key0 += 16) {
    float c[2][4] = {{0.f, 0.f, 0.f, 0.f}, {0.f, 0.f, 0.f, 0.f}};
#pragma unroll 1
    for (int cc = 0; cc < 4; cc++) {
      uint32_t qa[4], qb[4];
      const uint32_t a = (qa_ ^ ((cc & 1) * 64)) + (cc >> 1) * 16384;
      lds128<0>(qa, a); lds128<1024>(qb, a);
#pragma unroll
      for (int n = 0; n < 2; n++) {
        const uint4 kf = ldg128(kp + (size_t)(key0 + 8 * n) * 256 + cc * 32);
        mma16816(c[n], qa[0], qb[0], qa[1], qb[1], kf.x, kf.y);
        mma16816(c[n], qa[2], qb[2], qa[3], qb[3], kf.z, kf.w);
      }
    }
#pragma unroll
    for (int n = 0; n < 2; n++)
#pragma unroll
      for (int e = 0; e < 4; e++)
        if (key0 + 8 * n + 2 * t + (e & 1) > row0 + g + (e >> 1) * 8) c[n][e] = -INFINITY;
    float x0 = fmaxf(fmaxf(c[0][0], c[0][1]), fmaxf(c[1][0], c[1][1])), x1 = fmaxf(fmaxf(c[0][2], c[0][3]), fmaxf(c[1][2], c[1][3]));
    x0 = fmaxf(x0, __shfl_xor_sync(0xffffffffu, x0, 1)); x1 = fmaxf(x1, __shfl_xor_sync(0xffffffffu, x1, 1));
    x0 = fmaxf(x0, __shfl_xor_sync(0xffffffffu, x0, 2)); x1 = fmaxf(x1, __shfl_xor_sync(0xffffffffu, x1, 2));
    const float n0 = fmaxf(m0, x0), n1 = fmaxf(m1, x1);
    const float r0 = ex2(m0 - n0), r1 = ex2(m1 - n1);
    m0 = n0; m1 = n1;
#pragma unroll
    for (int n = 0; n < 2; n++) { c[n][0] = ex2(c[n][0] - n0); c[n][1] = ex2(c[n][1] - n0); c[n][2] = ex2(c[n][2] - n1); c[n][3] = ex2(c[n][3] - n1); }
    l0 = l0 * r0 + ((c[0][0] + c[0][1]) + (c[1][0] + c[1][1]));
    l1 = l1 * r1 + ((c[0][2] + c[0][3]) + (c[1][2] + c[1][3]));
    const uint32_t p0 = pack_bf16(c[0][0], c[0][1]), p1 = pack_bf16(c[0][2], c[0][3]), p2 = pack_bf16(c[1][0], c[1][1]), p3 = pack_bf16(c[1][2], c[1][3]);
#pragma unroll
    for (int j = 0; j < 16; j++) {
      const __nv_bfloat16* v = vp + (size_t)key0 * 256 + j * 8;
      const uint32_t b0 = ldg16(v) | (ldg16(v + 256) << 16), b1 = ldg16(v + 8 * 256) | (ldg16(v + 9 * 256) << 16);
      float o[4] = {O[4 * j] * r0, O[4 * j + 1] * r0, O[4 * j + 2] * r1, O[4 * j + 3] * r1};
      mma16816(o, p0, p1, p2, p3, b0, b1);
      O[4 * j] = o[0]; O[4 * j + 1] = o[1]; O[4 * j + 2] = o[2]; O[4 * j + 3] = o[3];
    }
  }
  a0 = rcp(quad_sum(l0)); a1 = rcp(quad_sum(l1));
}
__device__ __forceinline__ void att_output(const float (&O)[64], float a0, float a1, uint32_t (&pk)[32]) {
#pragma unroll
  for (int k = 0; k < 16; k++) { pk[2 * k] = v_pack(v_mul(O[4 * k + 0], a0), v_mul(O[4 * k + 1], a0)); pk[2 * k + 1] = v_pack(v_mul(O[4 * k + 2], a1), v_mul(O[4 * k + 3], a1)); }
}
template <int J1> __device__ __forceinline__ void exp_stage(float (&S)[64], float& l0, float& l1, const uint32_t (&P)[32], int w, const Cons& cs, uint32_t on) {
  const uint32_t lane = threadIdx.x & 31, wq = (threadIdx.x >> 5) & 3;
  const uint32_t a = cs.sb + w * 16384 + (wq * 16 + (lane & 15)) * 128 + (((lane >> 4) ^ (lane & 7)) << 4);
#define ES(c) \
  exp_inplace<c * J1 / 8, (c + 1) * J1 / 8>(S, l0, l1); \
  stmatrix_x4_after<OFF_STG + (c >> 2) * 8192>(a ^ ((c & 3) * 32), P[4 * c + 0], P[4 * c + 1], P[4 * c + 2], P[4 * c + 3], (c & 1) ? l1 : l0, on)
  ES(0); ES(1); ES(2); ES(3); ES(4); ES(5); ES(6); ES(7);
#undef ES
}
struct Att { uint32_t qd, kd, vd, c8, cb, xc, xp, pub; };
__device__ __forceinline__ void att_advance(Att& t) {
  constexpr uint32_t SLOT = 32768 >> 4;
  t.kd ^= SLOT; t.vd ^= SLOT; t.c8 ^= 8; t.cb ^= 8;
  const uint32_t x = t.xc; t.xc = t.xp ^ 1; t.xp = x;
}
template <bool SECOND>
__device__ __forceinline__ uint32_t diag_step(float (&S)[64], float (&O)[64], uint32_t (&P)[32], uint32_t (&pk)[32], float& l0, float& l1, uint32_t& unsafe, Att& t, int r, int w, Cons& cs) {
  constexpr int JD = SECOND ? JDIAG2 : JDIAG;
  const uint32_t sb = cs.sb;
  float a0 = 0.f, a1 = 0.f;
  uint32_t ready;
  auto sums = [&]() {
    unsafe = row_norm(l0, l1, a0, a1);
    mbar_arrive_if<BAR(B_QEMPTY)>(sb, (threadIdx.x & 31) == 0 && !unsafe);
    l0 = l1 = 0.f;
  };
  auto look_ahead = [&]() { ready = mbar_test<BAR(B_FULL)>(t.cb, t.xc); if (!SECOND) ready &= mbar_test<BAR(B_QFULL)>(sb, cs.fpar & 1); };
  if (w == 1) {
    bar_sync(2, 256);
    issue_qk<false, 2 + SECOND>(S, t.qd, t.kd);
    if (!SECOND && t.pub) { stage_publish(w, cs); t.pub = 0; }
    mbar_wait<BAR(B_FULL + 2)>(t.cb ^ 8, t.xp);
    issue_pv<8, 1, 4 + SECOND>(O, P, t.vd);
    bar_arrive(1, 256);
    att_advance(t);
    wg_wait<1>();
    fence_regs(S);
    mbar_arrive_cl<BAR(B_EMPTY)>(cs.rel, t.c8 ^ 8);
    if (SECOND) sums();
    exp_inplace<0, JD, 8>(S, l0, l1, r);
    pin_after(l0, l1);
    wg_wait<0>();
    fence_regs(O);
    fence_regs(P);
    mbar_arrive_cl<BAR(B_EMPTY + 2)>(cs.rel, t.c8);
    look_ahead();
    exp_pack<JD, 8, SECOND>(S, P, l0, l1, r, O, a0, a1, pk);
  } else {
    bar_sync(1, 256);
    issue_qk<true, 4 + SECOND>(S, t.qd, t.kd);
    mbar_wait<BAR(B_FULL + 2)>(t.cb ^ 8, t.xp);
    issue_pv<SECOND ? 4 : 8, 1, 1>(O, P, t.vd);
    bar_arrive(2, 256);
    if (!SECOND && t.pub) { stage_publish(w, cs); t.pub = 0; }
    att_advance(t);
    if (SECOND) sums();
    wg_wait<1>();
    fence_regs<0, 32>(S);
    mbar_arrive_cl<BAR(B_EMPTY)>(cs.rel, t.c8 ^ 8);
    exp_inplace<0, 8, 0>(S, l0, l1, r);
    pin_after(l0, l1);
    wg_wait<0>();
    fence_regs(O);
    fence_regs(P);
    mbar_arrive_cl<BAR(B_EMPTY + 2)>(cs.rel, t.c8);
    look_ahead();
#pragma unroll
    for (int k = 0; k < 8; k++) { P[2 * k] = v_pack(S[4 * k + 0], S[4 * k + 1]); P[2 * k + 1] = v_pack(S[4 * k + 2], S[4 * k + 3]); }
    if (SECOND) att_output(O, a0, a1, pk);
  }
  return __reduce_or_sync(0xffffffffu, ready ^ 1);
}
__device__ __forceinline__ void attention(uint32_t code, uint32_t rank, int idx, int w, Cons& cs, uint32_t (&P)[32], uint32_t (&pk)[32]) {
  const int lane = threadIdx.x & 31, wq = (threadIdx.x >> 5) & 3;
  constexpr int JS = JSPLIT, JE = JEDGE;
  const uint32_t sb = cs.sb;
  const int y = (code & 15) * 2 + rank;
  const int r = wq * 16 + (lane >> 2) - 2 * (lane & 3);
  float O[64], S[64];
  float l0 = 0.f, l1 = 0.f;
  Att t = {cs.da + dlo(OFF_A, 16), cs.d0 + dlo(OFF_B, 16), cs.d0 + dlo(OFF_B + 98304, 16384), 0, sb, cs.p0, cs.p1, 0};
  uint32_t unsafe = 0, late;
  int ns;
  auto stage_step = [&](uint32_t on) {
    att_advance(t);
    t.pub = 1;
    wg_wait<1>();
    fence_regs(S);
    mbar_arrive_cl<BAR(B_EMPTY)>(cs.rel, t.c8 ^ 8);
    exp_stage<JE>(S, l0, l1, pk, w, cs, on);
    pin_after(l0, l1);
    wg_wait<0>();
    fence_regs(O);
    fence_regs(P);
    mbar_arrive_cl<BAR(B_EMPTY + 2)>(cs.rel, t.c8);
    const uint32_t ready = mbar_test<BAR(B_FULL)>(t.cb, t.xc);
    exp_pack<JE, 16, false>(S, P, l0, l1, r, O, 0.f, 0.f, pk);
    late = __reduce_or_sync(0xffffffffu, ready ^ 1);
  };
  bar_sync(3 - w, 128 + 128 * w);
  if (y >= 2) {
    issue_qk<false, 6>(O, t.qd, cs.d0 + dlo(OFF_B + 32768, 16));
    mbar_wait<BAR(B_FULL)>(sb, t.xc);
    issue_qk<false, 7>(S, t.qd, t.kd);
    bar_arrive(1 + (w ^ 1), 256);
    wg_wait<1>();
    fence_regs(O);
    mbar_arrive_cl<BAR(B_EMPTY + 1)>(cs.rel);
    exp_stage<JP>(O, l0, l1, pk, w, cs, w ^ 1);
    pin_after(l0, l1);
    const uint32_t rd = mbar_test<BAR(B_FULL + 3)>(sb, t.xp);
    exp_pack<JP, 16, false>(O, P, l0, l1, r, O, 0.f, 0.f, pk);
    if (UNLIKELY(__reduce_or_sync(0xffffffffu, rd ^ 1))) mbar_wait<BAR(B_FULL + 3)>(sb, t.xp);
    bar_sync(1 + w, 256);
    issue_pv<8, 0, 6>(O, P, t.vd);
    bar_arrive(1 + (w ^ 1), 256);
    stage_step(w);
    ns = y - 2;
  } else {
    issue_qk<false, 8>(S, t.qd, cs.d0 + dlo(OFF_B + 32768, 16));
    bar_arrive(1 + (w ^ 1), 256);
    wg_wait<0>();
    fence_regs(S);
    mbar_arrive_cl<BAR(B_EMPTY + 1)>(cs.rel);
    causal_mask<0>(S, r + 64 * w + 128 * y);
    causal_mask<8>(S, r + 64 * w + 128 * y - 64);
    exp_pack<0, 16, false>(S, P, l0, l1, r, S, 0.f, 0.f, pk);
#pragma unroll
    for (int i = 0; i < 64; i++) O[i] = 0.f;
    late = 1;
    ns = 0;
  }
#pragma unroll 1
  for (uint32_t head = 0;; head++) {
    while (ns > 0) {
      if (UNLIKELY(late)) mbar_wait<BAR(B_FULL)>(t.cb, t.xc);
      bar_sync(1 + w, 256);
      issue_qk<false, 9>(S, t.qd, t.kd);
      if (t.pub) { stage_publish(w, cs); t.pub = 0; }
      mbar_wait<BAR(B_FULL + 2)>(t.cb ^ 8, t.xp);
      issue_pv<8, 1, 0>(O, P, t.vd);
      bar_arrive(1 + (w ^ 1), 256);
      ns--;
      att_advance(t);
      wg_wait<1>();
      fence_regs(S);
      mbar_arrive_cl<BAR(B_EMPTY)>(cs.rel, t.c8 ^ 8);
      exp_inplace<0, JS>(S, l0, l1);
      pin_after(l0, l1);
      wg_wait<0>();
      fence_regs(O);
      fence_regs(P);
      mbar_arrive_cl<BAR(B_EMPTY + 2)>(cs.rel, t.c8);
      const uint32_t rd = mbar_test<BAR(B_FULL)>(t.cb, t.xc);
      exp_pack<JS, 16, false>(S, P, l0, l1, 0, O, 0.f, 0.f, pk);
      late = __reduce_or_sync(0xffffffffu, rd ^ 1);
    }
    if (head == 0) {
      if (y != 0) {
        if (UNLIKELY(late)) mbar_wait<BAR(B_FULL)>(t.cb, t.xc);
        late = diag_step<false>(S, O, P, pk, l0, l1, unsafe, t, r, w, cs);
      }
      t.qd += 32768 >> 4;
      if (UNLIKELY(late)) { mbar_wait<BAR(B_QFULL)>(sb, cs.fpar & 1); mbar_wait<BAR(B_FULL)>(t.cb, t.xc); }
      late = diag_step<true>(S, O, P, pk, l0, l1, unsafe, t, r, w, cs);
    } else {
      bar_sync(1 + w, 256);
      mbar_wait<BAR(B_FULL + 2)>(t.cb ^ 8, t.xp);
      if (y != 1 || w) issue_pv<8, 1, 7>(O, P, t.vd); else issue_pv<4, 1, 2>(O, P, t.vd);
      if (w == 0) bar_arrive(2, 256);
      if (t.pub) stage_publish(w, cs);
      float a0, a1;
      unsafe = row_norm(l0, l1, a0, a1);
      mbar_arrive_if<BAR(B_QEMPTY + 1)>(sb, lane == 0 && !unsafe);
      wg_wait<0>();
      fence_regs(O);
      fence_regs(P);
      mbar_arrive_cl<BAR(B_EMPTY + 2)>(cs.rel, t.c8 ^ 8);
      att_output(O, a0, a1, pk);
    }
    if (UNLIKELY(unsafe)) {
      float a0, a1;
      slow_item(S, a0, a1, ((code >> 4) & 31) * 2 + head, y ^ head, sb + OFF_A + head * 32768, w);
      __syncwarp();
      mbar_arrive_if<BAR(B_QEMPTY)>(sb + head * 8, lane == 0);
      att_output(S, a0, a1, pk);
    }
    if (head) break;
    if (y != 1) {
      if (UNLIKELY(late)) mbar_wait<BAR(B_FULL)>(t.cb, t.xc);
      bar_sync(1 + w, 256);
      issue_qk<false, 10>(S, t.qd, t.kd);
      mbar_wait<BAR(B_STGE)>(sb + w * 8, (cs.round & 1) ^ 1);
      mbar_wait<BAR(B_FULL + 2)>(t.cb ^ 8, t.xp);
      if (w == 0) issue_pv<4, 0, 3>(O, P, t.vd); else issue_pv<8, 0, 6>(O, P, t.vd);
      bar_arrive(1 + (w ^ 1), 256);
      stage_step(1);
      ns = (y ^ 1) - 1;
    } else {
      stage_write(pk, w, cs);
      t.pub = 1;
#pragma unroll
      for (int i = 0; i < 64; i++) O[i] = 0.f;
    }
  }
  cs.p1 = t.xp ^ 1; cs.p0 = t.xc;
  cs.fpar ^= 1;
}

struct Src { const CUtensorMap *ma, *mb; int a0, a1, b0, b1, b2; uint32_t hb; };
__device__ __forceinline__ Src gemm_src(const Params& p, uint32_t code, uint32_t rank, uint32_t h) {
  const int kind = code >> 9, x = (code >> 4) & 31, m = code & 15;
  Src s;
  s.ma = &p.maps[M_AX + kind];
  s.mb = &p.maps[(kind == K_KV && h) ? M_WUV : M_WQKV + kind];
  if (kind == K_QL) { s.a0 = rank * 1024; s.a1 = m * 128; s.b0 = x * 64; s.b1 = h * 32; s.b2 = 0; s.hb = 12288; }
  else { s.a0 = 0; s.a1 = (2 * m + rank) * 128; s.b0 = 0; s.b1 = 0; s.b2 = kind == K_KV ? x * 2 : x * 4 + h * 2; s.hb = 16384; }
  return s;
}
__global__ void __cluster_dims__(2, 1, 1) __launch_bounds__(384, 1) mega_kernel(const __grid_constant__ Params p) {
  extern __shared__ __align__(1024) uint8_t smem_raw[];
  const uint32_t sb = smem_u32(smem_raw), sb0 = sb;
  const uint32_t bid = blockIdx.x, rank = bid & 1;
  const int warp = __shfl_sync(0xffffffffu, threadIdx.x >> 5, 0);
#define BI(b) mbar_init<BAR(b)>(sb, bar_count(b))
  static_assert(B_COUNT == 25, "barrier set-up");
  if (warp == 0) {
    const uint32_t c0 = p.sched[bid >> 1][threadIdx.x & 1];
    if (elect_one()) {
      BI(0); BI(1); BI(2); BI(3);
      asm volatile("fence.mbarrier_init.release.cluster;" ::: "memory");
    }
    __syncwarp();
    const uint32_t code0 = __shfl_sync(0xffffffffu, c0, 0) & 4095;
    const Src u = gemm_src(p, code0, rank, 0), v = gemm_src(p, code0, rank, 1);
#pragma unroll
    for (int s = 0; s < EARLYN; s++) {
      if (elect_one()) {
        const uint32_t bar = sb + BAR(B_FULL) + s * 8;
        mbar_expect_tx<0>(bar, 16384 + 2 * u.hb);
        tma_load_2d(sb + OFF_A + s * 16384, u.ma, u.a0 + s * 64, u.a1, bar);
        tma_load_3d(sb + OFF_B + s * 32768, u.mb, u.b0, u.b1 + s * 64, u.b2, bar);
        tma_load_3d(sb + OFF_B + s * 32768 + u.hb, v.mb, v.b0, v.b1 + s * 64, v.b2, bar);
      }
    }
  }
  if (threadIdx.x == 32 || threadIdx.x == 64 || threadIdx.x == 96) {
    if (threadIdx.x == 32) { BI(4); BI(5); BI(6); BI(7); BI(8); BI(9); BI(21); }
    else if (threadIdx.x == 64) { BI(10); BI(11); BI(12); BI(13); BI(14); BI(15); BI(22); }
    else {
      BI(16); BI(17); BI(18); BI(19); BI(20); BI(23); BI(24);
      asm volatile("st.shared.u32 [%0+%2], %1;\nst.shared.v4.u32 [%0+%3], {%1, %1, %1, %1};" ::"r"(sb), "r"(0), "n"(OFF_FILLS), "n"(OFF_FILLS + 16) : "memory");
      if ((sb & 0xffffffu) != SB) __trap();
    }
    asm volatile("fence.mbarrier_init.release.cluster;" ::: "memory");
  }
#undef BI
  if (warp == 4) {
    const int i = threadIdx.x - 128;
    if (i < MAX_ITEMS / 4) {
      const uint4 v = *reinterpret_cast<const uint4*>(&p.sched[bid >> 1][4 * i]);
      asm volatile("st.shared.v4.u32 [%0+%5], {%1, %2, %3, %4};" ::"r"(sb + i * 16), "r"(v.x), "r"(v.y), "r"(v.z), "r"(v.w), "n"(OFF_LIST) : "memory");
    }
    asm volatile("st.shared.v2.u32 [%0+%2], {%1, %1};" ::"r"(sb + i * 8), "r"(0), "n"(OFF_MASK) : "memory");
  }
  bar_sync(0, 384);
  cluster_arrive_relaxed();
  const int wg = warp >> 2;
  if (wg == 0) {
    reg_dealloc<REG_PROD>();
    cluster_wait();
    const int lane = threadIdx.x & 31;
    auto need = [&](uint32_t& have, int i, int b) {
      if (!((have >> b) & 1)) {
        uint32_t n = 0;
        while (have = __reduce_or_sync(0xffffffffu, lds_acquire<OFF_MASK>(sb + i * 4)), !((have >> b) & 1)) { __nanosleep(32); if (++n > (1u << 22)) __trap(); }
        fence_async_glob();
      }
    };
    if (warp == 0) {
      uint32_t e0 = 1, e1 = 1;
      uint32_t qe = 0, after_att = 0, fills = 0;
      const uint64_t pol_first = policy_evict_first(), pol_normal = POL_NORMAL;
      for (int idx = 0;; idx++) {
        const uint32_t full = item_full(sb, idx), code = full & 4095;
        const int kind = code >> 9, x = (code >> 4) & 31, m = code & 15, y = 2 * m + rank;
        if (kind == K_END) break;
        const uint32_t last = kind >= K_OA ? 0u : full;
        {
          const Src u = gemm_src(p, code, rank, rank);
          const uint64_t pa = (last & 0x1000) ? pol_first : pol_normal, pb = (last & 0x2000) ? pol_first : pol_normal;
          const int nk = kind == K_KV ? 8 : kind == K_OB ? 64 : 16;
          uint32_t have = kind >= K_OA ? 0u : 0xffffffffu;
#pragma unroll 1
          for (int k = idx == 0 ? EARLYN : 0; k < nk; k++) {
            const uint32_t s = k & 3;
            int kk = k;
            if (k >= 64 - 4 * HLATE) { const int j = (k >> 1) - (32 - 2 * HLATE); kk = (32 - 2 * HLATE + (j < HLATE ? 2 * j : 2 * (j - HLATE) + 1)) * 2 + (k & 1); }
            need(have, (kind == K_OA ? F_QL : F_CTX) + y, kind == K_OA ? k : kk >> 1);
            if (after_att && !(k & 1)) {
              mbar_wait_b<BAR(B_QEMPTY)>(sb + k * 4, qe);
              if (k == 2) { after_att = 0; qe ^= 1; }
            }
            fill_gemm(sb + s * 8, (s & 1) ? e1 : e0, 16384 + 2 * u.hb, sb + OFF_B + s * 32768 + rank * u.hb, u.mb, u.b0, u.b1 + kk * 64, u.b2, sb + OFF_A + s * 16384, u.ma, u.a0 + kk * 64, u.a1, pb, pa);
            asm volatile("st.volatile.shared.u32 [%0+%2], %1;" ::"r"(sb), "r"(++fills), "n"(OFF_FILLS) : "memory");
            if (s == 3) { e0 ^= 1; e1 ^= 1; }
          }
        }
        if (kind == K_QF) {
          uint32_t have = 0, xc = e1, xp = e0 ^ 1;
#pragma unroll 1
          for (int j = 0; j < 8 * m + 8; j++) {
            const int i = j >> 1, v = j & 1;
            if (v ? i == 0 : i == 4 * m + 3) continue;
            const int ib = i - v;
            if (i == 2 * m + 1 + rank && !v) have = 0;
            const int h = 2 * x + (ib >= 2 * m + 1 + (int)rank), blk = ib <= 2 * m + 1 ? ib : 4 * m + 2 - ib;
            const int row = h * SEQ + blk * 128;
            if (!v) need(have, F_KV + h, blk);
            const uint32_t b = 2 * v + ((ib + 1) & 1);
            const uint32_t dst = sb + OFF_B + b * 32768;
            const bool own = ib == 2 * m + 1;
            const uint64_t pol = ((last >> (16 + (h & 1) * 8 + (blk >> 1))) & 1) ? pol_first : pol_normal;
            fill_kv(sb + b * 8, v ? xp : xc, dst + rank * 16384, &p.maps[M_KV_LD], (2 * v + rank) * 64, row, own ? 1 + rank : 3, pol);
            if (own) tma_load_2d_h(dst + (rank ^ 1) * 16384, &p.maps[M_KV_LD], (2 * v + (rank ^ 1)) * 64, row, sb + BAR(B_FULL) + b * 8, pol);
            if (v || i == 0) { const uint32_t t = xc; xc = xp ^ 1; xp = t; }
          }
          e0 ^= 1;
          after_att = 1;
        }
      }
    } else if (warp == 2) {
      const uint32_t epoch = g_flags.epoch[bid];
      const uint64_t full = (lane >> 3) == 2 ? ~0ull : 0x0000ffff0000ffffull, flip = 0ull - (epoch & 1);
      uint64_t seen = 0;
      uint32_t tries = 0, hp = 1, hcode;
      int hidx = -1;
      auto next_halo = [&]() { do hcode = item(sb, ++hidx); while ((hcode >> 9) != K_END && ((hcode >> 9) != K_QL || (hcode & 15) == 0)); };
      next_halo();
      while (true) {
        const bool all = __all_sync(0xffffffffu, seen == full);
        if (all && (hcode >> 9) == K_END) break;
        if (!all) {
          uint64_t v;
          asm volatile("ld.acquire.gpu.global.u64 %0, [%1];" : "=l"(v) : "l"(&g_flags.m[2 * lane]) : "memory");
          v = (v ^ flip) & full;
          if (v != seen) { seen = v; asm volatile("st.release.cta.shared::cta.u64 [%0+%2], %1;" ::"r"(sb + lane * 8), "l"(v), "n"(OFF_MASK) : "memory"); }
        }
        if ((hcode >> 9) != K_END) {
          const int x = (hcode >> 4) & 31, m = hcode & 15;
          bool there = __any_sync(0xffffffffu, lane == F_QL / 2 + m - 1 && ((seen >> (32 * rank + x)) & 1));
          if (there && __all_sync(0xffffffffu, mbar_test<BAR(B_HEMPTY)>(sb, hp))) {
            __syncwarp();
            fence_async_glob();
            if (elect_one()) mbar_expect_tx<BAR(B_HFULL)>(sb, 2048);
            bulk_load(sb + OFF_HALO, g_halo + ((2 * m + rank - 2) * 16 + x) * 2048, 2048, sb + BAR(B_HFULL));
            hp ^= 1;
            next_halo();
          }
        }
        __nanosleep(WATCH_NS);
        if (++tries > (1u << 20)) __trap();
      }
      if (lane == 0) g_flags.epoch[bid] = epoch + 1;
    } else if (warp == 3) {
      uint32_t n = 0;
      for (int idx = 0;; idx++) {
        const uint32_t code = item(sb, idx);
        const int kind = code >> 9, x = (code >> 4) & 31, y = 2 * (code & 15) + rank;
        if (kind == K_END) break;
        if (kind > K_KV) continue;
#pragma unroll 1
        for (int r = 0; r <= (kind == K_QF); r++, n++) {
          mbar_wait_long<BAR(B_RELF)>(sb + (n & 1) * 8, (n >> 1) & 1);
          mbar_arrive_if<BAR(B_RELE)>(sb + (n & 1) * 8, lane == 0);
          flag_toggle(&g_flags.m[kind == K_QL ? F_QL + y : kind == K_KV ? F_KV + x : F_CTX + (y ^ r)], 1u << (kind == K_QL ? x : kind == K_KV ? y : 2 * x + r));
        }
      }
    } else {
      {
        uint32_t round = 0, fpar = 0, nrel = 0;
        const uint32_t rb = mapa(sb, rank ^ 1);
        const uint64_t pol_first = policy_evict_first(), pol_normal = POL_NORMAL;
        auto pace = [&]() {
          uint32_t c0, c, t0, t;
          asm volatile("ld.volatile.shared.u32 %0, [%1+%2];" : "=r"(c0) : "r"(sb), "n"(OFF_FILLS) : "memory");
          asm volatile("mov.u32 %0, %clock;" : "=r"(t0));
          do {
            asm volatile("ld.volatile.shared.u32 %0, [%1+%2];" : "=r"(c) : "r"(sb), "n"(OFF_FILLS) : "memory");
            asm volatile("mov.u32 %0, %clock;" : "=r"(t));
          } while (__all_sync(0xffffffffu, c == c0 && t - t0 < PACE_MAX));
        };
        for (int idx = 0;; idx++) {
          const uint32_t code = item(sb, idx);
          const int kind = code >> 9, x = (code >> 4) & 31, m = code & 15, y = 2 * m + rank;
          if (kind == K_END) break;
          const bool last = (item(sb, idx + 1) >> 9) == K_END;
          if (kind == K_QF) {
            if (elect_one()) mbar_expect_tx<BAR(B_QFULL)>(sb, 32768);
            mbar_wait_long<BAR(B_QX)>(sb, fpar);
#pragma unroll 1
            for (int v = 0; v < 2; v++) {
              mbar_wait_b<BAR(B_STGF)>(sb + v * 8, round & 1);
              bulk_send(rb + OFF_A + 32768 + v * 8192, sb + OFF_STG + v * 16384, 8192, rb + BAR(B_QFULL));
              bulk_send(rb + OFF_A + 49152 + v * 8192, sb + OFF_STG + v * 16384 + 8192, 8192, rb + BAR(B_QFULL));
            }
            mbar_wait_b<BAR(B_QFULL)>(sb, fpar);
            mbar_arrive_cl<BAR(B_STGE)>(lane < 2 ? rb : 0, lane * 8);
            round++; fpar ^= 1;
          }
          const CUtensorMap* mc = &p.maps[M_OA_ST + kind];
          const uint64_t pol = (kind >= K_OA || kind == K_QF) ? pol_first : pol_normal;
          int row = kind == K_KV ? x * SEQ + y * 128 : kind == K_OA ? m * 128 : y * 128;
          int cg = kind == K_QL ? x : kind == K_QF ? x * 4 : kind == K_KV ? 0 : kind == K_OA ? rank * 32 + x * 4 : 16 + x * 4;
          const int nr = kind == K_QL ? 1 : 2;
#pragma unroll 1
          for (int r = 0; r < nr; r++) {
            mbar_wait_long<BAR(B_STGF)>(sb, round & 1);
            if (last && kind >= K_KV) {
              tma_store_3d(mc, sb + OFF_STG, 0, row, cg, pol);
              mbar_wait_b<BAR(B_FIN)>(sb, 0);
              tma_store_3d(mc, sb + OFF_B, 0, row, cg + 2, pol);
              mbar_wait_b<BAR(B_STGF + 1)>(sb, round & 1);
              tma_store_3d(mc, sb + OFF_STG + 16384, 0, row + 64, cg, pol);
              mbar_wait_b<BAR(B_FIN + 1)>(sb, 0);
              tma_store_3d(mc, sb + OFF_B + 16384, 0, row + 64, cg + 2, pol);
              bulk_commit();
              r = 1;
            } else {
              const bool paced = !last && (kind >= K_KV || r == 1);
              if (paced) pace();
              tma_store_3d(mc, sb + OFF_STG, 0, row, cg, pol);
              bulk_commit();
              mbar_wait_b<BAR(B_STGF + 1)>(sb, round & 1);
              if (paced) pace();
              tma_store_3d(mc, sb + OFF_STG + 16384, 0, row + 64, cg, pol);
              if (kind == K_QL) bulk_store(g_halo + (y * 16 + x) * 2048, sb + OFF_STG + 16384 + 8192 + 3 * 2048, 2048);
              bulk_commit();
              bulk_wait_read<1>();
              mbar_arrive_if<BAR(B_STGE)>(sb, lane == 0);
              bulk_wait_read<0>();
              mbar_arrive_if<BAR(B_STGE + 1)>(sb, lane == 0);
              round++;
            }
            if (kind == K_QF || (kind <= K_KV && r == nr - 1)) {
              bulk_wait_all();
              mbar_wait_b<BAR(B_RELE)>(sb + (nrel & 1) * 8, ((nrel >> 1) & 1) ^ 1);
              __syncwarp();
              mbar_arrive_if<BAR(B_RELF)>(sb + (nrel & 1) * 8, lane == 0);
              nrel++;
            }
            cg += 2;
            if (kind == K_QF) row ^= 128;
          }
        }
        bulk_wait_all();
      }
      cluster_arrive_relaxed();
      cluster_wait();
    }
  } else {
    reg_alloc<REG_CONS>();
    cluster_wait();
    const int w = wg - 1;
    Cons cs;
    cs.sb = __reduce_or_sync(0xffffffffu, sb0);
    const uint32_t sb = cs.sb;
    cs.d0 = (sb & 0x3ffff) >> 4;
    cs.da = cs.d0 + w * 512;
    cs.rel = (threadIdx.x & 127) == 0 ? sb : (threadIdx.x & 127) == 1 ? mapa(sb, rank ^ 1) : 0;
    cs.p0 = cs.p1 = cs.lead = cs.round = cs.fpar = 0;
    uint32_t pkA[32], pkB[32], pend = 0;
#pragma unroll
    for (int i = 0; i < 32; i++) pkA[i] = pkB[i] = 0;
    uint32_t code = item(sb, 0);
    int idx = 0;
    do {
      const int kind = code >> 9;
      uint32_t ncode;
      if (kind == K_QL) {
        float acc[96];
        Loc l;
        ncode = gemm_tile(acc, 4, idx, w, cs, pend, pkA, pkB, [&] { l = local_prepare(code, w, cs); });
        local_epilogue(acc, code, w, cs, l);
        pend = 24;
        if (w == 1 && (ncode >> 9) != K_END) bar_arrive(5, 256);
        if ((ncode >> 9) >= K_OA) { stage_publish(w, cs); pend = 16; }
      } else {
        float acc[128];
        ncode = gemm_tile(acc, kind == K_KV ? 2 : kind == K_OB ? 16 : 4, idx, w, cs, pend, pkA, pkB, [] {});
        if (kind == K_QF) {
          mbar_arrive_cl<BAR(B_QX)>((threadIdx.x & 1) ? cs.rel : 0);
          tile_pack_write<OFF_A, 16384, 0>(acc, pkB, sb + w * 8192);
#pragma unroll
          for (int i = 0; i < 32; i++) pkA[i] = v_pack(acc[64 + 2 * i], acc[64 + 2 * i + 1]);
          mbar_wait<BAR(B_STGE)>(sb + w * 8, (cs.round & 1) ^ 1);
          if ((code & 15) == 0) { tile_write<OFF_STG, 8192>(pkA, sb + w * 16384); stage_publish(w, cs); }
          mbar_wait<BAR(B_FULL + 1)>(sb, cs.p1);
          fence_async_smem();
          attention(code, rank, idx, w, cs, pkB, pkA);
          pend = 1;
        } else {
          if (kind == K_KV) {
#pragma unroll
            for (int i = 0; i < 64; i++) acc[i] *= SCALE_LOG2;
          }
#pragma unroll
          for (int i = 0; i < 32; i++) pkA[i] = pack_bf16(acc[2 * i], acc[2 * i + 1]);
#pragma unroll
          for (int i = 0; i < 32; i++) pkB[i] = pack_bf16(acc[64 + 2 * i], acc[64 + 2 * i + 1]);
          pend = 3;
        }
      }
      code = ncode;
      idx++;
    } while ((code >> 9) != K_END);
    if (pend & 1) { stage_write(pkA, w, cs); stage_publish(w, cs); }
    if (pend & 2) {
      mbar_wait<BAR(B_EMPTY)>(sb, cs.p0 ^ 1);
      tile_write<OFF_B, 8192>(pkB, sb + w * 16384);
      fence_async_smem();
      __syncwarp();
      mbar_arrive_if<BAR(B_FIN)>(sb + w * 8, (threadIdx.x & 31) == 0);
    }
    cluster_arrive();
  }
}

typedef CUresult (*EncodeFn)(CUtensorMap*, CUtensorMapDataType, cuuint32_t, void*, const cuuint64_t*, const cuuint64_t*, const cuuint32_t*,
                             const cuuint32_t*, CUtensorMapInterleave, CUtensorMapSwizzle, CUtensorMapL2promotion, CUtensorMapFloatOOBfill);

void make_map_2d(EncodeFn enc, CUtensorMap* tm, const void* ptr, uint64_t cols, uint64_t rows) {
  cuuint64_t dims[2] = {cols, rows};
  cuuint64_t str[1] = {cols * 2};
  cuuint32_t box[2] = {64, 128};
  cuuint32_t es[2] = {1, 1};
  enc(tm, CU_TENSOR_MAP_DATA_TYPE_BFLOAT16, 2, const_cast<void*>(ptr), dims, str, box, es, CU_TENSOR_MAP_INTERLEAVE_NONE, CU_TENSOR_MAP_SWIZZLE_128B,
      CU_TENSOR_MAP_L2_PROMOTION_L2_256B, CU_TENSOR_MAP_FLOAT_OOB_FILL_NONE);
}
void make_map_3d(EncodeFn enc, CUtensorMap* tm, const void* ptr, uint64_t cols, uint64_t rows, uint64_t part, uint32_t br, uint32_t bg) {
  cuuint64_t dims[3] = {part, rows, cols / part};
  cuuint64_t str[2] = {cols * 2, part * 2};
  cuuint32_t box[3] = {64, br, bg};
  cuuint32_t es[3] = {1, 1, 1};
  enc(tm, CU_TENSOR_MAP_DATA_TYPE_BFLOAT16, 3, const_cast<void*>(ptr), dims, str, box, es, CU_TENSOR_MAP_INTERLEAVE_NONE, CU_TENSOR_MAP_SWIZZLE_128B,
      CU_TENSOR_MAP_L2_PROMOTION_L2_256B, CU_TENSOR_MAP_FLOAT_OOB_FILL_NONE);
}

static const uint32_t h_sched[NPAIR][MAX_ITEMS] = {
  {0x400,0xff800207,0x554,0x564,0x566,0x1e02c4,0x20a7,0x625,0xe00,0xe00,0xe00,0xe00,0xe00,0xe00,0xe00,0xe00,0xe00,0xe00,0xe00,0xe00},
  {0x420,0x454,0x2,0x83,0x25,0xb6,0x4f0,0x2a5,0x25d0,0x202f1,0x636,0xe00,0xe00,0xe00,0xe00,0xe00,0xe00,0xe00,0xe00,0xe00},
  {0x440,0x200,0xe3,0x55,0x520,0x4d4,0x524,0xfff002a7,0x2037,0x30f7,0xe00,0xe00,0xe00,0xe00,0xe00,0xe00,0xe00,0xe00,0xe00,0xe00},
  {0x460,0x206,0x32281,0x2c2,0x202e1,0x603,0xe00,0xe00,0xe00,0xe00,0xe00,0xe00,0xe00,0xe00,0xe00,0xe00,0xe00,0xe00,0xe00,0xe00},
  {0x410,0x1,0x92,0x24,0xd5,0x40252,0x202a1,0x830,0xe00,0xe00,0xe00,0xe00,0xe00,0xe00,0xe00,0xe00,0xe00,0xe00,0xe00,0xe00},
  {0x430,0x474,0x12,0x93,0x4c1,0x4e1,0x4e3,0x4d5,0x513,0x536,0x583,0x2a0,0x5f3,0x815,0xe00,0xe00,0xe00,0xe00,0xe00,0xe00},
  {0x450,0x205,0x510,0x512,0x534,0x584,0x2547,0x574,0x2d3,0x20d7,0x616,0xe00,0xe00,0xe00,0xe00,0xe00,0xe00,0xe00,0xe00,0xe00},
  {0x470,0x406,0x485,0x4a1,0x486,0x497,0x4a5,0xa6,0x180284,0x1002f4,0x634,0xe00,0xe00,0xe00,0xe00,0xe00,0xe00,0xe00,0xe00,0xe00},
  {0x401,0x11,0x244,0x2a4,0x812,0xe00,0xe00,0xe00,0xe00,0xe00,0xe00,0xe00,0xe00,0xe00,0xe00,0xe00,0xe00,0xe00,0xe00,0xe00},
  {0x0,0xb1,0x33,0xd4,0x36,0x24c7,0x505,0x526,0x563,0x546,0x5e3,0x596,0x5f6,0x816,0xe00,0xe00,0xe00,0xe00,0xe00,0xe00},
  {0x421,0x201,0x94,0x276,0x5d2,0x837,0xe00,0xe00,0xe00,0xe00,0xe00,0xe00,0xe00,0xe00,0xe00,0xe00,0xe00,0xe00,0xe00,0xe00},
  {0x441,0x21,0xa2,0x34,0xe5,0x285,0x1002e4,0x613,0xe00,0xe00,0xe00,0xe00,0xe00,0xe00,0xe00,0xe00,0xe00,0xe00,0xe00,0xe00},
  {0x10,0x224,0x4d7,0x515,0x544,0x5c0,0x585,0x577,0x2002e5,0x633,0xe00,0xe00,0xe00,0xe00,0xe00,0xe00,0xe00,0xe00,0xe00,0xe00},
  {0x461,0x203,0x76,0x523,0x506,0x802a3,0x822,0xe00,0xe00,0xe00,0xe00,0xe00,0xe00,0xe00,0xe00,0xe00,0xe00,0xe00,0xe00,0xe00},
  {0x480,0x210,0xf3,0x4c2,0xffc00277,0x802e3,0x622,0xe00,0xe00,0xe00,0xe00,0xe00,0xe00,0xe00,0xe00,0xe00,0xe00,0xe00,0xe00,0xe00},
  {0x20,0x233,0x4b3,0x260,0x290,0x5c6,0x5b6,0x800,0xe00,0xe00,0xe00,0xe00,0xe00,0xe00,0xe00,0xe00,0xe00,0xe00,0xe00,0xe00},
  {0x411,0x31,0xb2,0x256,0x586,0x590,0x2594,0x803,0xe00,0xe00,0xe00,0xe00,0xe00,0xe00,0xe00,0xe00,0xe00,0xe00,0xe00,0xe00},
  {0x431,0x426,0xff800247,0x4002c6,0x2077,0x614,0xe00,0xe00,0xe00,0xe00,0xe00,0xe00,0xe00,0xe00,0xe00,0xe00,0xe00,0xe00,0xe00,0xe00},
  {0x451,0x41,0xc2,0xff800257,0x592,0x1802d4,0x600,0xe00,0xe00,0xe00,0xe00,0xe00,0xe00,0xe00,0xe00,0xe00,0xe00,0xe00,0xe00,0xe00},
  {0x471,0x446,0x466,0x2456,0x2467,0x4a3,0x4c3,0x4b4,0x296,0x15f1,0x35f0,0x2017,0x2067,0x632,0xe00,0xe00,0xe00,0xe00,0xe00,0xe00},
  {0x490,0x484,0x22,0xa3,0x35,0xc6,0x40272,0x4002e6,0x623,0xe00,0xe00,0xe00,0xe00,0xe00,0xe00,0xe00,0xe00,0xe00,0xe00,0xe00},
  {0x402,0x465,0x32,0x476,0x495,0x75,0x521,0x4d3,0x525,0x2517,0x5e0,0x5a2,0x5c4,0x2002f5,0x604,0xe00,0xe00,0xe00,0xe00,0xe00},
  {0x30,0x400226,0x80293,0x834,0xe00,0xe00,0xe00,0xe00,0xe00,0xe00,0xe00,0xe00,0xe00,0xe00,0xe00,0xe00,0xe00,0xe00,0xe00,0xe00},
  {0x422,0x211,0xa4,0x500,0x502,0xffe00297,0x322d1,0x631,0xe00,0xe00,0xe00,0xe00,0xe00,0xe00,0xe00,0xe00,0xe00,0xe00,0xe00,0xe00},
  {0x40,0x2447,0x82,0x44,0xf5,0xe6,0x4f5,0x535,0x553,0x808002d7,0x611,0xe00,0xe00,0xe00,0xe00,0xe00,0xe00,0xe00,0xe00,0xe00},
  {0x442,0x416,0x42,0xb3,0x200255,0x5a3,0x5a5,0x5b7,0x813,0xe00,0xe00,0xe00,0xe00,0xe00,0xe00,0xe00,0xe00,0xe00,0xe00,0xe00},
  {0x462,0x220,0x4,0x65,0x4c5,0x522,0x541,0x514,0x545,0x573,0x5c3,0x5e5,0x5d6,0x806,0xe00,0xe00,0xe00,0xe00,0xe00,0xe00},
  {0x481,0x436,0x52,0xc3,0x45,0xd6,0x32261,0x5c2,0x4002f6,0x624,0xe00,0xe00,0xe00,0xe00,0xe00,0xe00,0xe00,0xe00,0xe00,0xe00},
  {0x412,0x204,0xffe00287,0x402f2,0x637,0xe00,0xe00,0xe00,0xe00,0xe00,0xe00,0xe00,0xe00,0xe00,0xe00,0xe00,0xe00,0xe00,0xe00,0xe00},
  {0x50,0xc1,0x43,0xe4,0x46,0x4e5,0x24e7,0x543,0x533,0x5c1,0x2567,0x593,0x5b5,0x833,0xe00,0xe00,0xe00,0xe00,0xe00,0xe00},
  {0x432,0x4a0,0x62,0xd3,0x4a4,0x200265,0x576,0x5d7,0x804,0xe00,0xe00,0xe00,0xe00,0xe00,0xe00,0xe00,0xe00,0xe00,0xe00,0xe00},
  {0x452,0x455,0x241,0xc5,0x286,0x831,0xe00,0xe00,0xe00,0xe00,0xe00,0xe00,0xe00,0xe00,0xe00,0xe00,0xe00,0xe00,0xe00,0xe00},
  {0x472,0x51,0x245,0x562,0x550,0x808002e7,0x607,0xe00,0xe00,0xe00,0xe00,0xe00,0xe00,0xe00,0xe00,0xe00,0xe00,0xe00,0xe00,0xe00},
  {0x403,0x61,0xd2,0x4a2,0x2496,0x4a6,0x501,0x250,0x537,0x565,0x2587,0x5e6,0x5b1,0x827,0xe00,0xe00,0xe00,0xe00,0xe00,0xe00},
  {0x423,0x71,0x243,0x4e6,0x100294,0x821,0xe00,0xe00,0xe00,0xe00,0xe00,0xe00,0xe00,0xe00,0xe00,0xe00,0xe00,0xe00,0xe00,0xe00},
  {0x443,0x202,0x85,0x200275,0x5d4,0x820,0xe00,0xe00,0xe00,0xe00,0xe00,0xe00,0xe00,0xe00,0xe00,0xe00,0xe00,0xe00,0xe00,0xe00},
  {0x482,0x212,0x95,0x80263,0x5a4,0x2575,0x5d5,0x836,0xe00,0xe00,0xe00,0xe00,0xe00,0xe00,0xe00,0xe00,0xe00,0xe00,0xe00,0xe00},
  {0x413,0x213,0x86,0x540,0x511,0x530,0x402a2,0x832,0xe00,0xe00,0xe00,0xe00,0xe00,0xe00,0xe00,0xe00,0xe00,0xe00,0xe00,0xe00},
  {0x433,0x216,0x516,0x532,0x572,0x2002c5,0x20b7,0x635,0xe00,0xe00,0xe00,0xe00,0xe00,0xe00,0xe00,0xe00,0xe00,0xe00,0xe00,0xe00},
  {0x60,0xd1,0x53,0xf4,0x24a7,0x4d0,0x504,0x280,0x808002f7,0x626,0xe00,0xe00,0xe00,0xe00,0xe00,0xe00,0xe00,0xe00,0xe00,0xe00},
  {0x453,0x222,0xa5,0x4c6,0x273,0x595,0x5b0,0x802,0xe00,0xe00,0xe00,0xe00,0xe00,0xe00,0xe00,0xe00,0xe00,0xe00,0xe00,0xe00},
  {0x70,0x240,0x2477,0xff800267,0x5f2,0x835,0xe00,0xe00,0xe00,0xe00,0xe00,0xe00,0xe00,0xe00,0xe00,0xe00,0xe00,0xe00,0xe00,0xe00},
  {0x491,0x475,0x72,0x494,0x2487,0x100254,0x5e2,0x5e4,0x25e7,0x5d1,0x812f3,0x627,0xe00,0xe00,0xe00,0xe00,0xe00,0xe00,0xe00,0xe00},
  {0x80,0xe1,0x63,0x5,0x56,0x503,0x4f3,0x561,0x531,0x5e1,0x591,0x5a6,0x5b2,0x826,0xe00,0xe00,0xe00,0xe00,0xe00,0xe00},
  {0x492,0x214,0x4d6,0x4f6,0x24f4,0x808002c7,0x20c7,0x606,0xe00,0xe00,0xe00,0xe00,0xe00,0xe00,0xe00,0xe00,0xe00,0xe00,0xe00,0xe00},
  {0x90,0x236,0x292,0x5b3,0x824,0xe00,0xe00,0xe00,0xe00,0xe00,0xe00,0xe00,0xe00,0xe00,0xe00,0xe00,0xe00,0xe00,0xe00,0xe00},
  {0x404,0x223,0x96,0x100274,0x5f4,0x807,0xe00,0xe00,0xe00,0xe00,0xe00,0xe00,0xe00,0xe00,0xe00,0xe00,0xe00,0xe00,0xe00,0xe00},
  {0x424,0x221,0xb4,0x4b6,0x4b0,0x283,0x5c7,0x5d3,0x825,0xe00,0xe00,0xe00,0xe00,0xe00,0xe00,0xe00,0xe00,0xe00,0xe00,0xe00},
  {0x444,0x231,0xc4,0x80253,0x556,0x4002d6,0x1630,0xe00,0xe00,0xe00,0xe00,0xe00,0xe00,0xe00,0xe00,0xe00,0xe00,0xe00,0xe00,0xe00},
  {0xa0,0x225,0x542,0x2507,0x555,0x571,0x2c3,0x132f0,0x621,0xe00,0xe00,0xe00,0xe00,0xe00,0xe00,0xe00,0xe00,0xe00,0xe00,0xe00},
  {0x463,0x81,0xe2,0x54,0x6,0x40262,0x2b1,0x817,0xe00,0xe00,0xe00,0xe00,0xe00,0xe00,0xe00,0xe00,0xe00,0xe00,0xe00,0xe00},
  {0x414,0x493,0x2417,0x3,0x4c0,0x4e0,0x100264,0x2c1,0x402d2,0x601,0xe00,0xe00,0xe00,0xe00,0xe00,0xe00,0xe00,0xe00,0xe00,0xe00},
  {0x434,0x407,0x2437,0x13,0x74,0x4c4,0x4b5,0x24b1,0x4f7,0x581,0x5a0,0x551,0x122b0,0x811,0xe00,0xe00,0xe00,0xe00,0xe00,0xe00},
  {0x473,0xff800217,0x582,0x552,0x3e02b5,0x2097,0x615,0xe00,0xe00,0xe00,0xe00,0xe00,0xe00,0xe00,0xe00,0xe00,0xe00,0xe00,0xe00,0xe00},
  {0x405,0x230,0x14,0x266,0x2002d5,0x612,0xe00,0xe00,0xe00,0xe00,0xe00,0xe00,0xe00,0xe00,0xe00,0xe00,0xe00,0xe00,0xe00,0xe00},
  {0xb0,0xf1,0x73,0x15,0x66,0x10f6,0x2a6,0x2007,0x2047,0x620,0xe00,0xe00,0xe00,0xe00,0xe00,0xe00,0xe00,0xe00,0xe00,0xe00},
  {0xc0,0x234,0x295,0x823,0xe00,0xe00,0xe00,0xe00,0xe00,0xe00,0xe00,0xe00,0xe00,0xe00,0xe00,0xe00,0xe00,0xe00,0xe00,0xe00},
  {0xd0,0x242,0x26,0x4d2,0x4f2,0x580,0x2b3,0x2d0,0x2027,0x20e7,0xe00,0xe00,0xe00,0xe00,0xe00,0xe00,0xe00,0xe00,0xe00,0xe00},
  {0x425,0x215,0x20271,0x570,0x597,0x122c0,0x402e2,0x617,0xe00,0xe00,0xe00,0xe00,0xe00,0xe00,0xe00,0xe00,0xe00,0xe00,0xe00,0xe00},
  {0xe0,0xff800237,0x32291,0x5b4,0x810,0xe00,0xe00,0xe00,0xe00,0xe00,0xe00,0xe00,0xe00,0xe00,0xe00,0xe00,0xe00,0xe00,0xe00,0xe00},
  {0x445,0x427,0x457,0x23,0x84,0x4e2,0x4b7,0x20251,0x5a1,0x2557,0x5c5,0x5f7,0x814,0xe00,0xe00,0xe00,0xe00,0xe00,0xe00,0xe00},
  {0x483,0x232,0xb5,0x4e4,0x4d1,0x40282,0x5a7,0x5f5,0x805,0xe00,0xe00,0xe00,0xe00,0xe00,0xe00,0xe00,0xe00,0xe00,0xe00,0xe00},
  {0x464,0x91,0xf2,0x64,0x16,0x4b2,0x4f1,0x560,0x808002b7,0x2057,0x602,0xe00,0xe00,0xe00,0xe00,0xe00,0xe00,0xe00,0xe00,0xe00},
  {0x415,0xff800227,0x2527,0x404002b6,0x2087,0x605,0xe00,0xe00,0xe00,0xe00,0xe00,0xe00,0xe00,0xe00,0xe00,0xe00,0xe00,0xe00,0xe00,0xe00},
  {0xf0,0x235,0x12270,0x2b4,0x122e0,0x610,0xe00,0xe00,0xe00,0xe00,0xe00,0xe00,0xe00,0xe00,0xe00,0xe00,0xe00,0xe00,0xe00,0xe00},
  {0x435,0xa1,0x400246,0x2b2,0x801,0xe00,0xe00,0xe00,0xe00,0xe00,0xe00,0xe00,0xe00,0xe00,0xe00,0xe00,0xe00,0xe00,0xe00,0xe00},
};

struct HostState { bool init; Params p; void* out; const void* in[9]; };
HostState g_hs;

void build_state(void* const* d_in, void* d_out) {
  void* fn = nullptr;
  cudaDriverEntryPointQueryResult qr;
  cudaGetDriverEntryPoint("cuTensorMapEncodeTiled", &fn, cudaEnableDefault, &qr);
  EncodeFn enc = (EncodeFn)fn;
  void *kv, *ctx, *oA;
  cudaGetSymbolAddress(&kv, g_kv);
  cudaGetSymbolAddress(&ctx, g_ctx);
  cudaGetSymbolAddress(&oA, g_oA);
  Params& p = g_hs.p;
  make_map_2d(enc, &p.maps[M_AX], d_in[0], 2048, SEQ / 2);
  make_map_2d(enc, &p.maps[M_BX], d_in[3], 1024, SEQ);
  make_map_2d(enc, &p.maps[M_CKV], d_in[4], 512, SEQ);
  make_map_2d(enc, &p.maps[M_OA], oA, 1024, SEQ);
  make_map_2d(enc, &p.maps[M_CTX], ctx, 4096, SEQ);
  make_map_3d(enc, &p.maps[M_WQKV], d_in[1], 3072, 1024, 1024, 32, 3);
  make_map_3d(enc, &p.maps[M_WQ], d_in[5], 4096, 1024, 64, 64, 2);
  make_map_3d(enc, &p.maps[M_WUK], d_in[6], 4096, 512, 64, 64, 2);
  make_map_3d(enc, &p.maps[M_WUV], d_in[7], 4096, 512, 64, 64, 2);
  make_map_3d(enc, &p.maps[M_WOA], d_in[2], 1024, 1024, 64, 64, 2);
  make_map_3d(enc, &p.maps[M_WOB], d_in[8], 1024, 4096, 64, 64, 2);
  make_map_2d(enc, &p.maps[M_KV_LD], kv, 256, 32 * SEQ);
  make_map_3d(enc, &p.maps[M_OA_ST], oA, 1024, SEQ, 64, 64, 1);
  make_map_3d(enc, &p.maps[M_CTX_ST], ctx, 4096, SEQ, 64, 64, 2);
  make_map_3d(enc, &p.maps[M_KV_ST], kv, 256, 32 * SEQ, 64, 64, 2);
  make_map_3d(enc, &p.maps[M_OUTA_ST], d_out, 4096, SEQ / 2, 64, 64, 2);
  make_map_3d(enc, &p.maps[M_OUTB_ST], d_out, 2048, SEQ, 64, 64, 2);
  for (int c = 0; c < NPAIR; c++)
    for (int i = 0; i < MAX_ITEMS; i++) p.sched[c][i] = h_sched[c][i];
  cudaFuncSetAttribute(mega_kernel, cudaFuncAttributeMaxDynamicSharedMemorySize, SMEM_BYTES);
}

}

extern "C" void kernel_launch(void* const* d_in, const int* in_sizes, int n_in, void* d_out, int out_size) {
  (void)in_sizes; (void)n_in; (void)out_size;
  bool same = g_hs.init && g_hs.out == d_out;
  for (int i = 0; i < 9 && same; i++) same = (g_hs.in[i] == d_in[i]);
  if (!same) {
    build_state(d_in, d_out);
    g_hs.init = true; g_hs.out = d_out;
    for (int i = 0; i < 9; i++) g_hs.in[i] = d_in[i];
  }
  mega_kernel<<<NCTA, 384, SMEM_BYTES, cudaStreamPerThread>>>(g_hs.p);
}
```

```cpp
#include <cuda_runtime.h>
#include <cuda_bf16.h>
#include <cuda.h>
#include <stdint.h>

namespace {

constexpr int SEQ = 2048;
constexpr int NCTA = 132, NPAIR = 66;
constexpr int MAX_ITEMS = 20;

__device__ __align__(1024) __nv_bfloat16 g_kv[32 * SEQ * 256];
__device__ __align__(1024) __nv_bfloat16 g_ctx[SEQ * 4096];
__device__ __align__(1024) __nv_bfloat16 g_oA[SEQ * 1024];
__device__ __align__(1024) uint8_t g_halo[16 * 16 * 2048];
struct Flags { uint32_t m[64]; uint32_t epoch[NCTA]; };
__device__ __align__(128) Flags g_flags;
enum { F_KV = 0, F_CTX = 32, F_QL = 48 };

enum { K_QL = 0, K_QF = 1, K_KV = 2, K_OA = 3, K_OB = 4, K_END = 7 };
enum { M_AX = 0, M_BX, M_CKV, M_OA, M_CTX, M_WQKV, M_WQ, M_WUK, M_WOA, M_WOB, M_WUV, M_KV_LD, M_OA_ST, M_CTX_ST, M_KV_ST, M_OUTA_ST, M_OUTB_ST, M_COUNT };

struct Params {
  CUtensorMap maps[M_COUNT];
  alignas(16) uint32_t sched[NPAIR][MAX_ITEMS];
};


constexpr uint32_t SB = 1024;
constexpr uint32_t OFF_A = 0;
constexpr uint32_t OFF_B = 65536;
constexpr uint32_t OFF_STG = 196608;
constexpr uint32_t OFF_HALO = 229376;
constexpr uint32_t OFF_BAR = 231424;
constexpr uint32_t OFF_MASK = OFF_BAR + 256;
constexpr uint32_t OFF_LIST = OFF_BAR + 512;
constexpr uint32_t OFF_FILLS = OFF_BAR + 608;
constexpr uint32_t SMEM_BYTES = OFF_BAR + 640;
enum { B_FULL = 0, B_EMPTY = 4, B_QEMPTY = 8, B_STGE = 10, B_STGF = 12, B_FIN = 14, B_QFULL = 16, B_QX = 17, B_LEAD = 18, B_HFULL = 19, B_HEMPTY = 20, B_RELF = 21, B_RELE = 23, B_COUNT = 25 };
__host__ __device__ constexpr uint32_t BAR(int b) { return OFF_BAR + b * 8; }
__host__ __device__ constexpr int bar_count(int b) { return b < B_EMPTY ? 1 : b < B_QEMPTY ? 4 : b < B_STGE ? 8 : b < B_STGF ? 1 : b < B_QFULL ? 4 : b == B_QX ? 2 : 1; }
constexpr int REG_CONS = 232, REG_PROD = 40;
constexpr int PACE_MAX = 1100;
constexpr int WATCH_NS = 250;
constexpr int EARLYN = 3;
constexpr int HLATE = 3;
constexpr int STGA = 3, STGB = 8, STGAL = 4, STGBL = 12;
constexpr int JSPLIT = 14, JEDGE = 14, JP = 14, JDIAG = 10, JDIAG2 = 8;

__device__ __forceinline__ uint32_t smem_u32(const void* p) { return (uint32_t)__cvta_generic_to_shared(p); }
__device__ __forceinline__ void wg_fence() { asm volatile("wgmma.fence.sync.aligned;" ::: "memory"); }
__device__ __forceinline__ void wg_commit() { asm volatile("wgmma.commit_group.sync.aligned;" ::: "memory"); }
template <int N> __device__ __forceinline__ void wg_wait() { asm volatile("wgmma.wait_group.sync.aligned %0;" ::"n"(N) : "memory"); }
__device__ __forceinline__ uint64_t desc(uint32_t lo) { uint64_t d; asm volatile("mov.b64 %0, {%1, 0x40000040};" : "=l"(d) : "r"(lo)); return d; }
__host__ __device__ constexpr uint32_t dlo(uint32_t off, uint32_t lbo) { return (off >> 4) | ((lbo >> 4) << 16); }
template <uint32_t O> __device__ __forceinline__ void mbar_init(uint32_t a, uint32_t cnt) { asm volatile("mbarrier.init.shared::cta.b64 [%0+%2], %1;" ::"r"(a), "r"(cnt), "n"(O) : "memory"); }
template <uint32_t O> __device__ __forceinline__ void mbar_expect_tx(uint32_t a, uint32_t bytes) { asm volatile("mbarrier.arrive.expect_tx.shared::cta.b64 _, [%0+%2], %1;" ::"r"(a), "r"(bytes), "n"(O) : "memory"); }
template <uint32_t O> __device__ __forceinline__ void mbar_arrive_if(uint32_t a, bool pred) {
  asm volatile("{\n.reg .pred p;\nsetp.ne.u32 p, %1, 0;\n@p mbarrier.arrive.shared::cta.b64 _, [%0+%2];\n}\n" ::"r"(a), "r"((uint32_t)pred), "n"(O) : "memory");
}
template <uint32_t O> __device__ __forceinline__ void mbar_arrive_cl(uint32_t a, uint32_t off = 0) {
  asm volatile("{\n.reg .pred p;\nsetp.ne.u32 p, %2, 0;\n@p mbarrier.arrive.shared::cluster.b64 _, [%0+%1];\n}\n" ::"r"(a + off), "n"(O), "r"(a) : "memory");
}
template <uint32_t O> __device__ __forceinline__ bool mbar_test(uint32_t a, uint32_t parity) {
  uint32_t ok;
  asm volatile("{\n.reg .pred p;\nmbarrier.test_wait.parity.shared::cta.b64 p, [%1+%3], %2;\nselp.u32 %0, 1, 0, p;\n}\n" : "=r"(ok) : "r"(a), "r"(parity), "n"(O) : "memory");
  return ok;
}
template <uint32_t O> __device__ __forceinline__ void mbar_wait(uint32_t a, uint32_t parity) {
  asm volatile("{\n.reg .pred p;\nWAIT_%=:\nmbarrier.try_wait.parity.shared::cta.b64 p, [%0+%2], %1;\n@!p bra WAIT_%=;\n}\n" ::"r"(a), "r"(parity), "n"(O) : "memory");
}
template <uint32_t O> __device__ __forceinline__ void mbar_wait_b(uint32_t a, uint32_t parity) {
  asm volatile("{\n.reg .pred p, q;\n.reg .u32 n;\nmov.u32 n, 0;\nWAIT_%=:\nadd.u32 n, n, 1;\nmbarrier.try_wait.parity.shared::cta.b64 p, [%0+%2], %1;\n"
               "setp.lt.u32 q, n, 4194304;\nand.pred q, q, !p;\n@q bra WAIT_%=;\n@!p st.shared.u32 [%0+1], n;\n}\n" ::"r"(a), "r"(parity), "n"(O) : "memory");
}
template <uint32_t O> __device__ __forceinline__ void mbar_wait_long(uint32_t a, uint32_t parity) {
  asm volatile("{\n.reg .pred p, q;\n.reg .u32 n;\nmov.u32 n, 0;\nWAIT_%=:\nadd.u32 n, n, 1;\nmbarrier.try_wait.parity.shared::cta.b64 p, [%0+%2], %1, 4000;\n"
               "setp.lt.u32 q, n, 524288;\nand.pred q, q, !p;\n@q bra WAIT_%=;\n@!p st.shared.u32 [%0+1], n;\n}\n" ::"r"(a), "r"(parity), "n"(O) : "memory");
}
__device__ __forceinline__ void tma_load_2d(uint32_t dst, const CUtensorMap* tm, int c0, int c1, uint32_t bar) {
  asm volatile("cp.async.bulk.tensor.2d.shared::cluster.global.mbarrier::complete_tx::bytes [%0], [%1, {%3, %4}], [%2];" ::"r"(dst), "l"(tm), "r"(bar), "r"(c0), "r"(c1) : "memory");
}
__device__ __forceinline__ void tma_load_3d(uint32_t dst, const CUtensorMap* tm, int c0, int c1, int c2, uint32_t bar) {
  asm volatile("cp.async.bulk.tensor.3d.shared::cluster.global.mbarrier::complete_tx::bytes [%0], [%1, {%3, %4, %5}], [%2];" ::"r"(dst), "l"(tm), "r"(bar), "r"(c0), "r"(c1), "r"(c2) : "memory");
}
#define FILL_HEAD "{\n.reg .pred p, q;\n.reg .u32 n;\nmov.u32 n, 0;\nWAIT_%=:\nadd.u32 n, n, 1;\nmbarrier.try_wait.parity.shared::cta.b64 p, [%0+%1], %3;\n" \
                  "setp.lt.u32 q, n, 4194304;\nand.pred q, q, !p;\n@q bra WAIT_%=;\n@!p st.shared.u32 [%0+1], n;\nelect.sync _|p, 0xffffffff;\n" \
                  "@p mbarrier.arrive.expect_tx.shared::cta.b64 _, [%2], %4;\n"
__device__ __forceinline__ void fill_gemm(uint32_t bb, uint32_t parity, uint32_t bytes, uint32_t dstb, const CUtensorMap* mb, int b0, int b1, int b2, uint32_t dsta, const CUtensorMap* ma, int a0, int a1, uint64_t pb, uint64_t pa) {
  asm volatile(FILL_HEAD
               "@p cp.async.bulk.tensor.3d.shared::cluster.global.mbarrier::complete_tx::bytes.multicast::cluster.L2::cache_hint [%5], [%6, {%7, %8, %9}], [%2], %14, %15;\n"
               "@p cp.async.bulk.tensor.2d.shared::cluster.global.mbarrier::complete_tx::bytes.L2::cache_hint [%10], [%11, {%12, %13}], [%2], %16;\n}\n"
               ::"r"(bb), "n"(BAR(B_EMPTY)), "r"(bb + BAR(B_FULL)), "r"(parity), "r"(bytes), "r"(dstb), "l"(mb), "r"(b0), "r"(b1), "r"(b2), "r"(dsta), "l"(ma), "r"(a0), "r"(a1), "h"((uint16_t)3), "l"(pb), "l"(pa) : "memory");
}
__device__ __forceinline__ void fill_kv(uint32_t bb, uint32_t parity, uint32_t dst, const CUtensorMap* m, int c0, int c1, uint16_t mask, uint64_t pol) {
  asm volatile(FILL_HEAD
               "@p cp.async.bulk.tensor.2d.shared::cluster.global.mbarrier::complete_tx::bytes.multicast::cluster.L2::cache_hint [%5], [%6, {%7, %8}], [%2], %9, %10;\n}\n"
               ::"r"(bb), "n"(BAR(B_EMPTY)), "r"(bb + BAR(B_FULL)), "r"(parity), "r"(32768), "r"(dst), "l"(m), "r"(c0), "r"(c1), "h"(mask), "l"(pol) : "memory");
}
__device__ __forceinline__ void tma_load_2d_h(uint32_t dst, const CUtensorMap* tm, int c0, int c1, uint32_t bar, uint64_t pol) {
  asm volatile("{\n.reg .pred p;\nelect.sync _|p, 0xffffffff;\n@p cp.async.bulk.tensor.2d.shared::cluster.global.mbarrier::complete_tx::bytes.L2::cache_hint [%0], [%1, {%3, %4}], [%2], %5;\n}\n" ::"r"(dst), "l"(tm), "r"(bar), "r"(c0), "r"(c1), "l"(pol) : "memory");
}
__device__ __forceinline__ void tma_store_3d(const CUtensorMap* tm, uint32_t src, int c0, int c1, int c2, uint64_t pol) {
  asm volatile("{\n.reg .pred p;\nelect.sync _|p, 0xffffffff;\n@p cp.async.bulk.tensor.3d.global.shared::cta.bulk_group.L2::cache_hint [%0, {%2, %3, %4}], [%1], %5;\n}\n" ::"l"(tm), "r"(src), "r"(c0), "r"(c1), "r"(c2), "l"(pol) : "memory");
}
__device__ __forceinline__ void bulk_load(uint32_t dst, const void* src, uint32_t bytes, uint32_t bar) {
  asm volatile("{\n.reg .pred p;\nelect.sync _|p, 0xffffffff;\n@p cp.async.bulk.shared::cluster.global.mbarrier::complete_tx::bytes [%0], [%1], %2, [%3];\n}\n" ::"r"(dst), "l"(src), "r"(bytes), "r"(bar) : "memory");
}
__device__ __forceinline__ void bulk_store(void* dst, uint32_t src, uint32_t bytes) {
  asm volatile("{\n.reg .pred p;\nelect.sync _|p, 0xffffffff;\n@p cp.async.bulk.global.shared::cta.bulk_group [%0], [%1], %2;\n}\n" ::"l"(dst), "r"(src), "r"(bytes) : "memory");
}
__device__ __forceinline__ void bulk_send(uint32_t dst, uint32_t src, uint32_t bytes, uint32_t bar) {
  asm volatile("{\n.reg .pred p;\nelect.sync _|p, 0xffffffff;\n@p cp.async.bulk.shared::cluster.shared::cta.mbarrier::complete_tx::bytes [%0], [%1], %2, [%3];\n}\n" ::"r"(dst), "r"(src), "r"(bytes), "r"(bar) : "memory");
}
__device__ __forceinline__ uint64_t policy_evict_first() { uint64_t p; asm volatile("createpolicy.fractional.L2::evict_first.b64 %0, 1.0;" : "=l"(p)); return p; }
constexpr uint64_t POL_NORMAL = 0x1000000000000000ull;
__device__ __forceinline__ uint32_t mapa(uint32_t addr, uint32_t rank) { uint32_t r; asm("mapa.shared::cluster.u32 %0, %1, %2;" : "=r"(r) : "r"(addr), "r"(rank)); return r; }
__device__ __forceinline__ void cluster_arrive_relaxed() { asm volatile("barrier.cluster.arrive.relaxed.aligned;" ::: "memory"); }
__device__ __forceinline__ void cluster_arrive() { asm volatile("barrier.cluster.arrive.release.aligned;" ::: "memory"); }
__device__ __forceinline__ void cluster_wait() { asm volatile("barrier.cluster.wait.acquire.aligned;" ::: "memory"); }
__device__ __forceinline__ void bulk_commit() { asm volatile("cp.async.bulk.commit_group;" ::: "memory"); }
template <int N> __device__ __forceinline__ void bulk_wait_read() { asm volatile("cp.async.bulk.wait_group.read %0;" ::"n"(N) : "memory"); }
__device__ __forceinline__ void bulk_wait_all() { asm volatile("cp.async.bulk.wait_group 0;" ::: "memory"); }
__device__ __forceinline__ void fence_async_smem() { asm volatile("fence.proxy.async.shared::cta;" ::: "memory"); }
__device__ __forceinline__ void fence_async_glob() { asm volatile("fence.proxy.async.global;" ::: "memory"); }
__device__ __forceinline__ void flag_toggle(uint32_t* p, uint32_t v) { asm volatile("{\n.reg .pred p;\nelect.sync _|p, 0xffffffff;\n@p red.release.gpu.global.xor.b32 [%0], %1;\n}\n" ::"l"(p), "r"(v) : "memory"); }
template <uint32_t O> __device__ __forceinline__ uint32_t lds_acquire(uint32_t a) { uint32_t v; asm volatile("ld.acquire.cta.shared::cta.u32 %0, [%1+%2];" : "=r"(v) : "r"(a), "n"(O) : "memory"); return v; }
__device__ __forceinline__ uint32_t item_full(uint32_t sb, int idx) {
  uint32_t c;
  asm volatile("ld.shared.u32 %0, [%1+%2];" : "=r"(c) : "r"(sb + idx * 4), "n"(OFF_LIST));
  return __reduce_or_sync(0xffffffffu, c);
}
__device__ __forceinline__ uint32_t item(uint32_t sb, int idx) { return item_full(sb, idx) & 4095; }
template <int N> __device__ __forceinline__ void reg_alloc() { asm volatile("setmaxnreg.inc.sync.aligned.u32 %0;" ::"n"(N)); }
template <int N> __device__ __forceinline__ void reg_dealloc() { asm volatile("setmaxnreg.dec.sync.aligned.u32 %0;" ::"n"(N)); }
template <int I0, int I1, int N> __device__ __forceinline__ void fence_regs(float (&d)[N]) {
#pragma unroll
  for (int i = I0; i < I1; i++) asm volatile("" : "+f"(d[i])::"memory");
}
template <int N> __device__ __forceinline__ void fence_regs(float (&d)[N]) { fence_regs<0, N, N>(d); }
template <int N> __device__ __forceinline__ void fence_regs(uint32_t (&d)[N]) {
#pragma unroll
  for (int i = 0; i < N; i++) asm volatile("" : "+r"(d[i])::"memory");
}
__device__ __forceinline__ uint32_t pack_bf16(float lo, float hi) { uint32_t r; asm("cvt.rn.bf16x2.f32 %0, %1, %2;" : "=r"(r) : "f"(hi), "f"(lo)); return r; }
__device__ __forceinline__ uint32_t v_pack(float lo, float hi) { uint32_t r; asm volatile("cvt.rn.bf16x2.f32 %0, %1, %2;" : "=r"(r) : "f"(hi), "f"(lo)); return r; }
template <uint32_t O> __device__ __forceinline__ void stmatrix_x4(uint32_t a, uint32_t r0, uint32_t r1, uint32_t r2, uint32_t r3) {
  asm volatile("stmatrix.sync.aligned.m8n8.x4.shared.b16 [%0+%5], {%1, %2, %3, %4};" ::"r"(a), "r"(r0), "r"(r1), "r"(r2), "r"(r3), "n"(O) : "memory");
}
template <uint32_t O> __device__ __forceinline__ void stmatrix_x4_after(uint32_t a, uint32_t r0, uint32_t r1, uint32_t r2, uint32_t r3, float dep, uint32_t on) {
  asm volatile("{\n.reg .pred p, q;\n.reg .u32 a;\nsetp.ne.u32 p, %7, 0;\nsetp.ne.u32 q, %6, 0xffffffff;\nselp.u32 a, %0, 0, q;\n@p stmatrix.sync.aligned.m8n8.x4.shared.b16 [a+%5], {%1, %2, %3, %4};\n}\n"
               ::"r"(a), "r"(r0), "r"(r1), "r"(r2), "r"(r3), "n"(O), "r"(__float_as_uint(dep)), "r"(on) : "memory");
}
template <uint32_t O> __device__ __forceinline__ void stmatrix_x4_trans(uint32_t a, uint32_t r0, uint32_t r1, uint32_t r2, uint32_t r3) {
  asm volatile("stmatrix.sync.aligned.m8n8.x4.trans.shared.b16 [%0+%5], {%1, %2, %3, %4};" ::"r"(a), "r"(r0), "r"(r1), "r"(r2), "r"(r3), "n"(O) : "memory");
}
template <uint32_t O> __device__ __forceinline__ void sts64(uint32_t a, const uint32_t* r) { asm volatile("st.shared.v2.u32 [%0+%3], {%1, %2};" ::"r"(a), "r"(r[0]), "r"(r[1]), "n"(O) : "memory"); }
template <uint32_t O> __device__ __forceinline__ void lds64(uint32_t* r, uint32_t a) { asm volatile("ld.shared.v2.u32 {%0, %1}, [%2+%3];" : "=r"(r[0]), "=r"(r[1]) : "r"(a), "n"(O) : "memory"); }
template <uint32_t O> __device__ __forceinline__ void lds128(uint32_t* r, uint32_t a) { asm volatile("ld.shared.v4.u32 {%0, %1, %2, %3}, [%4+%5];" : "=r"(r[0]), "=r"(r[1]), "=r"(r[2]), "=r"(r[3]) : "r"(a), "n"(O) : "memory"); }
__device__ __forceinline__ uint32_t transpose8(uint32_t a) { uint32_t d; asm volatile("movmatrix.sync.aligned.m8n8.trans.b16 %0, %1;" : "=r"(d) : "r"(a)); return d; }
__device__ __forceinline__ float ex2(float x) { float y; asm("ex2.approx.ftz.f32 %0, %1;" : "=f"(y) : "f"(x)); return y; }
__device__ __forceinline__ float rcp(float x) { float y; asm("rcp.approx.ftz.f32 %0, %1;" : "=f"(y) : "f"(x)); return y; }
__device__ __forceinline__ void bar_sync(int id, int n) { asm volatile("bar.sync %0, %1;" ::"r"(id), "r"(n) : "memory"); }
__device__ __forceinline__ void bar_arrive(int id, int n) { asm volatile("bar.arrive %0, %1;" ::"r"(id), "r"(n) : "memory"); }
__device__ __forceinline__ void mma16816(float (&c)[4], uint32_t a0, uint32_t a1, uint32_t a2, uint32_t a3, uint32_t b0, uint32_t b1) {
  asm("mma.sync.aligned.m16n8k16.row.col.f32.bf16.bf16.f32 {%0, %1, %2, %3}, {%4, %5, %6, %7}, {%8, %9}, {%0, %1, %2, %3};"
      : "+f"(c[0]), "+f"(c[1]), "+f"(c[2]), "+f"(c[3]) : "r"(a0), "r"(a1), "r"(a2), "r"(a3), "r"(b0), "r"(b1));
}
__device__ __forceinline__ void mma16816z(float (&c)[4], uint32_t a0, uint32_t a1, uint32_t a2, uint32_t a3, uint32_t b0, uint32_t b1, const uint32_t (&z)[4]) {
  asm("mma.sync.aligned.m16n8k16.row.col.f32.bf16.bf16.f32 {%0, %1, %2, %3}, {%4, %5, %6, %7}, {%8, %9}, {%10, %11, %12, %13};"
      : "=f"(c[0]), "=f"(c[1]), "=f"(c[2]), "=f"(c[3]) : "r"(a0), "r"(a1), "r"(a2), "r"(a3), "r"(b0), "r"(b1),
        "f"(__uint_as_float(z[0])), "f"(__uint_as_float(z[1])), "f"(__uint_as_float(z[2])), "f"(__uint_as_float(z[3])));
}
__device__ __forceinline__ uint4 ldg128(const void* p) { uint4 v; asm volatile("ld.global.cg.v4.u32 {%0, %1, %2, %3}, [%4];" : "=r"(v.x), "=r"(v.y), "=r"(v.z), "=r"(v.w) : "l"(p) : "memory"); return v; }
__device__ __forceinline__ uint32_t ldg16(const void* p) { uint16_t v; asm volatile("ld.global.cg.u16 %0, [%1];" : "=h"(v) : "l"(p) : "memory"); return v; }
__device__ __forceinline__ float quad_sum(float v) {
  v += __shfl_xor_sync(0xffffffffu, v, 1);
  v += __shfl_xor_sync(0xffffffffu, v, 2);
  return v;
}
__device__ __forceinline__ bool elect_one() { uint32_t p; asm volatile("{\n.reg .pred p;\nelect.sync _|p, 0xffffffff;\nselp.u32 %0, 1, 0, p;\n}\n" : "=r"(p)); return p; }
#define UNLIKELY(x) __builtin_expect(!!(x), 0)

template <int OA, int OB> __device__ __forceinline__ void wg_gemm_init(float (&d)[128], uint64_t da, uint64_t db) {
  asm volatile("{\n.reg .pred p;\n.reg .b64 da, db;\nadd.s64 da, %128, %129;\nadd.s64 db, %130, %131;\nsetp.ne.b32 p, 0, 0;\n"
    "wgmma.mma_async.sync.aligned.m64n256k16.f32.bf16.bf16 {"
    "%0, %1, %2, %3, %4, %5, %6, %7, %8, %9, %10, %11, %12, %13, %14, %15, %16, %17, %18, %19, %20, %21, %22, %23, %24, %25, %26, %27, %28, %29, %30, %31, "
    "%32, %33, %34, %35, %36, %37, %38, %39, %40, %41, %42, %43, %44, %45, %46, %47, %48, %49, %50, %51, %52, %53, %54, %55, %56, %57, %58, %59, %60, %61, %62, %63, "
    "%64, %65, %66, %67, %68, %69, %70, %71, %72, %73, %74, %75, %76, %77, %78, %79, %80, %81, %82, %83, %84, %85, %86, %87, %88, %89, %90, %91, %92, %93, %94, %95, "
    "%96, %97, %98, %99, %100, %101, %102, %103, %104, %105, %106, %107, %108, %109, %110, %111, %112, %113, %114, %115, %116, %117, %118, %119, %120, %121, %122, %123, %124, %125, %126, %127}, "
    "da, db, p, 1, 1, 0, 1;\n}\n"
    : "=f"(d[0]), "=f"(d[1]), "=f"(d[2]), "=f"(d[3]), "=f"(d[4]), "=f"(d[5]), "=f"(d[6]), "=f"(d[7]), "=f"(d[8]), "=f"(d[9]), "=f"(d[10]), "=f"(d[11]), "=f"(d[12]), "=f"(d[13]), "=f"(d[14]), "=f"(d[15]),
      "=f"(d[16]), "=f"(d[17]), "=f"(d[18]), "=f"(d[19]), "=f"(d[20]), "=f"(d[21]), "=f"(d[22]), "=f"(d[23]), "=f"(d[24]), "=f"(d[25]), "=f"(d[26]), "=f"(d[27]), "=f"(d[28]), "=f"(d[29]), "=f"(d[30]), "=f"(d[31]),
      "=f"(d[32]), "=f"(d[33]), "=f"(d[34]), "=f"(d[35]), "=f"(d[36]), "=f"(d[37]), "=f"(d[38]), "=f"(d[39]), "=f"(d[40]), "=f"(d[41]), "=f"(d[42]), "=f"(d[43]), "=f"(d[44]), "=f"(d[45]), "=f"(d[46]), "=f"(d[47]),
      "=f"(d[48]), "=f"(d[49]), "=f"(d[50]), "=f"(d[51]), "=f"(d[52]), "=f"(d[53]), "=f"(d[54]), "=f"(d[55]), "=f"(d[56]), "=f"(d[57]), "=f"(d[58]), "=f"(d[59]), "=f"(d[60]), "=f"(d[61]), "=f"(d[62]), "=f"(d[63]),
      "=f"(d[64]), "=f"(d[65]), "=f"(d[66]), "=f"(d[67]), "=f"(d[68]), "=f"(d[69]), "=f"(d[70]), "=f"(d[71]), "=f"(d[72]), "=f"(d[73]), "=f"(d[74]), "=f"(d[75]), "=f"(d[76]), "=f"(d[77]), "=f"(d[78]), "=f"(d[79]),
      "=f"(d[80]), "=f"(d[81]), "=f"(d[82]), "=f"(d[83]), "=f"(d[84]), "=f"(d[85]), "=f"(d[86]), "=f"(d[87]), "=f"(d[88]), "=f"(d[89]), "=f"(d[90]), "=f"(d[91]), "=f"(d[92]), "=f"(d[93]), "=f"(d[94]), "=f"(d[95]),
      "=f"(d[96]), "=f"(d[97]), "=f"(d[98]), "=f"(d[99]), "=f"(d[100]), "=f"(d[101]), "=f"(d[102]), "=f"(d[103]), "=f"(d[104]), "=f"(d[105]), "=f"(d[106]), "=f"(d[107]), "=f"(d[108]), "=f"(d[109]), "=f"(d[110]), "=f"(d[111]),
      "=f"(d[112]), "=f"(d[113]), "=f"(d[114]), "=f"(d[115]), "=f"(d[116]), "=f"(d[117]), "=f"(d[118]), "=f"(d[119]), "=f"(d[120]), "=f"(d[121]), "=f"(d[122]), "=f"(d[123]), "=f"(d[124]), "=f"(d[125]), "=f"(d[126]), "=f"(d[127])
    : "l"(da), "n"(OA), "l"(db), "n"(OB));
}
template <int OA, int OB> __device__ __forceinline__ void wg_gemm_acc(float (&d)[128], uint64_t da, uint64_t db) {
  asm volatile("{\n.reg .pred p;\n.reg .b64 da, db;\nadd.s64 da, %128, %129;\nadd.s64 db, %130, %131;\nsetp.eq.b32 p, 0, 0;\n"
    "wgmma.mma_async.sync.aligned.m64n256k16.f32.bf16.bf16 {"
    "%0, %1, %2, %3, %4, %5, %6, %7, %8, %9, %10, %11, %12, %13, %14, %15, %16, %17, %18, %19, %20, %21, %22, %23, %24, %25, %26, %27, %28, %29, %30, %31, "
    "%32, %33, %34, %35, %36, %37, %38, %39, %40, %41, %42, %43, %44, %45, %46, %47, %48, %49, %50, %51, %52, %53, %54, %55, %56, %57, %58, %59, %60, %61, %62, %63, "
    "%64, %65, %66, %67, %68, %69, %70, %71, %72, %73, %74, %75, %76, %77, %78, %79, %80, %81, %82, %83, %84, %85, %86, %87, %88, %89, %90, %91, %92, %93, %94, %95, "
    "%96, %97, %98, %99, %100, %101, %102, %103, %104, %105, %106, %107, %108, %109, %110, %111, %112, %113, %114, %115, %116, %117, %118, %119, %120, %121, %122, %123, %124, %125, %126, %127}, "
    "da, db, p, 1, 1, 0, 1;\n}\n"
    : "+f"(d[0]), "+f"(d[1]), "+f"(d[2]), "+f"(d[3]), "+f"(d[4]), "+f"(d[5]), "+f"(d[6]), "+f"(d[7]), "+f"(d[8]), "+f"(d[9]), "+f"(d[10]), "+f"(d[11]), "+f"(d[12]), "+f"(d[13]), "+f"(d[14]), "+f"(d[15]),
      "+f"(d[16]), "+f"(d[17]), "+f"(d[18]), "+f"(d[19]), "+f"(d[20]), "+f"(d[21]), "+f"(d[22]), "+f"(d[23]), "+f"(d[24]), "+f"(d[25]), "+f"(d[26]), "+f"(d[27]), "+f"(d[28]), "+f"(d[29]), "+f"(d[30]), "+f"(d[31]),
      "+f"(d[32]), "+f"(d[33]), "+f"(d[34]), "+f"(d[35]), "+f"(d[36]), "+f"(d[37]), "+f"(d[38]), "+f"(d[39]), "+f"(d[40]), "+f"(d[41]), "+f"(d[42]), "+f"(d[43]), "+f"(d[44]), "+f"(d[45]), "+f"(d[46]), "+f"(d[47]),
      "+f"(d[48]), "+f"(d[49]), "+f"(d[50]), "+f"(d[51]), "+f"(d[52]), "+f"(d[53]), "+f"(d[54]), "+f"(d[55]), "+f"(d[56]), "+f"(d[57]), "+f"(d[58]), "+f"(d[59]), "+f"(d[60]), "+f"(d[61]), "+f"(d[62]), "+f"(d[63]),
      "+f"(d[64]), "+f"(d[65]), "+f"(d[66]), "+f"(d[67]), "+f"(d[68]), "+f"(d[69]), "+f"(d[70]), "+f"(d[71]), "+f"(d[72]), "+f"(d[73]), "+f"(d[74]), "+f"(d[75]), "+f"(d[76]), "+f"(d[77]), "+f"(d[78]), "+f"(d[79]),
      "+f"(d[80]), "+f"(d[81]), "+f"(d[82]), "+f"(d[83]), "+f"(d[84]), "+f"(d[85]), "+f"(d[86]), "+f"(d[87]), "+f"(d[88]), "+f"(d[89]), "+f"(d[90]), "+f"(d[91]), "+f"(d[92]), "+f"(d[93]), "+f"(d[94]), "+f"(d[95]),
      "+f"(d[96]), "+f"(d[97]), "+f"(d[98]), "+f"(d[99]), "+f"(d[100]), "+f"(d[101]), "+f"(d[102]), "+f"(d[103]), "+f"(d[104]), "+f"(d[105]), "+f"(d[106]), "+f"(d[107]), "+f"(d[108]), "+f"(d[109]), "+f"(d[110]), "+f"(d[111]),
      "+f"(d[112]), "+f"(d[113]), "+f"(d[114]), "+f"(d[115]), "+f"(d[116]), "+f"(d[117]), "+f"(d[118]), "+f"(d[119]), "+f"(d[120]), "+f"(d[121]), "+f"(d[122]), "+f"(d[123]), "+f"(d[124]), "+f"(d[125]), "+f"(d[126]), "+f"(d[127])
    : "l"(da), "n"(OA), "l"(db), "n"(OB));
}
template <int OA, int OB> __device__ __forceinline__ void wg_gemm_init(float (&d)[96], uint64_t da, uint64_t db) {
  asm volatile("{\n.reg .pred p;\n.reg .b64 da, db;\nadd.s64 da, %96, %97;\nadd.s64 db, %98, %99;\nsetp.ne.b32 p, 0, 0;\n"
    "wgmma.mma_async.sync.aligned.m64n192k16.f32.bf16.bf16 {"
    "%0, %1, %2, %3, %4, %5, %6, %7, %8, %9, %10, %11, %12, %13, %14, %15, %16, %17, %18, %19, %20, %21, %22, %23, %24, %25, %26, %27, %28, %29, %30, %31, "
    "%32, %33, %34, %35, %36, %37, %38, %39, %40, %41, %42, %43, %44, %45, %46, %47, %48, %49, %50, %51, %52, %53, %54, %55, %56, %57, %58, %59, %60, %61, %62, %63, "
    "%64, %65, %66, %67, %68, %69, %70, %71, %72, %73, %74, %75, %76, %77, %78, %79, %80, %81, %82, %83, %84, %85, %86, %87, %88, %89, %90, %91, %92, %93, %94, %95}, "
    "da, db, p, 1, 1, 0, 1;\n}\n"
    : "=f"(d[0]), "=f"(d[1]), "=f"(d[2]), "=f"(d[3]), "=f"(d[4]), "=f"(d[5]), "=f"(d[6]), "=f"(d[7]), "=f"(d[8]), "=f"(d[9]), "=f"(d[10]), "=f"(d[11]), "=f"(d[12]), "=f"(d[13]), "=f"(d[14]), "=f"(d[15]),
      "=f"(d[16]), "=f"(d[17]), "=f"(d[18]), "=f"(d[19]), "=f"(d[20]), "=f"(d[21]), "=f"(d[22]), "=f"(d[23]), "=f"(d[24]), "=f"(d[25]), "=f"(d[26]), "=f"(d[27]), "=f"(d[28]), "=f"(d[29]), "=f"(d[30]), "=f"(d[31]),
      "=f"(d[32]), "=f"(d[33]), "=f"(d[34]), "=f"(d[35]), "=f"(d[36]), "=f"(d[37]), "=f"(d[38]), "=f"(d[39]), "=f"(d[40]), "=f"(d[41]), "=f"(d[42]), "=f"(d[43]), "=f"(d[44]), "=f"(d[45]), "=f"(d[46]), "=f"(d[47]),
      "=f"(d[48]), "=f"(d[49]), "=f"(d[50]), "=f"(d[51]), "=f"(d[52]), "=f"(d[53]), "=f"(d[54]), "=f"(d[55]), "=f"(d[56]), "=f"(d[57]), "=f"(d[58]), "=f"(d[59]), "=f"(d[60]), "=f"(d[61]), "=f"(d[62]), "=f"(d[63]),
      "=f"(d[64]), "=f"(d[65]), "=f"(d[66]), "=f"(d[67]), "=f"(d[68]), "=f"(d[69]), "=f"(d[70]), "=f"(d[71]), "=f"(d[72]), "=f"(d[73]), "=f"(d[74]), "=f"(d[75]), "=f"(d[76]), "=f"(d[77]), "=f"(d[78]), "=f"(d[79]),
      "=f"(d[80]), "=f"(d[81]), "=f"(d[82]), "=f"(d[83]), "=f"(d[84]), "=f"(d[85]), "=f"(d[86]), "=f"(d[87]), "=f"(d[88]), "=f"(d[89]), "=f"(d[90]), "=f"(d[91]), "=f"(d[92]), "=f"(d[93]), "=f"(d[94]), "=f"(d[95])
    : "l"(da), "n"(OA), "l"(db), "n"(OB));
}
template <int OA, int OB> __device__ __forceinline__ void wg_gemm_acc(float (&d)[96], uint64_t da, uint64_t db) {
  asm volatile("{\n.reg .pred p;\n.reg .b64 da, db;\nadd.s64 da, %96, %97;\nadd.s64 db, %98, %99;\nsetp.eq.b32 p, 0, 0;\n"
    "wgmma.mma_async.sync.aligned.m64n192k16.f32.bf16.bf16 {"
    "%0, %1, %2, %3, %4, %5, %6, %7, %8, %9, %10, %11, %12, %13, %14, %15, %16, %17, %18, %19, %20, %21, %22, %23, %24, %25, %26, %27, %28, %29, %30, %31, "
    "%32, %33, %34, %35, %36, %37, %38, %39, %40, %41, %42, %43, %44, %45, %46, %47, %48, %49, %50, %51, %52, %53, %54, %55, %56, %57, %58, %59, %60, %61, %62, %63, "
    "%64, %65, %66, %67, %68, %69, %70, %71, %72, %73, %74, %75, %76, %77, %78, %79, %80, %81, %82, %83, %84, %85, %86, %87, %88, %89, %90, %91, %92, %93, %94, %95}, "
    "da, db, p, 1, 1, 0, 1;\n}\n"
    : "+f"(d[0]), "+f"(d[1]), "+f"(d[2]), "+f"(d[3]), "+f"(d[4]), "+f"(d[5]), "+f"(d[6]), "+f"(d[7]), "+f"(d[8]), "+f"(d[9]), "+f"(d[10]), "+f"(d[11]), "+f"(d[12]), "+f"(d[13]), "+f"(d[14]), "+f"(d[15]),
      "+f"(d[16]), "+f"(d[17]), "+f"(d[18]), "+f"(d[19]), "+f"(d[20]), "+f"(d[21]), "+f"(d[22]), "+f"(d[23]), "+f"(d[24]), "+f"(d[25]), "+f"(d[26]), "+f"(d[27]), "+f"(d[28]), "+f"(d[29]), "+f"(d[30]), "+f"(d[31]),
      "+f"(d[32]), "+f"(d[33]), "+f"(d[34]), "+f"(d[35]), "+f"(d[36]), "+f"(d[37]), "+f"(d[38]), "+f"(d[39]), "+f"(d[40]), "+f"(d[41]), "+f"(d[42]), "+f"(d[43]), "+f"(d[44]), "+f"(d[45]), "+f"(d[46]), "+f"(d[47]),
      "+f"(d[48]), "+f"(d[49]), "+f"(d[50]), "+f"(d[51]), "+f"(d[52]), "+f"(d[53]), "+f"(d[54]), "+f"(d[55]), "+f"(d[56]), "+f"(d[57]), "+f"(d[58]), "+f"(d[59]), "+f"(d[60]), "+f"(d[61]), "+f"(d[62]), "+f"(d[63]),
      "+f"(d[64]), "+f"(d[65]), "+f"(d[66]), "+f"(d[67]), "+f"(d[68]), "+f"(d[69]), "+f"(d[70]), "+f"(d[71]), "+f"(d[72]), "+f"(d[73]), "+f"(d[74]), "+f"(d[75]), "+f"(d[76]), "+f"(d[77]), "+f"(d[78]), "+f"(d[79]),
      "+f"(d[80]), "+f"(d[81]), "+f"(d[82]), "+f"(d[83]), "+f"(d[84]), "+f"(d[85]), "+f"(d[86]), "+f"(d[87]), "+f"(d[88]), "+f"(d[89]), "+f"(d[90]), "+f"(d[91]), "+f"(d[92]), "+f"(d[93]), "+f"(d[94]), "+f"(d[95])
    : "l"(da), "n"(OA), "l"(db), "n"(OB));
}
template <int OA, int OB> __device__ __forceinline__ void wg_qk_init(float (&d)[64], uint64_t da, uint64_t db) {
  asm volatile("{\n.reg .pred p;\n.reg .b64 da, db;\nadd.s64 da, %64, %65;\nadd.s64 db, %66, %67;\nsetp.ne.b32 p, 0, 0;\n"
    "wgmma.mma_async.sync.aligned.m64n128k16.f32.bf16.bf16 {"
    "%0, %1, %2, %3, %4, %5, %6, %7, %8, %9, %10, %11, %12, %13, %14, %15, %16, %17, %18, %19, %20, %21, %22, %23, %24, %25, %26, %27, %28, %29, %30, %31, "
    "%32, %33, %34, %35, %36, %37, %38, %39, %40, %41, %42, %43, %44, %45, %46, %47, %48, %49, %50, %51, %52, %53, %54, %55, %56, %57, %58, %59, %60, %61, %62, %63}, "
    "da, db, p, 1, 1, 0, 0;\n}\n"
    : "=f"(d[0]), "=f"(d[1]), "=f"(d[2]), "=f"(d[3]), "=f"(d[4]), "=f"(d[5]), "=f"(d[6]), "=f"(d[7]), "=f"(d[8]), "=f"(d[9]), "=f"(d[10]), "=f"(d[11]), "=f"(d[12]), "=f"(d[13]), "=f"(d[14]), "=f"(d[15]),
      "=f"(d[16]), "=f"(d[17]), "=f"(d[18]), "=f"(d[19]), "=f"(d[20]), "=f"(d[21]), "=f"(d[22]), "=f"(d[23]), "=f"(d[24]), "=f"(d[25]), "=f"(d[26]), "=f"(d[27]), "=f"(d[28]), "=f"(d[29]), "=f"(d[30]), "=f"(d[31]),
      "=f"(d[32]), "=f"(d[33]), "=f"(d[34]), "=f"(d[35]), "=f"(d[36]), "=f"(d[37]), "=f"(d[38]), "=f"(d[39]), "=f"(d[40]), "=f"(d[41]), "=f"(d[42]), "=f"(d[43]), "=f"(d[44]), "=f"(d[45]), "=f"(d[46]), "=f"(d[47]),
      "=f"(d[48]), "=f"(d[49]), "=f"(d[50]), "=f"(d[51]), "=f"(d[52]), "=f"(d[53]), "=f"(d[54]), "=f"(d[55]), "=f"(d[56]), "=f"(d[57]), "=f"(d[58]), "=f"(d[59]), "=f"(d[60]), "=f"(d[61]), "=f"(d[62]), "=f"(d[63])
    : "l"(da), "n"(OA), "l"(db), "n"(OB));
}
template <int OA, int OB> __device__ __forceinline__ void wg_qk_acc(float (&d)[64], uint64_t da, uint64_t db) {
  asm volatile("{\n.reg .pred p;\n.reg .b64 da, db;\nadd.s64 da, %64, %65;\nadd.s64 db, %66, %67;\nsetp.eq.b32 p, 0, 0;\n"
    "wgmma.mma_async.sync.aligned.m64n128k16.f32.bf16.bf16 {"
    "%0, %1, %2, %3, %4, %5, %6, %7, %8, %9, %10, %11, %12, %13, %14, %15, %16, %17, %18, %19, %20, %21, %22, %23, %24, %25, %26, %27, %28, %29, %30, %31, "
    "%32, %33, %34, %35, %36, %37, %38, %39, %40, %41, %42, %43, %44, %45, %46, %47, %48, %49, %50, %51, %52, %53, %54, %55, %56, %57, %58, %59, %60, %61, %62, %63}, "
    "da, db, p, 1, 1, 0, 0;\n}\n"
    : "+f"(d[0]), "+f"(d[1]), "+f"(d[2]), "+f"(d[3]), "+f"(d[4]), "+f"(d[5]), "+f"(d[6]), "+f"(d[7]), "+f"(d[8]), "+f"(d[9]), "+f"(d[10]), "+f"(d[11]), "+f"(d[12]), "+f"(d[13]), "+f"(d[14]), "+f"(d[15]),
      "+f"(d[16]), "+f"(d[17]), "+f"(d[18]), "+f"(d[19]), "+f"(d[20]), "+f"(d[21]), "+f"(d[22]), "+f"(d[23]), "+f"(d[24]), "+f"(d[25]), "+f"(d[26]), "+f"(d[27]), "+f"(d[28]), "+f"(d[29]), "+f"(d[30]), "+f"(d[31]),
      "+f"(d[32]), "+f"(d[33]), "+f"(d[34]), "+f"(d[35]), "+f"(d[36]), "+f"(d[37]), "+f"(d[38]), "+f"(d[39]), "+f"(d[40]), "+f"(d[41]), "+f"(d[42]), "+f"(d[43]), "+f"(d[44]), "+f"(d[45]), "+f"(d[46]), "+f"(d[47]),
      "+f"(d[48]), "+f"(d[49]), "+f"(d[50]), "+f"(d[51]), "+f"(d[52]), "+f"(d[53]), "+f"(d[54]), "+f"(d[55]), "+f"(d[56]), "+f"(d[57]), "+f"(d[58]), "+f"(d[59]), "+f"(d[60]), "+f"(d[61]), "+f"(d[62]), "+f"(d[63])
    : "l"(da), "n"(OA), "l"(db), "n"(OB));
}
template <int OA, int OB> __device__ __forceinline__ void wg_qk64_init(float (&d)[64], uint64_t da, uint64_t db) {
  asm volatile("{\n.reg .pred p;\n.reg .b64 da, db;\nadd.s64 da, %32, %33;\nadd.s64 db, %34, %35;\nsetp.ne.b32 p, 0, 0;\n"
    "wgmma.mma_async.sync.aligned.m64n64k16.f32.bf16.bf16 {"
    "%0, %1, %2, %3, %4, %5, %6, %7, %8, %9, %10, %11, %12, %13, %14, %15, %16, %17, %18, %19, %20, %21, %22, %23, %24, %25, %26, %27, %28, %29, %30, %31}, "
    "da, db, p, 1, 1, 0, 0;\n}\n"
    : "=f"(d[0]), "=f"(d[1]), "=f"(d[2]), "=f"(d[3]), "=f"(d[4]), "=f"(d[5]), "=f"(d[6]), "=f"(d[7]), "=f"(d[8]), "=f"(d[9]), "=f"(d[10]), "=f"(d[11]), "=f"(d[12]), "=f"(d[13]), "=f"(d[14]), "=f"(d[15]),
      "=f"(d[16]), "=f"(d[17]), "=f"(d[18]), "=f"(d[19]), "=f"(d[20]), "=f"(d[21]), "=f"(d[22]), "=f"(d[23]), "=f"(d[24]), "=f"(d[25]), "=f"(d[26]), "=f"(d[27]), "=f"(d[28]), "=f"(d[29]), "=f"(d[30]), "=f"(d[31])
    : "l"(da), "n"(OA), "l"(db), "n"(OB));
}
template <int OA, int OB> __device__ __forceinline__ void wg_qk64_acc(float (&d)[64], uint64_t da, uint64_t db) {
  asm volatile("{\n.reg .pred p;\n.reg .b64 da, db;\nadd.s64 da, %32, %33;\nadd.s64 db, %34, %35;\nsetp.eq.b32 p, 0, 0;\n"
    "wgmma.mma_async.sync.aligned.m64n64k16.f32.bf16.bf16 {"
    "%0, %1, %2, %3, %4, %5, %6, %7, %8, %9, %10, %11, %12, %13, %14, %15, %16, %17, %18, %19, %20, %21, %22, %23, %24, %25, %26, %27, %28, %29, %30, %31}, "
    "da, db, p, 1, 1, 0, 0;\n}\n"
    : "+f"(d[0]), "+f"(d[1]), "+f"(d[2]), "+f"(d[3]), "+f"(d[4]), "+f"(d[5]), "+f"(d[6]), "+f"(d[7]), "+f"(d[8]), "+f"(d[9]), "+f"(d[10]), "+f"(d[11]), "+f"(d[12]), "+f"(d[13]), "+f"(d[14]), "+f"(d[15]),
      "+f"(d[16]), "+f"(d[17]), "+f"(d[18]), "+f"(d[19]), "+f"(d[20]), "+f"(d[21]), "+f"(d[22]), "+f"(d[23]), "+f"(d[24]), "+f"(d[25]), "+f"(d[26]), "+f"(d[27]), "+f"(d[28]), "+f"(d[29]), "+f"(d[30]), "+f"(d[31])
    : "l"(da), "n"(OA), "l"(db), "n"(OB));
}
template <int OB> __device__ __forceinline__ void wg_pv_init(float (&d)[64], const uint32_t* a, uint64_t db) {
  asm volatile("{\n.reg .pred p;\n.reg .b64 da, db;\nadd.s64 db, %68, %69;\nsetp.ne.b32 p, 0, 0;\n"
    "wgmma.mma_async.sync.aligned.m64n128k16.f32.bf16.bf16 {"
    "%0, %1, %2, %3, %4, %5, %6, %7, %8, %9, %10, %11, %12, %13, %14, %15, %16, %17, %18, %19, %20, %21, %22, %23, %24, %25, %26, %27, %28, %29, %30, %31, "
    "%32, %33, %34, %35, %36, %37, %38, %39, %40, %41, %42, %43, %44, %45, %46, %47, %48, %49, %50, %51, %52, %53, %54, %55, %56, %57, %58, %59, %60, %61, %62, %63}, "
    "{%64, %65, %66, %67}, db, p, 1, 1, 1;\n}\n"
    : "=f"(d[0]), "=f"(d[1]), "=f"(d[2]), "=f"(d[3]), "=f"(d[4]), "=f"(d[5]), "=f"(d[6]), "=f"(d[7]), "=f"(d[8]), "=f"(d[9]), "=f"(d[10]), "=f"(d[11]), "=f"(d[12]), "=f"(d[13]), "=f"(d[14]), "=f"(d[15]),
      "=f"(d[16]), "=f"(d[17]), "=f"(d[18]), "=f"(d[19]), "=f"(d[20]), "=f"(d[21]), "=f"(d[22]), "=f"(d[23]), "=f"(d[24]), "=f"(d[25]), "=f"(d[26]), "=f"(d[27]), "=f"(d[28]), "=f"(d[29]), "=f"(d[30]), "=f"(d[31]),
      "=f"(d[32]), "=f"(d[33]), "=f"(d[34]), "=f"(d[35]), "=f"(d[36]), "=f"(d[37]), "=f"(d[38]), "=f"(d[39]), "=f"(d[40]), "=f"(d[41]), "=f"(d[42]), "=f"(d[43]), "=f"(d[44]), "=f"(d[45]), "=f"(d[46]), "=f"(d[47]),
      "=f"(d[48]), "=f"(d[49]), "=f"(d[50]), "=f"(d[51]), "=f"(d[52]), "=f"(d[53]), "=f"(d[54]), "=f"(d[55]), "=f"(d[56]), "=f"(d[57]), "=f"(d[58]), "=f"(d[59]), "=f"(d[60]), "=f"(d[61]), "=f"(d[62]), "=f"(d[63])
    : "r"(a[0]), "r"(a[1]), "r"(a[2]), "r"(a[3]), "l"(db), "n"(OB));
}
template <int OB> __device__ __forceinline__ void wg_pv_acc(float (&d)[64], const uint32_t* a, uint64_t db) {
  asm volatile("{\n.reg .pred p;\n.reg .b64 da, db;\nadd.s64 db, %68, %69;\nsetp.eq.b32 p, 0, 0;\n"
    "wgmma.mma_async.sync.aligned.m64n128k16.f32.bf16.bf16 {"
    "%0, %1, %2, %3, %4, %5, %6, %7, %8, %9, %10, %11, %12, %13, %14, %15, %16, %17, %18, %19, %20, %21, %22, %23, %24, %25, %26, %27, %28, %29, %30, %31, "
    "%32, %33, %34, %35, %36, %37, %38, %39, %40, %41, %42, %43, %44, %45, %46, %47, %48, %49, %50, %51, %52, %53, %54, %55, %56, %57, %58, %59, %60, %61, %62, %63}, "
    "{%64, %65, %66, %67}, db, p, 1, 1, 1;\n}\n"
    : "+f"(d[0]), "+f"(d[1]), "+f"(d[2]), "+f"(d[3]), "+f"(d[4]), "+f"(d[5]), "+f"(d[6]), "+f"(d[7]), "+f"(d[8]), "+f"(d[9]), "+f"(d[10]), "+f"(d[11]), "+f"(d[12]), "+f"(d[13]), "+f"(d[14]), "+f"(d[15]),
      "+f"(d[16]), "+f"(d[17]), "+f"(d[18]), "+f"(d[19]), "+f"(d[20]), "+f"(d[21]), "+f"(d[22]), "+f"(d[23]), "+f"(d[24]), "+f"(d[25]), "+f"(d[26]), "+f"(d[27]), "+f"(d[28]), "+f"(d[29]), "+f"(d[30]), "+f"(d[31]),
      "+f"(d[32]), "+f"(d[33]), "+f"(d[34]), "+f"(d[35]), "+f"(d[36]), "+f"(d[37]), "+f"(d[38]), "+f"(d[39]), "+f"(d[40]), "+f"(d[41]), "+f"(d[42]), "+f"(d[43]), "+f"(d[44]), "+f"(d[45]), "+f"(d[46]), "+f"(d[47]),
      "+f"(d[48]), "+f"(d[49]), "+f"(d[50]), "+f"(d[51]), "+f"(d[52]), "+f"(d[53]), "+f"(d[54]), "+f"(d[55]), "+f"(d[56]), "+f"(d[57]), "+f"(d[58]), "+f"(d[59]), "+f"(d[60]), "+f"(d[61]), "+f"(d[62]), "+f"(d[63])
    : "r"(a[0]), "r"(a[1]), "r"(a[2]), "r"(a[3]), "l"(db), "n"(OB));
}

struct Cons {
  uint32_t d0, da;
  uint32_t sb;
  uint32_t rel;
  uint32_t p0, p1;
  uint32_t lead, round, fpar;
};

template <uint32_t OFF, uint32_t GROUP> __device__ __forceinline__ void tile_write(const uint32_t (&pk)[32], uint32_t base) {
  const uint32_t lane = threadIdx.x & 31, wq = (threadIdx.x >> 5) & 3;
  const uint32_t a = base + (wq * 16 + (lane & 15)) * 128 + (((lane >> 4) ^ (lane & 7)) << 4);
#define TW(j) stmatrix_x4<OFF + (j >> 2) * GROUP>(a ^ ((j & 3) * 32), pk[4 * j + 0], pk[4 * j + 1], pk[4 * j + 2], pk[4 * j + 3])
  TW(0); TW(1); TW(2); TW(3); TW(4); TW(5); TW(6); TW(7);
#undef TW
}
template <uint32_t OFF, uint32_t GROUP, int A0> __device__ __forceinline__ void tile_pack_write(const float (&acc)[128], uint32_t (&pk)[32], uint32_t base) {
  const uint32_t lane = threadIdx.x & 31, wq = (threadIdx.x >> 5) & 3;
  const uint32_t a = base + (wq * 16 + (lane & 15)) * 128 + (((lane >> 4) ^ (lane & 7)) << 4);
#define TW(j) \
  pk[4 * j + 0] = v_pack(acc[A0 + 8 * j + 0], acc[A0 + 8 * j + 1]); pk[4 * j + 1] = v_pack(acc[A0 + 8 * j + 2], acc[A0 + 8 * j + 3]); \
  pk[4 * j + 2] = v_pack(acc[A0 + 8 * j + 4], acc[A0 + 8 * j + 5]); pk[4 * j + 3] = v_pack(acc[A0 + 8 * j + 6], acc[A0 + 8 * j + 7]); \
  stmatrix_x4<OFF + (j >> 2) * GROUP>(a ^ ((j & 3) * 32), pk[4 * j + 0], pk[4 * j + 1], pk[4 * j + 2], pk[4 * j + 3])
  TW(0); TW(1); TW(2); TW(3); TW(4); TW(5); TW(6); TW(7);
#undef TW
}
__device__ __forceinline__ void stage_write(const uint32_t (&pk)[32], int w, const Cons& cs) {
  mbar_wait<BAR(B_STGE)>(cs.sb + w * 8, (cs.round & 1) ^ 1);
  tile_write<OFF_STG, 8192>(pk, cs.sb + w * 16384);
}
__device__ __forceinline__ void stage_publish(int w, Cons& cs) {
  fence_async_smem();
  __syncwarp();
  mbar_arrive_if<BAR(B_STGF)>(cs.sb + w * 8, (threadIdx.x & 31) == 0);
  cs.round++;
}

template <int ST, bool INIT, bool FIRST = INIT, int NA> __device__ __forceinline__ void g_issue(float (&acc)[NA], const Cons& cs) {
  constexpr int B2 = NA == 128 ? 256 : 768, Z = FIRST ? 128 : 0;
  uint32_t a, b;
  asm volatile("add.u32 %0, %2, %4;\nadd.u32 %1, %3, %5;" : "=r"(a), "=r"(b) : "r"(cs.da), "r"(cs.d0), "n"(dlo(OFF_A + ST * 16384, NA + (FIRST ? 16 : 0))), "n"(dlo(OFF_B + ST * 32768, NA == 128 ? 8192 : 4096) + Z));
  const uint64_t A = desc(a), B = desc(b);
  wg_fence();
  if (INIT) wg_gemm_init<0, -Z>(acc, A, B); else wg_gemm_acc<0, -Z>(acc, A, B);
  wg_gemm_acc<2, 128 - Z>(acc, A, B);
  wg_gemm_acc<4, B2 - Z>(acc, A, B);
  wg_gemm_acc<6, B2 + 128 - Z>(acc, A, B);
  wg_commit();
}
template <int NA, class F>
__device__ __forceinline__ uint32_t gemm_tile(float (&acc)[NA], int nk4, int idx, int w, Cons& cs, uint32_t pend, const uint32_t (&pkA)[32], const uint32_t (&pkB)[32], F&& before_end) {
  const uint32_t sb = cs.sb, rel = cs.rel;
  constexpr int SA = NA == 128 ? STGA : STGAL, SBB = NA == 128 ? STGB : STGBL;
#define HOOK(n) \
  if (n == 0 && (pend & 8)) stage_publish(w, cs); \
  if (n == 0 && (pend & 16) && w == 0) bar_sync(5, 256); \
  if (n == SA && (pend & 1)) stage_write(pkA, w, cs); \
  if (n == SA + 1 && (pend & 1)) { stage_publish(w, cs); pend &= 6; } \
  if (n == SBB && (pend & 2)) { stage_write(pkB, w, cs); pend = 4; } \
  if (n == SBB + 1 && (pend & 4)) { stage_publish(w, cs); pend = 0; }
  mbar_wait<BAR(B_FULL + 0)>(sb, cs.p0);
  g_issue<0, true>(acc, cs);
  HOOK(0);
  mbar_wait<BAR(B_FULL + 1)>(sb, cs.p1);
  g_issue<1, false, true>(acc, cs);
  HOOK(2);
  wg_wait<1>();
  mbar_arrive_cl<BAR(B_EMPTY + 0)>(rel);
  HOOK(3);
  mbar_wait<BAR(B_FULL + 2)>(sb, cs.p0);
  g_issue<2, false, true>(acc, cs);
  HOOK(4);
  wg_wait<1>();
  mbar_arrive_cl<BAR(B_EMPTY + 1)>(rel);
  HOOK(5);
  mbar_wait<BAR(B_FULL + 3)>(sb, cs.p1);
  g_issue<3, false, true>(acc, cs);
  HOOK(6);
  const uint32_t ncode = item(sb, idx + 1);
  wg_wait<1>();
  mbar_arrive_cl<BAR(B_EMPTY + 2)>(rel);
  HOOK(7);
  cs.p0 ^= 1; cs.p1 ^= 1;
  const bool final_tile = NA == 128 && (ncode >> 9) == K_END;
#pragma unroll 1
  for (int q = 1; q < nk4; q++) {
    const bool tail = q == nk4 - 1;
    mbar_wait<BAR(B_FULL + 0)>(sb, cs.p0);
    g_issue<0, false>(acc, cs);
    HOOK(8);
    wg_wait<1>();
    mbar_arrive_cl<BAR(B_EMPTY + 3)>(rel);
    HOOK(9);
    mbar_wait<BAR(B_FULL + 1)>(sb, cs.p1);
    uint32_t rel0 = rel;
    if (final_tile && tail && w == 1) {
      wg_wait<0>();
      mbar_arrive_cl<BAR(B_EMPTY + 0)>(rel);
      rel0 = 0;
      mbar_wait<BAR(B_LEAD)>(sb, cs.lead);
    }
    g_issue<1, false>(acc, cs);
    HOOK(10);
    wg_wait<1>();
    mbar_arrive_cl<BAR(B_EMPTY + 0)>(rel0);
    HOOK(11);
    mbar_wait<BAR(B_FULL + 2)>(sb, cs.p0);
    uint32_t rel1 = rel;
    if (!final_tile && tail && w == 1) {
      wg_wait<0>();
      mbar_arrive_cl<BAR(B_EMPTY + 1)>(rel);
      rel1 = 0;
      mbar_wait<BAR(B_LEAD)>(sb, cs.lead);
    }
    g_issue<2, false>(acc, cs);
    HOOK(12);
    wg_wait<1>();
    mbar_arrive_cl<BAR(B_EMPTY + 1)>(rel1);
    HOOK(13);
    mbar_wait<BAR(B_FULL + 3)>(sb, cs.p1);
    g_issue<3, false>(acc, cs);
    mbar_arrive_if<BAR(B_LEAD)>(sb, tail && threadIdx.x == 128);
    HOOK(14);
    wg_wait<1>();
    mbar_arrive_cl<BAR(B_EMPTY + 2)>(rel);
    cs.p0 ^= 1; cs.p1 ^= 1;
  }
#undef HOOK
  cs.lead ^= 1;
  before_end();
  wg_wait<0>();
  fence_regs(acc);
  mbar_arrive_cl<BAR(B_EMPTY + 3)>(rel);
  return ncode;
}

__device__ __forceinline__ void local_probs(bool first, const float (&S)[3][4], uint32_t (&pb)[4]) {
  const int lane = threadIdx.x & 31, g = lane >> 2, t = lane & 3;
  const bool c0 = 2 * t > g, c1 = 2 * t + 1 > g;
  float x0 = c0 ? S[0][0] : S[1][0], x1 = c1 ? S[0][1] : S[1][1], y0 = c0 ? S[1][2] : S[2][2], y1 = c1 ? S[1][3] : S[2][3];
  if (first && c0) x0 = -INFINITY;
  if (first && c1) x1 = -INFINITY;
  float m0 = fmaxf(x0, x1), m1 = fmaxf(y0, y1);
  m0 = fmaxf(fmaxf(m0, __shfl_xor_sync(0xffffffffu, m0, 1)), fmaxf(__shfl_xor_sync(0xffffffffu, m0, 2), __shfl_xor_sync(0xffffffffu, m0, 3)));
  m1 = fmaxf(fmaxf(m1, __shfl_xor_sync(0xffffffffu, m1, 1)), fmaxf(__shfl_xor_sync(0xffffffffu, m1, 2), __shfl_xor_sync(0xffffffffu, m1, 3)));
  constexpr float C = 0.17677669529663687f * 1.4426950408889634f;
  const float b0 = -m0 * C, b1 = -m1 * C;
  x0 = ex2(fmaf(x0, C, b0)); x1 = ex2(fmaf(x1, C, b0)); y0 = ex2(fmaf(y0, C, b1)); y1 = ex2(fmaf(y1, C, b1));
  const float l0 = rcp(quad_sum(x0 + x1)), l1 = rcp(quad_sum(y0 + y1));
  const uint32_t px = pack_bf16(x0 * l0, x1 * l0), py = pack_bf16(y0 * l1, y1 * l1);
  const uint32_t m = (c0 ? 0xffffu : 0u) | (c1 ? 0xffff0000u : 0u);
  pb[0] = px & m; pb[1] = px & ~m; pb[2] = py & m; pb[3] = py & ~m;
}
struct Loc { uint32_t xa, ra, oa; };
__device__ __forceinline__ Loc local_prepare(uint32_t code, int w, Cons& cs) {
  const uint32_t lane = threadIdx.x & 31, wq = (threadIdx.x >> 5) & 3;
  const bool has_halo = (code & 15) != 0;
  Loc l;
  l.xa = cs.sb + OFF_STG + 8192 + w * 16384 + wq * 2048 + lane * 8;
  l.ra = l.xa - (wq == 0 ? 16384 - 3 * 2048 : 2048);
  if (w + wq == 0) l.ra = has_halo ? cs.sb + OFF_HALO + lane * 8 : l.xa;
  l.oa = cs.sb + w * 16384 + (wq * 16 + (lane & 7)) * 128 + (((lane >> 3) ^ (lane & 7)) << 4);
  asm volatile("{\n.reg .pred p;\nsetp.eq.u32 p, %0, 0;\n@p st.shared.u32 [%1], %2;\n}\n" ::"r"(l.xa), "r"(l.ra), "r"(l.oa) : "memory");
  mbar_wait<BAR(B_STGE)>(cs.sb + w * 8, (cs.round & 1) ^ 1);
  if (has_halo && w == 0) mbar_wait<BAR(B_HFULL)>(cs.sb, cs.fpar >> 1);
  cs.fpar ^= has_halo ? 2 : 0;
  return l;
}
__device__ __forceinline__ void local_epilogue(const float (&acc)[96], uint32_t code, int w, Cons& cs, const Loc& l) {
  const uint32_t cw = (threadIdx.x >> 5) - 4;
  const bool has_halo = (code & 15) != 0;
  uint32_t kf[3][8], vt[3][8];
#pragma unroll
  for (int j = 0; j < 8; j++) { kf[2][j] = pack_bf16(acc[32 + 4 * j + 2], acc[32 + 4 * j + 3]); vt[2][j] = transpose8(pack_bf16(acc[64 + 4 * j + 2], acc[64 + 4 * j + 3])); }
  sts64<0>(l.xa, &kf[2][0]); sts64<256>(l.xa, &kf[2][2]); sts64<512>(l.xa, &kf[2][4]); sts64<768>(l.xa, &kf[2][6]);
  sts64<1024>(l.xa, &vt[2][0]); sts64<1280>(l.xa, &vt[2][2]); sts64<1536>(l.xa, &vt[2][4]); sts64<1792>(l.xa, &vt[2][6]);
  if (cw == 3) bar_arrive(4, 160);
  uint32_t q[8][2];
#pragma unroll
  for (int j = 0; j < 8; j++) {
    q[j][0] = pack_bf16(acc[4 * j], acc[4 * j + 1]); q[j][1] = pack_bf16(acc[4 * j + 2], acc[4 * j + 3]);
    kf[1][j] = pack_bf16(acc[32 + 4 * j], acc[32 + 4 * j + 1]);
  }
  bar_sync(3 + w, 128 + 32 * w);
  uint32_t z[4];
  lds128<OFF_FILLS + 16>(z, cs.sb);
  lds64<0>(&kf[0][0], l.ra); lds64<512>(&kf[0][4], l.ra); lds64<256>(&kf[0][2], l.ra); lds64<768>(&kf[0][6], l.ra);
  lds64<1024>(&vt[0][0], l.ra); lds64<1280>(&vt[0][2], l.ra); lds64<1536>(&vt[0][4], l.ra); lds64<1792>(&vt[0][6], l.ra);
  float S[2][3][4];
#pragma unroll
  for (int n = 2; n >= 0; n--)
#pragma unroll
    for (int u = 0; u < 2; u++) mma16816z(S[u][n], q[4 * u][0], q[4 * u][1], q[4 * u + 1][0], q[4 * u + 1][1], kf[n][4 * u], kf[n][4 * u + 1], z);
#pragma unroll
  for (int n = 2; n >= 0; n--)
#pragma unroll
    for (int u = 0; u < 2; u++) mma16816(S[u][n], q[4 * u + 2][0], q[4 * u + 2][1], q[4 * u + 3][0], q[4 * u + 3][1], kf[n][4 * u + 2], kf[n][4 * u + 3]);
#pragma unroll
  for (int j = 0; j < 8; j++) vt[1][j] = transpose8(pack_bf16(acc[64 + 4 * j], acc[64 + 4 * j + 1]));
  uint32_t pb[2][4];
#pragma unroll
  for (int u = 0; u < 2; u++) local_probs(cw == 0 && !has_halo, S[u], pb[u]);
  const uint32_t oa = l.oa;
#pragma unroll
  for (int u = 0; u < 2; u++)
#pragma unroll
    for (int hf = 0; hf < 2; hf++) {
      float O[2][4];
#pragma unroll
      for (int mt = 0; mt < 2; mt++) {
        O[mt][0] = O[mt][1] = O[mt][2] = O[mt][3] = 0.f;
        mma16816(O[mt], vt[hf][4 * u + 2 * mt], vt[hf][4 * u + 2 * mt + 1], vt[hf + 1][4 * u + 2 * mt], vt[hf + 1][4 * u + 2 * mt + 1], pb[u][2 * hf], pb[u][2 * hf + 1]);
      }
      const uint32_t o0 = pack_bf16(O[0][0], O[0][1]), o1 = pack_bf16(O[0][2], O[0][3]), o2 = pack_bf16(O[1][0], O[1][1]), o3 = pack_bf16(O[1][2], O[1][3]);
      if (hf == 0) stmatrix_x4_trans<OFF_STG>(oa ^ (u * 64), o0, o1, o2, o3); else stmatrix_x4_trans<OFF_STG + 1024>(oa ^ (u * 64), o0, o1, o2, o3);
    }
  mbar_arrive_if<BAR(B_HEMPTY)>(cs.sb, has_halo && threadIdx.x == 128);
}

constexpr float SCALE_LOG2 = 0.08838834764831845f * 1.4426950408889634f;
#define SUM_LO 8.673617379884035e-19f
#define SUM_HI 1152921504606846976.f
template <int J0> __device__ __forceinline__ void causal_mask(float (&S)[64], int r) {
#pragma unroll
  for (int j = 0; j < 8; j++) {
    if (8 * j > r) S[4 * (J0 + j) + 0] = -INFINITY;
    if (8 * j + 1 > r) S[4 * (J0 + j) + 1] = -INFINITY;
    if (8 * j - 8 > r) S[4 * (J0 + j) + 2] = -INFINITY;
    if (8 * j - 7 > r) S[4 * (J0 + j) + 3] = -INFINITY;
  }
}
__device__ __forceinline__ float v_ex2(float x) { float y; asm volatile("ex2.approx.ftz.f32 %0, %1;" : "=f"(y) : "f"(x)); return y; }
__device__ __forceinline__ float v_add(float a, float b) { float y; asm volatile("add.f32 %0, %1, %2;" : "=f"(y) : "f"(a), "f"(b)); return y; }
__device__ __forceinline__ float v_mul(float a, float b) { float y; asm volatile("mul.f32 %0, %1, %2;" : "=f"(y) : "f"(a), "f"(b)); return y; }
template <int MJ> __device__ __forceinline__ float exp_el(float x, int j, int e, int r) {
  float p = v_ex2(x);
  if (j >= MJ) asm volatile("{\n.reg .pred q;\nsetp.lt.s32 q, %1, %2;\n@q mov.b32 %0, 0f00000000;\n}\n" : "+f"(p) : "r"(r), "r"(8 * (j - MJ) + (e & 1) - 4 * (e & 2)));
  return p;
}
template <int J0, int J1, int MJ = 16> __device__ __forceinline__ void exp_inplace(float (&S)[64], float& l0, float& l1, int r = 0) {
#pragma unroll
  for (int j = J0; j < J1; j++) {
#pragma unroll
    for (int e = 0; e < 4; e++) S[4 * j + e] = exp_el<MJ>(S[4 * j + e], j, e, r);
    l0 = v_add(l0, S[4 * j + 0]); l1 = v_add(l1, S[4 * j + 2]); l0 = v_add(l0, S[4 * j + 1]); l1 = v_add(l1, S[4 * j + 3]);
  }
}
template <int JS, int MJ, bool OUT>
__device__ __forceinline__ void exp_pack(float (&S)[64], uint32_t (&P)[32], float& l0, float& l1, int r, const float (&O)[64], float a0, float a1, uint32_t (&pk)[32]) {
#pragma unroll
  for (int j = JS; j < 16; j++) {
    const float p0 = exp_el<MJ>(S[4 * j + 0], j, 0, r), p1 = exp_el<MJ>(S[4 * j + 1], j, 1, r), p2 = exp_el<MJ>(S[4 * j + 2], j, 2, r), p3 = exp_el<MJ>(S[4 * j + 3], j, 3, r);
#pragma unroll
    for (int k = (j - JS) * JS / (16 - JS); k < (j + 1 - JS) * JS / (16 - JS); k++) { P[2 * k] = v_pack(S[4 * k + 0], S[4 * k + 1]); P[2 * k + 1] = v_pack(S[4 * k + 2], S[4 * k + 3]); }
    if (OUT) {
#pragma unroll
      for (int k = (j - JS) * 16 / (16 - JS); k < (j + 1 - JS) * 16 / (16 - JS); k++) {
        pk[2 * k] = v_pack(v_mul(O[4 * k + 0], a0), v_mul(O[4 * k + 1], a0)); pk[2 * k + 1] = v_pack(v_mul(O[4 * k + 2], a1), v_mul(O[4 * k + 3], a1));
      }
    }
    l0 = v_add(l0, p0); l1 = v_add(l1, p2); l0 = v_add(l0, p1); l1 = v_add(l1, p3);
    P[2 * j] = v_pack(p0, p1); P[2 * j + 1] = v_pack(p2, p3);
  }
}
__device__ __forceinline__ void pin_after(float a, float b) {
  asm volatile("{\n.reg .pred p;\nsetp.eq.u32 p, %0, 0xffffffff;\n@p st.shared.b32 [%1], %1;\n}\n" ::"r"(__float_as_uint(a)), "r"(__float_as_uint(b)) : "memory");
}
template <bool HALF, int SITE> __device__ __forceinline__ void issue_qk(float (&S)[64], uint32_t qlo, uint32_t klo) {
  uint32_t q, k;
  asm volatile("add.u32 %0, %2, %4;\nadd.u32 %1, %3, %4;" : "=r"(q), "=r"(k) : "r"(qlo), "r"(klo), "n"(SITE << 16));
  const uint64_t qd = desc(q), kd = desc(k);
  wg_fence();
  if (HALF) wg_qk64_init<0, 0>(S, qd, kd); else wg_qk_init<0, 0>(S, qd, kd);
#define QK(o) if (HALF) wg_qk64_acc<o, o>(S, qd, kd); else wg_qk_acc<o, o>(S, qd, kd)
  QK(2); QK(4); QK(6); QK(1024); QK(1026); QK(1028); QK(1030);
#undef QK
  wg_commit();
}
template <int NK, int ACC, int SITE> __device__ __forceinline__ void issue_pv(float (&O)[64], const uint32_t (&P)[32], uint32_t vlo) {
  constexpr int Z = 128 * SITE;
  uint32_t v;
  asm volatile("add.u32 %0, %1, %2;" : "=r"(v) : "r"(vlo), "n"(Z));
  const uint64_t vd = desc(v);
  wg_fence();
  if (ACC) wg_pv_acc<-Z>(O, &P[0], vd); else wg_pv_init<-Z>(O, &P[0], vd);
  wg_pv_acc<128 - Z>(O, &P[4], vd); wg_pv_acc<256 - Z>(O, &P[8], vd); wg_pv_acc<384 - Z>(O, &P[12], vd);
  if (NK == 8) { wg_pv_acc<512 - Z>(O, &P[16], vd); wg_pv_acc<640 - Z>(O, &P[20], vd); wg_pv_acc<768 - Z>(O, &P[24], vd); wg_pv_acc<896 - Z>(O, &P[28], vd); }
  wg_commit();
}
__device__ __forceinline__ uint32_t row_norm(float l0, float l1, float& a0, float& a1) {
  const float q0 = quad_sum(l0), q1 = quad_sum(l1);
  a0 = rcp(q0); a1 = rcp(q1);
  return __reduce_or_sync(0xffffffffu, (q0 >= SUM_LO && q0 <= SUM_HI && q1 >= SUM_LO && q1 <= SUM_HI) ? 0u : 1u);
}
__device__ __forceinline__ void slow_item(float (&O)[64], float& a0, float& a1, int head, int tile, uint32_t qbase, int w) {
  const int lane = threadIdx.x & 31, g = lane >> 2, t = lane & 3;
  const int rw = w * 64 + (int)__reduce_or_sync(0xffffffffu, (threadIdx.x >> 1) & 48);
  const int row0 = tile * 128 + rw;
  const uint32_t qa_ = qbase + (rw + g) * 128 + ((t ^ g) << 4);
  const __nv_bfloat16* kp = g_kv + ((size_t)head * SEQ + g) * 256 + 8 * t;
  const __nv_bfloat16* vp = g_kv + ((size_t)head * SEQ + 2 * t) * 256 + 128 + g;
  float m0 = -INFINITY, m1 = -INFINITY, l0 = 0.f, l1 = 0.f;
#pragma unroll
  for (int i = 0; i < 64; i++) O[i] = 0.f;
#pragma unroll 1
  for (int key0 = 0; key0 < row0 + 16; key0 += 16) {
    float c[2][4] = {{0.f, 0.f, 0.f, 0.f}, {0.f, 0.f, 0.f, 0.f}};
#pragma unroll 1
    for (int cc = 0; cc < 4; cc++) {
      uint32_t qa[4], qb[4];
      const uint32_t a = (qa_ ^ ((cc & 1) * 64)) + (cc >> 1) * 16384;
      lds128<0>(qa, a); lds128<1024>(qb, a);
#pragma unroll
      for (int n = 0; n < 2; n++) {
        const uint4 kf = ldg128(kp + (size_t)(key0 + 8 * n) * 256 + cc * 32);
        mma16816(c[n], qa[0], qb[0], qa[1], qb[1], kf.x, kf.y);
        mma16816(c[n], qa[2], qb[2], qa[3], qb[3], kf.z, kf.w);
      }
    }
#pragma unroll
    for (int n = 0; n < 2; n++)
#pragma unroll
      for (int e = 0; e < 4; e++)
        if (key0 + 8 * n + 2 * t + (e & 1) > row0 + g + (e >> 1) * 8) c[n][e] = -INFINITY;
    float x0 = fmaxf(fmaxf(c[0][0], c[0][1]), fmaxf(c[1][0], c[1][1])), x1 = fmaxf(fmaxf(c[0][2], c[0][3]), fmaxf(c[1][2], c[1][3]));
    x0 = fmaxf(x0, __shfl_xor_sync(0xffffffffu, x0, 1)); x1 = fmaxf(x1, __shfl_xor_sync(0xffffffffu, x1, 1));
    x0 = fmaxf(x0, __shfl_xor_sync(0xffffffffu, x0, 2)); x1 = fmaxf(x1, __shfl_xor_sync(0xffffffffu, x1, 2));
    const float n0 = fmaxf(m0, x0), n1 = fmaxf(m1, x1);
    const float r0 = ex2(m0 - n0), r1 = ex2(m1 - n1);
    m0 = n0; m1 = n1;
#pragma unroll
    for (int n = 0; n < 2; n++) { c[n][0] = ex2(c[n][0] - n0); c[n][1] = ex2(c[n][1] - n0); c[n][2] = ex2(c[n][2] - n1); c[n][3] = ex2(c[n][3] - n1); }
    l0 = l0 * r0 + ((c[0][0] + c[0][1]) + (c[1][0] + c[1][1]));
    l1 = l1 * r1 + ((c[0][2] + c[0][3]) + (c[1][2] + c[1][3]));
    const uint32_t p0 = pack_bf16(c[0][0], c[0][1]), p1 = pack_bf16(c[0][2], c[0][3]), p2 = pack_bf16(c[1][0], c[1][1]), p3 = pack_bf16(c[1][2], c[1][3]);
#pragma unroll
    for (int j = 0; j < 16; j++) {
      const __nv_bfloat16* v = vp + (size_t)key0 * 256 + j * 8;
      const uint32_t b0 = ldg16(v) | (ldg16(v + 256) << 16), b1 = ldg16(v + 8 * 256) | (ldg16(v + 9 * 256) << 16);
      float o[4] = {O[4 * j] * r0, O[4 * j + 1] * r0, O[4 * j + 2] * r1, O[4 * j + 3] * r1};
      mma16816(o, p0, p1, p2, p3, b0, b1);
      O[4 * j] = o[0]; O[4 * j + 1] = o[1]; O[4 * j + 2] = o[2]; O[4 * j + 3] = o[3];
    }
  }
  a0 = rcp(quad_sum(l0)); a1 = rcp(quad_sum(l1));
}
__device__ __forceinline__ void att_output(const float (&O)[64], float a0, float a1, uint32_t (&pk)[32]) {
#pragma unroll
  for (int k = 0; k < 16; k++) { pk[2 * k] = v_pack(v_mul(O[4 * k + 0], a0), v_mul(O[4 * k + 1], a0)); pk[2 * k + 1] = v_pack(v_mul(O[4 * k + 2], a1), v_mul(O[4 * k + 3], a1)); }
}
template <int J1> __device__ __forceinline__ void exp_stage(float (&S)[64], float& l0, float& l1, const uint32_t (&P)[32], int w, const Cons& cs, uint32_t on) {
  const uint32_t lane = threadIdx.x & 31, wq = (threadIdx.x >> 5) & 3;
  const uint32_t a = cs.sb + w * 16384 + (wq * 16 + (lane & 15)) * 128 + (((lane >> 4) ^ (lane & 7)) << 4);
#define ES(c) \
  exp_inplace<c * J1 / 8, (c + 1) * J1 / 8>(S, l0, l1); \
  stmatrix_x4_after<OFF_STG + (c >> 2) * 8192>(a ^ ((c & 3) * 32), P[4 * c + 0], P[4 * c + 1], P[4 * c + 2], P[4 * c + 3], (c & 1) ? l1 : l0, on)
  ES(0); ES(1); ES(2); ES(3); ES(4); ES(5); ES(6); ES(7);
#undef ES
}
struct Att { uint32_t qd, kd, vd, c8, cb, xc, xp, pub; };
__device__ __forceinline__ void att_advance(Att& t) {
  constexpr uint32_t SLOT = 32768 >> 4;
  t.kd ^= SLOT; t.vd ^= SLOT; t.c8 ^= 8; t.cb ^= 8;
  const uint32_t x = t.xc; t.xc = t.xp ^ 1; t.xp = x;
}
__device__ __forceinline__ void head_sums(float& l0, float& l1, float& a0, float& a1, uint32_t& unsafe, const Cons& cs) {
  unsafe = row_norm(l0, l1, a0, a1);
  mbar_arrive_if<BAR(B_QEMPTY)>(cs.sb, (threadIdx.x & 31) == 0 && !unsafe);
  l0 = l1 = 0.f;
}
template <bool SECOND>
__device__ __forceinline__ uint32_t diag_full(float (&S)[64], float (&O)[64], uint32_t (&P)[32], uint32_t (&pk)[32], float& l0, float& l1, float& a0, float& a1, uint32_t& unsafe, Att& t, int r, Cons& cs) {
  constexpr int JD = SECOND ? JDIAG2 : JDIAG, w = 1;
  bar_sync(2, 256);
  issue_qk<false, 2 + SECOND>(S, t.qd, t.kd);
  if (!SECOND && t.pub) { stage_publish(w, cs); t.pub = 0; }
  mbar_wait<BAR(B_FULL + 2)>(t.cb ^ 8, t.xp);
  issue_pv<8, 1, 4 + SECOND>(O, P, t.vd);
  bar_arrive(1, 256);
  att_advance(t);
  wg_wait<1>();
  fence_regs(S);
  mbar_arrive_cl<BAR(B_EMPTY)>(cs.rel, t.c8 ^ 8);
  if (SECOND) head_sums(l0, l1, a0, a1, unsafe, cs);
  exp_inplace<0, JD, 8>(S, l0, l1, r);
  pin_after(l0, l1);
  wg_wait<0>();
  fence_regs(O);
  fence_regs(P);
  mbar_arrive_cl<BAR(B_EMPTY + 2)>(cs.rel, t.c8);
  uint32_t ready = mbar_test<BAR(B_FULL)>(t.cb, t.xc);
  if (!SECOND) ready &= mbar_test<BAR(B_QFULL)>(cs.sb, cs.fpar & 1);
  exp_pack<JD, 8, SECOND>(S, P, l0, l1, r, O, a0, a1, pk);
  return __reduce_or_sync(0xffffffffu, ready ^ 1);
}
__device__ __forceinline__ void diag_half(bool second, float (&S)[64], float (&O)[64], uint32_t (&P)[32], float& l0, float& l1, float& a0, float& a1, uint32_t& unsafe, Att& t, int r, Cons& cs) {
  constexpr int w = 0;
  bar_sync(1, 256);
  issue_qk<true, 4>(S, t.qd, t.kd);
  mbar_wait<BAR(B_FULL + 2)>(t.cb ^ 8, t.xp);
  if (second) issue_pv<4, 1, 1>(O, P, t.vd); else issue_pv<8, 1, 3>(O, P, t.vd);
  bar_arrive(2, 256);
  if (t.pub) { stage_publish(w, cs); t.pub = 0; }
  att_advance(t);
  if (second) head_sums(l0, l1, a0, a1, unsafe, cs);
  wg_wait<1>();
  fence_regs<0, 32>(S);
  mbar_arrive_cl<BAR(B_EMPTY)>(cs.rel, t.c8 ^ 8);
  exp_inplace<0, 8, 0>(S, l0, l1, r);
  pin_after(l0, l1);
  wg_wait<0>();
  fence_regs(O);
  fence_regs(P);
  mbar_arrive_cl<BAR(B_EMPTY + 2)>(cs.rel, t.c8);
#pragma unroll
  for (int k = 0; k < 8; k++) { P[2 * k] = v_pack(S[4 * k + 0], S[4 * k + 1]); P[2 * k + 1] = v_pack(S[4 * k + 2], S[4 * k + 3]); }
}
__device__ __forceinline__ void attention(uint32_t code, uint32_t rank, int idx, int w, Cons& cs, uint32_t (&P)[32], uint32_t (&pk)[32]) {
  const int lane = threadIdx.x & 31, wq = (threadIdx.x >> 5) & 3;
  constexpr int JS = JSPLIT, JE = JEDGE;
  const uint32_t sb = cs.sb;
  const int y = (code & 15) * 2 + rank;
  const int r = wq * 16 + (lane >> 2) - 2 * (lane & 3);
  float O[64], S[64];
  float l0 = 0.f, l1 = 0.f;
  Att t = {cs.da + dlo(OFF_A, 16), cs.d0 + dlo(OFF_B, 16), cs.d0 + dlo(OFF_B + 98304, 16384), 0, sb, cs.p0, cs.p1, 0};
  uint32_t unsafe = 0, late;
  int ns;
  auto stage_step = [&](uint32_t on) {
    att_advance(t);
    t.pub = 1;
    wg_wait<1>();
    fence_regs(S);
    mbar_arrive_cl<BAR(B_EMPTY)>(cs.rel, t.c8 ^ 8);
    exp_stage<JE>(S, l0, l1, pk, w, cs, on);
    pin_after(l0, l1);
    wg_wait<0>();
    fence_regs(O);
    fence_regs(P);
    mbar_arrive_cl<BAR(B_EMPTY + 2)>(cs.rel, t.c8);
    const uint32_t ready = mbar_test<BAR(B_FULL)>(t.cb, t.xc);
    exp_pack<JE, 16, false>(S, P, l0, l1, r, O, 0.f, 0.f, pk);
    late = __reduce_or_sync(0xffffffffu, ready ^ 1);
  };
  bar_sync(3 - w, 128 + 128 * w);
  if (y >= 2) {
    issue_qk<false, 6>(O, t.qd, cs.d0 + dlo(OFF_B + 32768, 16));
    mbar_wait<BAR(B_FULL)>(sb, t.xc);
    issue_qk<false, 7>(S, t.qd, t.kd);
    bar_arrive(1 + (w ^ 1), 256);
    wg_wait<1>();
    fence_regs(O);
    mbar_arrive_cl<BAR(B_EMPTY + 1)>(cs.rel);
    exp_stage<JP>(O, l0, l1, pk, w, cs, w ^ 1);
    pin_after(l0, l1);
    const uint32_t rd = mbar_test<BAR(B_FULL + 3)>(sb, t.xp);
    exp_pack<JP, 16, false>(O, P, l0, l1, r, O, 0.f, 0.f, pk);
    if (UNLIKELY(__reduce_or_sync(0xffffffffu, rd ^ 1))) mbar_wait<BAR(B_FULL + 3)>(sb, t.xp);
    bar_sync(1 + w, 256);
    issue_pv<8, 0, 6>(O, P, t.vd);
    bar_arrive(1 + (w ^ 1), 256);
    stage_step(w);
    ns = y - 2;
  } else {
    issue_qk<false, 8>(S, t.qd, cs.d0 + dlo(OFF_B + 32768, 16));
    bar_arrive(1 + (w ^ 1), 256);
    wg_wait<0>();
    fence_regs(S);
    mbar_arrive_cl<BAR(B_EMPTY + 1)>(cs.rel);
    causal_mask<0>(S, r + 64 * w + 128 * y);
    causal_mask<8>(S, r + 64 * w + 128 * y - 64);
    exp_pack<0, 16, false>(S, P, l0, l1, r, S, 0.f, 0.f, pk);
#pragma unroll
    for (int i = 0; i < 64; i++) O[i] = 0.f;
    late = 1;
    ns = 0;
  }
#pragma unroll 1
  for (uint32_t head = 0;; head++) {
    while (ns > 0) {
      if (UNLIKELY(late)) mbar_wait<BAR(B_FULL)>(t.cb, t.xc);
      bar_sync(1 + w, 256);
      issue_qk<false, 9>(S, t.qd, t.kd);
      if (t.pub) { stage_publish(w, cs); t.pub = 0; }
      mbar_wait<BAR(B_FULL + 2)>(t.cb ^ 8, t.xp);
      issue_pv<8, 1, 0>(O, P, t.vd);
      bar_arrive(1 + (w ^ 1), 256);
      ns--;
      att_advance(t);
      wg_wait<1>();
      fence_regs(S);
      mbar_arrive_cl<BAR(B_EMPTY)>(cs.rel, t.c8 ^ 8);
      exp_inplace<0, JS>(S, l0, l1);
      pin_after(l0, l1);
      wg_wait<0>();
      fence_regs(O);
      fence_regs(P);
      mbar_arrive_cl<BAR(B_EMPTY + 2)>(cs.rel, t.c8);
      const uint32_t rd = mbar_test<BAR(B_FULL)>(t.cb, t.xc);
      exp_pack<JS, 16, false>(S, P, l0, l1, 0, O, 0.f, 0.f, pk);
      late = __reduce_or_sync(0xffffffffu, rd ^ 1);
    }
    float a0 = 0.f, a1 = 0.f;
    if (head == 0) {
      if (w == 1) {
        if (y != 0) {
          if (UNLIKELY(late)) mbar_wait<BAR(B_FULL)>(t.cb, t.xc);
          late = diag_full<false>(S, O, P, pk, l0, l1, a0, a1, unsafe, t, r, cs);
        }
        t.qd += 32768 >> 4;
        if (UNLIKELY(late)) { mbar_wait<BAR(B_QFULL)>(sb, cs.fpar & 1); mbar_wait<BAR(B_FULL)>(t.cb, t.xc); }
        late = diag_full<true>(S, O, P, pk, l0, l1, a0, a1, unsafe, t, r, cs);
      } else {
#pragma unroll 1
        for (int second = y == 0; second < 2; second++) {
          if (second) {
            t.qd += 32768 >> 4;
            mbar_wait<BAR(B_QFULL)>(sb, cs.fpar & 1);
          }
          if (late) mbar_wait<BAR(B_FULL)>(t.cb, t.xc);
          diag_half(second, S, O, P, l0, l1, a0, a1, unsafe, t, r, cs);
          late = 1;
        }
      }
    } else {
      bar_sync(1 + w, 256);
      mbar_wait<BAR(B_FULL + 2)>(t.cb ^ 8, t.xp);
      if (y != 1 || w) issue_pv<8, 1, 7>(O, P, t.vd); else issue_pv<4, 1, 2>(O, P, t.vd);
      if (w == 0) bar_arrive(2, 256);
      if (t.pub) stage_publish(w, cs);
      unsafe = row_norm(l0, l1, a0, a1);
      mbar_arrive_if<BAR(B_QEMPTY + 1)>(sb, lane == 0 && !unsafe);
      wg_wait<0>();
      fence_regs(O);
      fence_regs(P);
      mbar_arrive_cl<BAR(B_EMPTY + 2)>(cs.rel, t.c8 ^ 8);
    }
    if (head >= w) att_output(O, a0, a1, pk);
    if (UNLIKELY(unsafe)) {
      slow_item(S, a0, a1, ((code >> 4) & 31) * 2 + head, y ^ head, sb + OFF_A + head * 32768, w);
      __syncwarp();
      mbar_arrive_if<BAR(B_QEMPTY)>(sb + head * 8, lane == 0);
      att_output(S, a0, a1, pk);
    }
    if (head) break;
    if (y != 1) {
      if (UNLIKELY(late)) mbar_wait<BAR(B_FULL)>(t.cb, t.xc);
      bar_sync(1 + w, 256);
      issue_qk<false, 10>(S, t.qd, t.kd);
      mbar_wait<BAR(B_STGE)>(sb + w * 8, (cs.round & 1) ^ 1);
      mbar_wait<BAR(B_FULL + 2)>(t.cb ^ 8, t.xp);
      if (w == 0) issue_pv<4, 0, 3>(O, P, t.vd); else issue_pv<8, 0, 6>(O, P, t.vd);
      bar_arrive(1 + (w ^ 1), 256);
      stage_step(1);
      ns = (y ^ 1) - 1;
    } else {
      stage_write(pk, w, cs);
      t.pub = 1;
#pragma unroll
      for (int i = 0; i < 64; i++) O[i] = 0.f;
    }
  }
  cs.p1 = t.xp ^ 1; cs.p0 = t.xc;
  cs.fpar ^= 1;
}

struct Src { const CUtensorMap *ma, *mb; int a0, a1, b0, b1, b2; uint32_t hb; };
__device__ __forceinline__ Src gemm_src(const Params& p, uint32_t code, uint32_t rank, uint32_t h) {
  const int kind = code >> 9, x = (code >> 4) & 31, m = code & 15;
  Src s;
  s.ma = &p.maps[M_AX + kind];
  s.mb = &p.maps[(kind == K_KV && h) ? M_WUV : M_WQKV + kind];
  if (kind == K_QL) { s.a0 = rank * 1024; s.a1 = m * 128; s.b0 = x * 64; s.b1 = h * 32; s.b2 = 0; s.hb = 12288; }
  else { s.a0 = 0; s.a1 = (2 * m + rank) * 128; s.b0 = 0; s.b1 = 0; s.b2 = kind == K_KV ? x * 2 : x * 4 + h * 2; s.hb = 16384; }
  return s;
}
__global__ void __cluster_dims__(2, 1, 1) __launch_bounds__(384, 1) mega_kernel(const __grid_constant__ Params p) {
  extern __shared__ __align__(1024) uint8_t smem_raw[];
  const uint32_t sb = smem_u32(smem_raw), sb0 = sb;
  const uint32_t bid = blockIdx.x, rank = bid & 1;
  const int warp = __shfl_sync(0xffffffffu, threadIdx.x >> 5, 0);
#define BI(b) mbar_init<BAR(b)>(sb, bar_count(b))
  static_assert(B_COUNT == 25, "barrier set-up");
  if (warp == 0) {
    const uint32_t c0 = p.sched[bid >> 1][threadIdx.x & 1];
    if (elect_one()) {
      BI(0); BI(1); BI(2); BI(3);
      asm volatile("fence.mbarrier_init.release.cluster;" ::: "memory");
    }
    __syncwarp();
    const uint32_t code0 = __shfl_sync(0xffffffffu, c0, 0) & 4095;
    const Src u = gemm_src(p, code0, rank, 0), v = gemm_src(p, code0, rank, 1);
#pragma unroll
    for (int s = 0; s < EARLYN; s++) {
      if (elect_one()) {
        const uint32_t bar = sb + BAR(B_FULL) + s * 8;
        mbar_expect_tx<0>(bar, 16384 + 2 * u.hb);
        tma_load_2d(sb + OFF_A + s * 16384, u.ma, u.a0 + s * 64, u.a1, bar);
        tma_load_3d(sb + OFF_B + s * 32768, u.mb, u.b0, u.b1 + s * 64, u.b2, bar);
        tma_load_3d(sb + OFF_B + s * 32768 + u.hb, v.mb, v.b0, v.b1 + s * 64, v.b2, bar);
      }
    }
  }
  if (threadIdx.x == 32 || threadIdx.x == 64 || threadIdx.x == 96) {
    if (threadIdx.x == 32) { BI(4); BI(5); BI(6); BI(7); BI(8); BI(9); BI(21); }
    else if (threadIdx.x == 64) { BI(10); BI(11); BI(12); BI(13); BI(14); BI(15); BI(22); }
    else {
      BI(16); BI(17); BI(18); BI(19); BI(20); BI(23); BI(24);
      asm volatile("st.shared.u32 [%0+%2], %1;\nst.shared.v4.u32 [%0+%3], {%1, %1, %1, %1};" ::"r"(sb), "r"(0), "n"(OFF_FILLS), "n"(OFF_FILLS + 16) : "memory");
      if ((sb & 0xffffffu) != SB) __trap();
    }
    asm volatile("fence.mbarrier_init.release.cluster;" ::: "memory");
  }
#undef BI
  if (warp == 4) {
    const int i = threadIdx.x - 128;
    if (i < MAX_ITEMS / 4) {
      const uint4 v = *reinterpret_cast<const uint4*>(&p.sched[bid >> 1][4 * i]);
      asm volatile("st.shared.v4.u32 [%0+%5], {%1, %2, %3, %4};" ::"r"(sb + i * 16), "r"(v.x), "r"(v.y), "r"(v.z), "r"(v.w), "n"(OFF_LIST) : "memory");
    }
    asm volatile("st.shared.v2.u32 [%0+%2], {%1, %1};" ::"r"(sb + i * 8), "r"(0), "n"(OFF_MASK) : "memory");
  }
  bar_sync(0, 384);
  cluster_arrive_relaxed();
  const int wg = warp >> 2;
  if (wg == 0) {
    reg_dealloc<REG_PROD>();
    cluster_wait();
    const int lane = threadIdx.x & 31;
    auto need = [&](uint32_t& have, int i, int b) {
      if (!((have >> b) & 1)) {
        uint32_t n = 0;
        while (have = __reduce_or_sync(0xffffffffu, lds_acquire<OFF_MASK>(sb + i * 4)), !((have >> b) & 1)) { __nanosleep(32); if (++n > (1u << 22)) __trap(); }
        fence_async_glob();
      }
    };
    if (warp == 0) {
      uint32_t e0 = 1, e1 = 1;
      uint32_t qe = 0, after_att = 0, fills = 0;
      const uint64_t pol_first = policy_evict_first(), pol_normal = POL_NORMAL;
      for (int idx = 0;; idx++) {
        const uint32_t full = item_full(sb, idx), code = full & 4095;
        const int kind = code >> 9, x = (code >> 4) & 31, m = code & 15, y = 2 * m + rank;
        if (kind == K_END) break;
        const uint32_t last = kind >= K_OA ? 0u : full;
        {
          const Src u = gemm_src(p, code, rank, rank);
          const uint64_t pa = (last & 0x1000) ? pol_first : pol_normal, pb = (last & 0x2000) ? pol_first : pol_normal;
          const int nk = kind == K_KV ? 8 : kind == K_OB ? 64 : 16;
          uint32_t have = kind >= K_OA ? 0u : 0xffffffffu;
#pragma unroll 1
          for (int k = idx == 0 ? EARLYN : 0; k < nk; k++) {
            const uint32_t s = k & 3;
            int kk = k;
            if (k >= 64 - 4 * HLATE) { const int j = (k >> 1) - (32 - 2 * HLATE); kk = (32 - 2 * HLATE + (j < HLATE ? 2 * j : 2 * (j - HLATE) + 1)) * 2 + (k & 1); }
            need(have, (kind == K_OA ? F_QL : F_CTX) + y, kind == K_OA ? k : kk >> 1);
            if (after_att && !(k & 1)) {
              mbar_wait_b<BAR(B_QEMPTY)>(sb + k * 4, qe);
              if (k == 2) { after_att = 0; qe ^= 1; }
            }
            fill_gemm(sb + s * 8, (s & 1) ? e1 : e0, 16384 + 2 * u.hb, sb + OFF_B + s * 32768 + rank * u.hb, u.mb, u.b0, u.b1 + kk * 64, u.b2, sb + OFF_A + s * 16384, u.ma, u.a0 + kk * 64, u.a1, pb, pa);
            asm volatile("st.volatile.shared.u32 [%0+%2], %1;" ::"r"(sb), "r"(++fills), "n"(OFF_FILLS) : "memory");
            if (s == 3) { e0 ^= 1; e1 ^= 1; }
          }
        }
        if (kind == K_QF) {
          uint32_t have = 0, xc = e1, xp = e0 ^ 1;
#pragma unroll 1
          for (int j = 0; j < 8 * m + 8; j++) {
            const int i = j >> 1, v = j & 1;
            if (v ? i == 0 : i == 4 * m + 3) continue;
            const int ib = i - v;
            if (i == 2 * m + 1 + rank && !v) have = 0;
            const int h = 2 * x + (ib >= 2 * m + 1 + (int)rank), blk = ib <= 2 * m + 1 ? ib : 4 * m + 2 - ib;
            const int row = h * SEQ + blk * 128;
            if (!v) need(have, F_KV + h, blk);
            const uint32_t b = 2 * v + ((ib + 1) & 1);
            const uint32_t dst = sb + OFF_B + b * 32768;
            const bool own = ib == 2 * m + 1;
            const uint64_t pol = ((last >> (16 + (h & 1) * 8 + (blk >> 1))) & 1) ? pol_first : pol_normal;
            fill_kv(sb + b * 8, v ? xp : xc, dst + rank * 16384, &p.maps[M_KV_LD], (2 * v + rank) * 64, row, own ? 1 + rank : 3, pol);
            if (own) tma_load_2d_h(dst + (rank ^ 1) * 16384, &p.maps[M_KV_LD], (2 * v + (rank ^ 1)) * 64, row, sb + BAR(B_FULL) + b * 8, pol);
            if (v || i == 0) { const uint32_t t = xc; xc = xp ^ 1; xp = t; }
          }
          e0 ^= 1;
          after_att = 1;
        }
      }
    } else if (warp == 2) {
      const uint32_t epoch = g_flags.epoch[bid];
      const uint64_t full = (lane >> 3) == 2 ? ~0ull : 0x0000ffff0000ffffull, flip = 0ull - (epoch & 1);
      uint64_t seen = 0;
      uint32_t tries = 0, hp = 1, hcode;
      int hidx = -1;
      auto next_halo = [&]() { do hcode = item(sb, ++hidx); while ((hcode >> 9) != K_END && ((hcode >> 9) != K_QL || (hcode & 15) == 0)); };
      next_halo();
      while (true) {
        const bool all = __all_sync(0xffffffffu, seen == full);
        if (all && (hcode >> 9) == K_END) break;
        if (!all) {
          uint64_t v;
          asm volatile("ld.acquire.gpu.global.u64 %0, [%1];" : "=l"(v) : "l"(&g_flags.m[2 * lane]) : "memory");
          v = (v ^ flip) & full;
          if (v != seen) { seen = v; asm volatile("st.release.cta.shared::cta.u64 [%0+%2], %1;" ::"r"(sb + lane * 8), "l"(v), "n"(OFF_MASK) : "memory"); }
        }
        if ((hcode >> 9) != K_END) {
          const int x = (hcode >> 4) & 31, m = hcode & 15;
          bool there = __any_sync(0xffffffffu, lane == F_QL / 2 + m - 1 && ((seen >> (32 * rank + x)) & 1));
          if (there && __all_sync(0xffffffffu, mbar_test<BAR(B_HEMPTY)>(sb, hp))) {
            __syncwarp();
            fence_async_glob();
            if (elect_one()) mbar_expect_tx<BAR(B_HFULL)>(sb, 2048);
            bulk_load(sb + OFF_HALO, g_halo + ((2 * m + rank - 2) * 16 + x) * 2048, 2048, sb + BAR(B_HFULL));
            hp ^= 1;
            next_halo();
          }
        }
        __nanosleep(WATCH_NS);
        if (++tries > (1u << 20)) __trap();
      }
      if (lane == 0) g_flags.epoch[bid] = epoch + 1;
    } else if (warp == 3) {
      uint32_t n = 0;
      for (int idx = 0;; idx++) {
        const uint32_t code = item(sb, idx);
        const int kind = code >> 9, x = (code >> 4) & 31, y = 2 * (code & 15) + rank;
        if (kind == K_END) break;
        if (kind > K_KV) continue;
#pragma unroll 1
        for (int r = 0; r <= (kind == K_QF); r++, n++) {
          mbar_wait_long<BAR(B_RELF)>(sb + (n & 1) * 8, (n >> 1) & 1);
          mbar_arrive_if<BAR(B_RELE)>(sb + (n & 1) * 8, lane == 0);
          flag_toggle(&g_flags.m[kind == K_QL ? F_QL + y : kind == K_KV ? F_KV + x : F_CTX + (y ^ r)], 1u << (kind == K_QL ? x : kind == K_KV ? y : 2 * x + r));
        }
      }
    } else {
      {
        uint32_t round = 0, fpar = 0, nrel = 0;
        const uint32_t rb = mapa(sb, rank ^ 1);
        const uint64_t pol_first = policy_evict_first(), pol_normal = POL_NORMAL;
        auto pace = [&]() {
          uint32_t c0, c, t0, t;
          asm volatile("ld.volatile.shared.u32 %0, [%1+%2];" : "=r"(c0) : "r"(sb), "n"(OFF_FILLS) : "memory");
          asm volatile("mov.u32 %0, %clock;" : "=r"(t0));
          do {
            asm volatile("ld.volatile.shared.u32 %0, [%1+%2];" : "=r"(c) : "r"(sb), "n"(OFF_FILLS) : "memory");
            asm volatile("mov.u32 %0, %clock;" : "=r"(t));
          } while (__all_sync(0xffffffffu, c == c0 && t - t0 < PACE_MAX));
        };
        for (int idx = 0;; idx++) {
          const uint32_t code = item(sb, idx);
          const int kind = code >> 9, x = (code >> 4) & 31, m = code & 15, y = 2 * m + rank;
          if (kind == K_END) break;
          const bool last = (item(sb, idx + 1) >> 9) == K_END;
          if (kind == K_QF) {
            if (elect_one()) mbar_expect_tx<BAR(B_QFULL)>(sb, 32768);
            mbar_wait_long<BAR(B_QX)>(sb, fpar);
#pragma unroll 1
            for (int v = 0; v < 2; v++) {
              mbar_wait_b<BAR(B_STGF)>(sb + v * 8, round & 1);
              bulk_send(rb + OFF_A + 32768 + v * 8192, sb + OFF_STG + v * 16384, 8192, rb + BAR(B_QFULL));
              bulk_send(rb + OFF_A + 49152 + v * 8192, sb + OFF_STG + v * 16384 + 8192, 8192, rb + BAR(B_QFULL));
            }
            mbar_wait_b<BAR(B_QFULL)>(sb, fpar);
            mbar_arrive_cl<BAR(B_STGE)>(lane < 2 ? rb : 0, lane * 8);
            round++; fpar ^= 1;
          }
          const CUtensorMap* mc = &p.maps[M_OA_ST + kind];
          const uint64_t pol = (kind >= K_OA || kind == K_QF) ? pol_first : pol_normal;
          int row = kind == K_KV ? x * SEQ + y * 128 : kind == K_OA ? m * 128 : y * 128;
          int cg = kind == K_QL ? x : kind == K_QF ? x * 4 : kind == K_KV ? 0 : kind == K_OA ? rank * 32 + x * 4 : 16 + x * 4;
          const int nr = kind == K_QL ? 1 : 2;
#pragma unroll 1
          for (int r = 0; r < nr; r++) {
            mbar_wait_long<BAR(B_STGF)>(sb, round & 1);
            if (last && kind >= K_KV) {
              tma_store_3d(mc, sb + OFF_STG, 0, row, cg, pol);
              mbar_wait_b<BAR(B_FIN)>(sb, 0);
              tma_store_3d(mc, sb + OFF_B, 0, row, cg + 2, pol);
              mbar_wait_b<BAR(B_STGF + 1)>(sb, round & 1);
              tma_store_3d(mc, sb + OFF_STG + 16384, 0, row + 64, cg, pol);
              mbar_wait_b<BAR(B_FIN + 1)>(sb, 0);
              tma_store_3d(mc, sb + OFF_B + 16384, 0, row + 64, cg + 2, pol);
              bulk_commit();
              r = 1;
            } else {
              const bool paced = !last && (kind >= K_KV || r == 1);
              if (paced) pace();
              tma_store_3d(mc, sb + OFF_STG, 0, row, cg, pol);
              bulk_commit();
              mbar_wait_b<BAR(B_STGF + 1)>(sb, round & 1);
              if (paced) pace();
              tma_store_3d(mc, sb + OFF_STG + 16384, 0, row + 64, cg, pol);
              if (kind == K_QL) bulk_store(g_halo + (y * 16 + x) * 2048, sb + OFF_STG + 16384 + 8192 + 3 * 2048, 2048);
              bulk_commit();
              bulk_wait_read<1>();
              mbar_arrive_if<BAR(B_STGE)>(sb, lane == 0);
              bulk_wait_read<0>();
              mbar_arrive_if<BAR(B_STGE + 1)>(sb, lane == 0);
              round++;
            }
            if (kind == K_QF || (kind <= K_KV && r == nr - 1)) {
              bulk_wait_all();
              mbar_wait_b<BAR(B_RELE)>(sb + (nrel & 1) * 8, ((nrel >> 1) & 1) ^ 1);
              __syncwarp();
              mbar_arrive_if<BAR(B_RELF)>(sb + (nrel & 1) * 8, lane == 0);
              nrel++;
            }
            cg += 2;
            if (kind == K_QF) row ^= 128;
          }
        }
        bulk_wait_all();
      }
      cluster_arrive_relaxed();
      cluster_wait();
    }
  } else {
    reg_alloc<REG_CONS>();
    cluster_wait();
    const int w = wg - 1;
    Cons cs;
    cs.sb = __reduce_or_sync(0xffffffffu, sb0);
    const uint32_t sb = cs.sb;
    cs.d0 = (sb & 0x3ffff) >> 4;
    cs.da = cs.d0 + w * 512;
    cs.rel = (threadIdx.x & 127) == 0 ? sb : (threadIdx.x & 127) == 1 ? mapa(sb, rank ^ 1) : 0;
    cs.p0 = cs.p1 = cs.lead = cs.round = cs.fpar = 0;
    uint32_t pkA[32], pkB[32], pend = 0;
#pragma unroll
    for (int i = 0; i < 32; i++) pkA[i] = pkB[i] = 0;
    uint32_t code = item(sb, 0);
    int idx = 0;
    do {
      const int kind = code >> 9;
      uint32_t ncode;
      if (kind == K_QL) {
        float acc[96];
        Loc l;
        ncode = gemm_tile(acc, 4, idx, w, cs, pend, pkA, pkB, [&] { l = local_prepare(code, w, cs); });
        local_epilogue(acc, code, w, cs, l);
        pend = 24;
        if (w == 1 && (ncode >> 9) != K_END) bar_arrive(5, 256);
        if ((ncode >> 9) >= K_OA) { stage_publish(w, cs); pend = 16; }
      } else {
        float acc[128];
        ncode = gemm_tile(acc, kind == K_KV ? 2 : kind == K_OB ? 16 : 4, idx, w, cs, pend, pkA, pkB, [] {});
        if (kind == K_QF) {
          mbar_arrive_cl<BAR(B_QX)>((threadIdx.x & 1) ? cs.rel : 0);
          tile_pack_write<OFF_A, 16384, 0>(acc, pkB, sb + w * 8192);
#pragma unroll
          for (int i = 0; i < 32; i++) pkA[i] = v_pack(acc[64 + 2 * i], acc[64 + 2 * i + 1]);
          mbar_wait<BAR(B_STGE)>(sb + w * 8, (cs.round & 1) ^ 1);
          if ((code & 15) == 0) { tile_write<OFF_STG, 8192>(pkA, sb + w * 16384); stage_publish(w, cs); }
          mbar_wait<BAR(B_FULL + 1)>(sb, cs.p1);
          fence_async_smem();
          attention(code, rank, idx, w, cs, pkB, pkA);
          pend = 1;
        } else {
          if (kind == K_KV) {
#pragma unroll
            for (int i = 0; i < 64; i++) acc[i] *= SCALE_LOG2;
          }
#pragma unroll
          for (int i = 0; i < 32; i++) pkA[i] = pack_bf16(acc[2 * i], acc[2 * i + 1]);
#pragma unroll
          for (int i = 0; i < 32; i++) pkB[i] = pack_bf16(acc[64 + 2 * i], acc[64 + 2 * i + 1]);
          pend = 3;
        }
      }
      code = ncode;
      idx++;
    } while ((code >> 9) != K_END);
    if (pend & 1) { stage_write(pkA, w, cs); stage_publish(w, cs); }
    if (pend & 2) {
      mbar_wait<BAR(B_EMPTY)>(sb, cs.p0 ^ 1);
      tile_write<OFF_B, 8192>(pkB, sb + w * 16384);
      fence_async_smem();
      __syncwarp();
      mbar_arrive_if<BAR(B_FIN)>(sb + w * 8, (threadIdx.x & 31) == 0);
    }
    cluster_arrive();
  }
}

typedef CUresult (*EncodeFn)(CUtensorMap*, CUtensorMapDataType, cuuint32_t, void*, const cuuint64_t*, const cuuint64_t*, const cuuint32_t*,
                             const cuuint32_t*, CUtensorMapInterleave, CUtensorMapSwizzle, CUtensorMapL2promotion, CUtensorMapFloatOOBfill);

void make_map_2d(EncodeFn enc, CUtensorMap* tm, const void* ptr, uint64_t cols, uint64_t rows) {
  cuuint64_t dims[2] = {cols, rows};
  cuuint64_t str[1] = {cols * 2};
  cuuint32_t box[2] = {64, 128};
  cuuint32_t es[2] = {1, 1};
  enc(tm, CU_TENSOR_MAP_DATA_TYPE_BFLOAT16, 2, const_cast<void*>(ptr), dims, str, box, es, CU_TENSOR_MAP_INTERLEAVE_NONE, CU_TENSOR_MAP_SWIZZLE_128B,
      CU_TENSOR_MAP_L2_PROMOTION_L2_256B, CU_TENSOR_MAP_FLOAT_OOB_FILL_NONE);
}
void make_map_3d(EncodeFn enc, CUtensorMap* tm, const void* ptr, uint64_t cols, uint64_t rows, uint64_t part, uint32_t br, uint32_t bg) {
  cuuint64_t dims[3] = {part, rows, cols / part};
  cuuint64_t str[2] = {cols * 2, part * 2};
  cuuint32_t box[3] = {64, br, bg};
  cuuint32_t es[3] = {1, 1, 1};
  enc(tm, CU_TENSOR_MAP_DATA_TYPE_BFLOAT16, 3, const_cast<void*>(ptr), dims, str, box, es, CU_TENSOR_MAP_INTERLEAVE_NONE, CU_TENSOR_MAP_SWIZZLE_128B,
      CU_TENSOR_MAP_L2_PROMOTION_L2_256B, CU_TENSOR_MAP_FLOAT_OOB_FILL_NONE);
}

static const uint32_t h_sched[NPAIR][MAX_ITEMS] = {
  {0x400,0xff800207,0x554,0x564,0x566,0x1e02c4,0x20a7,0x625,0xe00,0xe00,0xe00,0xe00,0xe00,0xe00,0xe00,0xe00,0xe00,0xe00,0xe00,0xe00},
  {0x420,0x454,0x2,0x83,0x25,0xb6,0x4f0,0x2a5,0x25d0,0x202f1,0x636,0xe00,0xe00,0xe00,0xe00,0xe00,0xe00,0xe00,0xe00,0xe00},
  {0x440,0x200,0xe3,0x55,0x520,0x4d4,0x524,0xfff002a7,0x2037,0x30f7,0xe00,0xe00,0xe00,0xe00,0xe00,0xe00,0xe00,0xe00,0xe00,0xe00},
  {0x460,0x206,0x32281,0x2c2,0x202e1,0x603,0xe00,0xe00,0xe00,0xe00,0xe00,0xe00,0xe00,0xe00,0xe00,0xe00,0xe00,0xe00,0xe00,0xe00},
  {0x410,0x1,0x92,0x24,0xd5,0x40252,0x202a1,0x830,0xe00,0xe00,0xe00,0xe00,0xe00,0xe00,0xe00,0xe00,0xe00,0xe00,0xe00,0xe00},
  {0x430,0x474,0x12,0x93,0x4c1,0x4e1,0x4e3,0x4d5,0x513,0x536,0x583,0x2a0,0x5f3,0x815,0xe00,0xe00,0xe00,0xe00,0xe00,0xe00},
  {0x450,0x205,0x510,0x512,0x534,0x584,0x2547,0x574,0x2d3,0x20d7,0x616,0xe00,0xe00,0xe00,0xe00,0xe00,0xe00,0xe00,0xe00,0xe00},
  {0x470,0x406,0x485,0x4a1,0x486,0x497,0x4a5,0xa6,0x180284,0x1002f4,0x634,0xe00,0xe00,0xe00,0xe00,0xe00,0xe00,0xe00,0xe00,0xe00},
  {0x401,0x11,0x244,0x2a4,0x812,0xe00,0xe00,0xe00,0xe00,0xe00,0xe00,0xe00,0xe00,0xe00,0xe00,0xe00,0xe00,0xe00,0xe00,0xe00},
  {0x0,0xb1,0x33,0xd4,0x36,0x24c7,0x505,0x526,0x563,0x546,0x5e3,0x596,0x5f6,0x816,0xe00,0xe00,0xe00,0xe00,0xe00,0xe00},
  {0x421,0x201,0x94,0x276,0x5d2,0x837,0xe00,0xe00,0xe00,0xe00,0xe00,0xe00,0xe00,0xe00,0xe00,0xe00,0xe00,0xe00,0xe00,0xe00},
  {0x441,0x21,0xa2,0x34,0xe5,0x285,0x1002e4,0x613,0xe00,0xe00,0xe00,0xe00,0xe00,0xe00,0xe00,0xe00,0xe00,0xe00,0xe00,0xe00},
  {0x10,0x224,0x4d7,0x515,0x544,0x5c0,0x585,0x577,0x2002e5,0x633,0xe00,0xe00,0xe00,0xe00,0xe00,0xe00,0xe00,0xe00,0xe00,0xe00},
  {0x461,0x203,0x76,0x523,0x506,0x802a3,0x822,0xe00,0xe00,0xe00,0xe00,0xe00,0xe00,0xe00,0xe00,0xe00,0xe00,0xe00,0xe00,0xe00},
  {0x480,0x210,0xf3,0x4c2,0xffc00277,0x802e3,0x622,0xe00,0xe00,0xe00,0xe00,0xe00,0xe00,0xe00,0xe00,0xe00,0xe00,0xe00,0xe00,0xe00},
  {0x20,0x233,0x4b3,0x260,0x290,0x5c6,0x5b6,0x800,0xe00,0xe00,0xe00,0xe00,0xe00,0xe00,0xe00,0xe00,0xe00,0xe00,0xe00,0xe00},
  {0x411,0x31,0xb2,0x256,0x586,0x590,0x2594,0x803,0xe00,0xe00,0xe00,0xe00,0xe00,0xe00,0xe00,0xe00,0xe00,0xe00,0xe00,0xe00},
  {0x431,0x426,0xff800247,0x4002c6,0x2077,0x614,0xe00,0xe00,0xe00,0xe00,0xe00,0xe00,0xe00,0xe00,0xe00,0xe00,0xe00,0xe00,0xe00,0xe00},
  {0x451,0x41,0xc2,0xff800257,0x592,0x1802d4,0x600,0xe00,0xe00,0xe00,0xe00,0xe00,0xe00,0xe00,0xe00,0xe00,0xe00,0xe00,0xe00,0xe00},
  {0x471,0x446,0x466,0x2456,0x2467,0x4a3,0x4c3,0x4b4,0x296,0x15f1,0x35f0,0x2017,0x2067,0x632,0xe00,0xe00,0xe00,0xe00,0xe00,0xe00},
  {0x490,0x484,0x22,0xa3,0x35,0xc6,0x40272,0x4002e6,0x623,0xe00,0xe00,0xe00,0xe00,0xe00,0xe00,0xe00,0xe00,0xe00,0xe00,0xe00},
  {0x402,0x465,0x32,0x476,0x495,0x75,0x521,0x4d3,0x525,0x2517,0x5e0,0x5a2,0x5c4,0x2002f5,0x604,0xe00,0xe00,0xe00,0xe00,0xe00},
  {0x30,0x400226,0x80293,0x834,0xe00,0xe00,0xe00,0xe00,0xe00,0xe00,0xe00,0xe00,0xe00,0xe00,0xe00,0xe00,0xe00,0xe00,0xe00,0xe00},
  {0x422,0x211,0xa4,0x500,0x502,0xffe00297,0x322d1,0x631,0xe00,0xe00,0xe00,0xe00,0xe00,0xe00,0xe00,0xe00,0xe00,0xe00,0xe00,0xe00},
  {0x40,0x2447,0x82,0x44,0xf5,0xe6,0x4f5,0x535,0x553,0x808002d7,0x611,0xe00,0xe00,0xe00,0xe00,0xe00,0xe00,0xe00,0xe00,0xe00},
  {0x442,0x416,0x42,0xb3,0x200255,0x5a3,0x5a5,0x5b7,0x813,0xe00,0xe00,0xe00,0xe00,0xe00,0xe00,0xe00,0xe00,0xe00,0xe00,0xe00},
  {0x462,0x220,0x4,0x65,0x4c5,0x522,0x541,0x514,0x545,0x573,0x5c3,0x5e5,0x5d6,0x806,0xe00,0xe00,0xe00,0xe00,0xe00,0xe00},
  {0x481,0x436,0x52,0xc3,0x45,0xd6,0x32261,0x5c2,0x4002f6,0x624,0xe00,0xe00,0xe00,0xe00,0xe00,0xe00,0xe00,0xe00,0xe00,0xe00},
  {0x412,0x204,0xffe00287,0x402f2,0x637,0xe00,0xe00,0xe00,0xe00,0xe00,0xe00,0xe00,0xe00,0xe00,0xe00,0xe00,0xe00,0xe00,0xe00,0xe00},
  {0x50,0xc1,0x43,0xe4,0x46,0x4e5,0x24e7,0x543,0x533,0x5c1,0x2567,0x593,0x5b5,0x833,0xe00,0xe00,0xe00,0xe00,0xe00,0xe00},
  {0x432,0x4a0,0x62,0xd3,0x4a4,0x200265,0x576,0x5d7,0x804,0xe00,0xe00,0xe00,0xe00,0xe00,0xe00,0xe00,0xe00,0xe00,0xe00,0xe00},
  {0x452,0x455,0x241,0xc5,0x286,0x831,0xe00,0xe00,0xe00,0xe00,0xe00,0xe00,0xe00,0xe00,0xe00,0xe00,0xe00,0xe00,0xe00,0xe00},
  {0x472,0x51,0x245,0x562,0x550,0x808002e7,0x607,0xe00,0xe00,0xe00,0xe00,0xe00,0xe00,0xe00,0xe00,0xe00,0xe00,0xe00,0xe00,0xe00},
  {0x403,0x61,0xd2,0x4a2,0x2496,0x4a6,0x501,0x250,0x537,0x565,0x2587,0x5e6,0x5b1,0x827,0xe00,0xe00,0xe00,0xe00,0xe00,0xe00},
  {0x423,0x71,0x243,0x4e6,0x100294,0x821,0xe00,0xe00,0xe00,0xe00,0xe00,0xe00,0xe00,0xe00,0xe00,0xe00,0xe00,0xe00,0xe00,0xe00},
  {0x443,0x202,0x85,0x200275,0x5d4,0x820,0xe00,0xe00,0xe00,0xe00,0xe00,0xe00,0xe00,0xe00,0xe00,0xe00,0xe00,0xe00,0xe00,0xe00},
  {0x482,0x212,0x95,0x80263,0x5a4,0x2575,0x5d5,0x836,0xe00,0xe00,0xe00,0xe00,0xe00,0xe00,0xe00,0xe00,0xe00,0xe00,0xe00,0xe00},
  {0x413,0x213,0x86,0x540,0x511,0x530,0x402a2,0x832,0xe00,0xe00,0xe00,0xe00,0xe00,0xe00,0xe00,0xe00,0xe00,0xe00,0xe00,0xe00},
  {0x433,0x216,0x516,0x532,0x572,0x2002c5,0x20b7,0x635,0xe00,0xe00,0xe00,0xe00,0xe00,0xe00,0xe00,0xe00,0xe00,0xe00,0xe00,0xe00},
  {0x60,0xd1,0x53,0xf4,0x24a7,0x4d0,0x504,0x280,0x808002f7,0x626,0xe00,0xe00,0xe00,0xe00,0xe00,0xe00,0xe00,0xe00,0xe00,0xe00},
  {0x453,0x222,0xa5,0x4c6,0x273,0x595,0x5b0,0x802,0xe00,0xe00,0xe00,0xe00,0xe00,0xe00,0xe00,0xe00,0xe00,0xe00,0xe00,0xe00},
  {0x70,0x240,0x2477,0xff800267,0x5f2,0x835,0xe00,0xe00,0xe00,0xe00,0xe00,0xe00,0xe00,0xe00,0xe00,0xe00,0xe00,0xe00,0xe00,0xe00},
  {0x491,0x475,0x72,0x494,0x2487,0x100254,0x5e2,0x5e4,0x25e7,0x5d1,0x812f3,0x627,0xe00,0xe00,0xe00,0xe00,0xe00,0xe00,0xe00,0xe00},
  {0x80,0xe1,0x63,0x5,0x56,0x503,0x4f3,0x561,0x531,0x5e1,0x591,0x5a6,0x5b2,0x826,0xe00,0xe00,0xe00,0xe00,0xe00,0xe00},
  {0x492,0x214,0x4d6,0x4f6,0x24f4,0x808002c7,0x20c7,0x606,0xe00,0xe00,0xe00,0xe00,0xe00,0xe00,0xe00,0xe00,0xe00,0xe00,0xe00,0xe00},
  {0x90,0x236,0x292,0x5b3,0x824,0xe00,0xe00,0xe00,0xe00,0xe00,0xe00,0xe00,0xe00,0xe00,0xe00,0xe00,0xe00,0xe00,0xe00,0xe00},
  {0x404,0x223,0x96,0x100274,0x5f4,0x807,0xe00,0xe00,0xe00,0xe00,0xe00,0xe00,0xe00,0xe00,0xe00,0xe00,0xe00,0xe00,0xe00,0xe00},
  {0x424,0x221,0xb4,0x4b6,0x4b0,0x283,0x5c7,0x5d3,0x825,0xe00,0xe00,0xe00,0xe00,0xe00,0xe00,0xe00,0xe00,0xe00,0xe00,0xe00},
  {0x444,0x231,0xc4,0x80253,0x556,0x4002d6,0x1630,0xe00,0xe00,0xe00,0xe00,0xe00,0xe00,0xe00,0xe00,0xe00,0xe00,0xe00,0xe00,0xe00},
  {0xa0,0x225,0x542,0x2507,0x555,0x571,0x2c3,0x132f0,0x621,0xe00,0xe00,0xe00,0xe00,0xe00,0xe00,0xe00,0xe00,0xe00,0xe00,0xe00},
  {0x463,0x81,0xe2,0x54,0x6,0x40262,0x2b1,0x817,0xe00,0xe00,0xe00,0xe00,0xe00,0xe00,0xe00,0xe00,0xe00,0xe00,0xe00,0xe00},
  {0x414,0x493,0x2417,0x3,0x4c0,0x4e0,0x100264,0x2c1,0x402d2,0x601,0xe00,0xe00,0xe00,0xe00,0xe00,0xe00,0xe00,0xe00,0xe00,0xe00},
  {0x434,0x407,0x2437,0x13,0x74,0x4c4,0x4b5,0x24b1,0x4f7,0x581,0x5a0,0x551,0x122b0,0x811,0xe00,0xe00,0xe00,0xe00,0xe00,0xe00},
  {0x473,0xff800217,0x582,0x552,0x3e02b5,0x2097,0x615,0xe00,0xe00,0xe00,0xe00,0xe00,0xe00,0xe00,0xe00,0xe00,0xe00,0xe00,0xe00,0xe00},
  {0x405,0x230,0x14,0x266,0x2002d5,0x612,0xe00,0xe00,0xe00,0xe00,0xe00,0xe00,0xe00,0xe00,0xe00,0xe00,0xe00,0xe00,0xe00,0xe00},
  {0xb0,0xf1,0x73,0x15,0x66,0x10f6,0x2a6,0x2007,0x2047,0x620,0xe00,0xe00,0xe00,0xe00,0xe00,0xe00,0xe00,0xe00,0xe00,0xe00},
  {0xc0,0x234,0x295,0x823,0xe00,0xe00,0xe00,0xe00,0xe00,0xe00,0xe00,0xe00,0xe00,0xe00,0xe00,0xe00,0xe00,0xe00,0xe00,0xe00},
  {0xd0,0x242,0x26,0x4d2,0x4f2,0x580,0x2b3,0x2d0,0x2027,0x20e7,0xe00,0xe00,0xe00,0xe00,0xe00,0xe00,0xe00,0xe00,0xe00,0xe00},
  {0x425,0x215,0x20271,0x570,0x597,0x122c0,0x402e2,0x617,0xe00,0xe00,0xe00,0xe00,0xe00,0xe00,0xe00,0xe00,0xe00,0xe00,0xe00,0xe00},
  {0xe0,0xff800237,0x32291,0x5b4,0x810,0xe00,0xe00,0xe00,0xe00,0xe00,0xe00,0xe00,0xe00,0xe00,0xe00,0xe00,0xe00,0xe00,0xe00,0xe00},
  {0x445,0x427,0x457,0x23,0x84,0x4e2,0x4b7,0x20251,0x5a1,0x2557,0x5c5,0x5f7,0x814,0xe00,0xe00,0xe00,0xe00,0xe00,0xe00,0xe00},
  {0x483,0x232,0xb5,0x4e4,0x4d1,0x40282,0x5a7,0x5f5,0x805,0xe00,0xe00,0xe00,0xe00,0xe00,0xe00,0xe00,0xe00,0xe00,0xe00,0xe00},
  {0x464,0x91,0xf2,0x64,0x16,0x4b2,0x4f1,0x560,0x808002b7,0x2057,0x602,0xe00,0xe00,0xe00,0xe00,0xe00,0xe00,0xe00,0xe00,0xe00},
  {0x415,0xff800227,0x2527,0x404002b6,0x2087,0x605,0xe00,0xe00,0xe00,0xe00,0xe00,0xe00,0xe00,0xe00,0xe00,0xe00,0xe00,0xe00,0xe00,0xe00},
  {0xf0,0x235,0x12270,0x2b4,0x122e0,0x610,0xe00,0xe00,0xe00,0xe00,0xe00,0xe00,0xe00,0xe00,0xe00,0xe00,0xe00,0xe00,0xe00,0xe00},
  {0x435,0xa1,0x400246,0x2b2,0x801,0xe00,0xe00,0xe00,0xe00,0xe00,0xe00,0xe00,0xe00,0xe00,0xe00,0xe00,0xe00,0xe00,0xe00,0xe00},
};

struct HostState { bool init; Params p; void* out; const void* in[9]; };
HostState g_hs;

void build_state(void* const* d_in, void* d_out) {
  void* fn = nullptr;
  cudaDriverEntryPointQueryResult qr;
  cudaGetDriverEntryPoint("cuTensorMapEncodeTiled", &fn, cudaEnableDefault, &qr);
  EncodeFn enc = (EncodeFn)fn;
  void *kv, *ctx, *oA;
  cudaGetSymbolAddress(&kv, g_kv);
  cudaGetSymbolAddress(&ctx, g_ctx);
  cudaGetSymbolAddress(&oA, g_oA);
  Params& p = g_hs.p;
  make_map_2d(enc, &p.maps[M_AX], d_in[0], 2048, SEQ / 2);
  make_map_2d(enc, &p.maps[M_BX], d_in[3], 1024, SEQ);
  make_map_2d(enc, &p.maps[M_CKV], d_in[4], 512, SEQ);
  make_map_2d(enc, &p.maps[M_OA], oA, 1024, SEQ);
  make_map_2d(enc, &p.maps[M_CTX], ctx, 4096, SEQ);
  make_map_3d(enc, &p.maps[M_WQKV], d_in[1], 3072, 1024, 1024, 32, 3);
  make_map_3d(enc, &p.maps[M_WQ], d_in[5], 4096, 1024, 64, 64, 2);
  make_map_3d(enc, &p.maps[M_WUK], d_in[6], 4096, 512, 64, 64, 2);
  make_map_3d(enc, &p.maps[M_WUV], d_in[7], 4096, 512, 64, 64, 2);
  make_map_3d(enc, &p.maps[M_WOA], d_in[2], 1024, 1024, 64, 64, 2);
  make_map_3d(enc, &p.maps[M_WOB], d_in[8], 1024, 4096, 64, 64, 2);
  make_map_2d(enc, &p.maps[M_KV_LD], kv, 256, 32 * SEQ);
  make_map_3d(enc, &p.maps[M_OA_ST], oA, 1024, SEQ, 64, 64, 1);
  make_map_3d(enc, &p.maps[M_CTX_ST], ctx, 4096, SEQ, 64, 64, 2);
  make_map_3d(enc, &p.maps[M_KV_ST], kv, 256, 32 * SEQ, 64, 64, 2);
  make_map_3d(enc, &p.maps[M_OUTA_ST], d_out, 4096, SEQ / 2, 64, 64, 2);
  make_map_3d(enc, &p.maps[M_OUTB_ST], d_out, 2048, SEQ, 64, 64, 2);
  for (int c = 0; c < NPAIR; c++)
    for (int i = 0; i < MAX_ITEMS; i++) p.sched[c][i] = h_sched[c][i];
  cudaFuncSetAttribute(mega_kernel, cudaFuncAttributeMaxDynamicSharedMemorySize, SMEM_BYTES);
}

}

extern "C" void kernel_launch(void* const* d_in, const int* in_sizes, int n_in, void* d_out, int out_size) {
  (void)in_sizes; (void)n_in; (void)out_size;
  bool same = g_hs.init && g_hs.out == d_out;
  for (int i = 0; i < 9 && same; i++) same = (g_hs.in[i] == d_in[i]);
  if (!same) {
    build_state(d_in, d_out);
    g_hs.init = true; g_hs.out = d_out;
    for (int i = 0; i < 9; i++) g_hs.in[i] = d_in[i];
  }
  mega_kernel<<<NCTA, 384, SMEM_BYTES, cudaStreamPerThread>>>(g_hs.p);
}
```

```cpp
#include <cuda_runtime.h>
#include <cuda_bf16.h>
#include <cuda.h>
#include <stdint.h>

namespace {

constexpr int SEQ = 2048;
constexpr int NCTA = 132, NPAIR = 66;
constexpr int MAX_ITEMS = 20;

__device__ __align__(1024) __nv_bfloat16 g_kv[32 * SEQ * 256];
__device__ __align__(1024) __nv_bfloat16 g_ctx[SEQ * 4096];
__device__ __align__(1024) __nv_bfloat16 g_oA[SEQ * 1024];
__device__ __align__(1024) uint8_t g_halo[16 * 16 * 2048];
struct Flags { uint32_t m[64]; uint32_t epoch[NCTA]; };
__device__ __align__(128) Flags g_flags;
enum { F_KV = 0, F_CTX = 32, F_QL = 48 };

enum { K_QL = 0, K_QF = 1, K_KV = 2, K_OA = 3, K_OB = 4, K_END = 7 };
enum { M_AX = 0, M_BX, M_CKV, M_OA, M_CTX, M_WQKV, M_WQ, M_WUK, M_WOA, M_WOB, M_WUV, M_KV_LD, M_OA_ST, M_CTX_ST, M_KV_ST, M_OUTA_ST, M_OUTB_ST, M_COUNT };

struct Params {
  CUtensorMap maps[M_COUNT];
  alignas(16) uint32_t sched[NPAIR][MAX_ITEMS];
};


constexpr uint32_t SB = 1024;
constexpr uint32_t OFF_A = 0;
constexpr uint32_t OFF_B = 65536;
constexpr uint32_t OFF_STG = 196608;
constexpr uint32_t OFF_HALO = 229376;
constexpr uint32_t OFF_BAR = 231424;
constexpr uint32_t OFF_MASK = OFF_BAR + 256;
constexpr uint32_t OFF_LIST = OFF_BAR + 512;
constexpr uint32_t OFF_FILLS = OFF_BAR + 608;
constexpr uint32_t SMEM_BYTES = OFF_BAR + 640;
enum { B_FULL = 0, B_EMPTY = 4, B_QEMPTY = 8, B_STGE = 10, B_STGF = 12, B_FIN = 14, B_QFULL = 16, B_QX = 17, B_LEAD = 18, B_HFULL = 19, B_HEMPTY = 20, B_RELF = 21, B_RELE = 23, B_COUNT = 25 };
__host__ __device__ constexpr uint32_t BAR(int b) { return OFF_BAR + b * 8; }
__host__ __device__ constexpr int bar_count(int b) { return b < B_EMPTY ? 1 : b < B_QEMPTY ? 4 : b < B_STGE ? 8 : b < B_STGF ? 1 : b < B_QFULL ? 4 : b == B_QX ? 2 : 1; }
constexpr int REG_CONS = 232, REG_PROD = 40;
constexpr int PACE_MAX = 1100;
constexpr int WATCH_NS = 250;
constexpr int EARLYN = 3;
constexpr int HLATE = 3;
constexpr int STGA = 3, STGB = 8, STGAL = 4, STGBL = 12;
constexpr int JSPLIT = 14, JEDGE = 14, JP = 14, JDIAG = 10, JDIAG2 = 8;

__device__ __forceinline__ uint32_t smem_u32(const void* p) { return (uint32_t)__cvta_generic_to_shared(p); }
__device__ __forceinline__ void wg_fence() { asm volatile("wgmma.fence.sync.aligned;" ::: "memory"); }
__device__ __forceinline__ void wg_commit() { asm volatile("wgmma.commit_group.sync.aligned;" ::: "memory"); }
template <int N> __device__ __forceinline__ void wg_wait() { asm volatile("wgmma.wait_group.sync.aligned %0;" ::"n"(N) : "memory"); }
__device__ __forceinline__ uint64_t desc(uint32_t lo) { uint64_t d; asm volatile("mov.b64 %0, {%1, 0x40000040};" : "=l"(d) : "r"(lo)); return d; }
__host__ __device__ constexpr uint32_t dlo(uint32_t off, uint32_t lbo) { return (off >> 4) | ((lbo >> 4) << 16); }
template <uint32_t O> __device__ __forceinline__ void mbar_init(uint32_t a, uint32_t cnt) { asm volatile("mbarrier.init.shared::cta.b64 [%0+%2], %1;" ::"r"(a), "r"(cnt), "n"(O) : "memory"); }
template <uint32_t O> __device__ __forceinline__ void mbar_expect_tx(uint32_t a, uint32_t bytes) { asm volatile("mbarrier.arrive.expect_tx.shared::cta.b64 _, [%0+%2], %1;" ::"r"(a), "r"(bytes), "n"(O) : "memory"); }
template <uint32_t O> __device__ __forceinline__ void mbar_arrive_if(uint32_t a, bool pred) {
  asm volatile("{\n.reg .pred p;\nsetp.ne.u32 p, %1, 0;\n@p mbarrier.arrive.shared::cta.b64 _, [%0+%2];\n}\n" ::"r"(a), "r"((uint32_t)pred), "n"(O) : "memory");
}
template <uint32_t O> __device__ __forceinline__ void mbar_arrive_cl(uint32_t a, uint32_t off = 0) {
  asm volatile("{\n.reg .pred p;\nsetp.ne.u32 p, %2, 0;\n@p mbarrier.arrive.shared::cluster.b64 _, [%0+%1];\n}\n" ::"r"(a + off), "n"(O), "r"(a) : "memory");
}
template <uint32_t O> __device__ __forceinline__ bool mbar_test(uint32_t a, uint32_t parity) {
  uint32_t ok;
  asm volatile("{\n.reg .pred p;\nmbarrier.test_wait.parity.shared::cta.b64 p, [%1+%3], %2;\nselp.u32 %0, 1, 0, p;\n}\n" : "=r"(ok) : "r"(a), "r"(parity), "n"(O) : "memory");
  return ok;
}
template <uint32_t O> __device__ __forceinline__ void mbar_wait(uint32_t a, uint32_t parity) {
  asm volatile("{\n.reg .pred p;\nWAIT_%=:\nmbarrier.try_wait.parity.shared::cta.b64 p, [%0+%2], %1;\n@!p bra WAIT_%=;\n}\n" ::"r"(a), "r"(parity), "n"(O) : "memory");
}
template <uint32_t O> __device__ __forceinline__ void mbar_wait_b(uint32_t a, uint32_t parity) {
  asm volatile("{\n.reg .pred p, q;\n.reg .u32 n;\nmov.u32 n, 0;\nWAIT_%=:\nadd.u32 n, n, 1;\nmbarrier.try_wait.parity.shared::cta.b64 p, [%0+%2], %1;\n"
               "setp.lt.u32 q, n, 4194304;\nand.pred q, q, !p;\n@q bra WAIT_%=;\n@!p st.shared.u32 [%0+1], n;\n}\n" ::"r"(a), "r"(parity), "n"(O) : "memory");
}
template <uint32_t O> __device__ __forceinline__ void mbar_wait_long(uint32_t a, uint32_t parity) {
  asm volatile("{\n.reg .pred p, q;\n.reg .u32 n;\nmov.u32 n, 0;\nWAIT_%=:\nadd.u32 n, n, 1;\nmbarrier.try_wait.parity.shared::cta.b64 p, [%0+%2], %1, 4000;\n"
               "setp.lt.u32 q, n, 524288;\nand.pred q, q, !p;\n@q bra WAIT_%=;\n@!p st.shared.u32 [%0+1], n;\n}\n" ::"r"(a), "r"(parity), "n"(O) : "memory");
}
__device__ __forceinline__ void tma_load_2d(uint32_t dst, const CUtensorMap* tm, int c0, int c1, uint32_t bar) {
  asm volatile("cp.async.bulk.tensor.2d.shared::cluster.global.mbarrier::complete_tx::bytes [%0], [%1, {%3, %4}], [%2];" ::"r"(dst), "l"(tm), "r"(bar), "r"(c0), "r"(c1) : "memory");
}
__device__ __forceinline__ void tma_load_3d(uint32_t dst, const CUtensorMap* tm, int c0, int c1, int c2, uint32_t bar) {
  asm volatile("cp.async.bulk.tensor.3d.shared::cluster.global.mbarrier::complete_tx::bytes [%0], [%1, {%3, %4, %5}], [%2];" ::"r"(dst), "l"(tm), "r"(bar), "r"(c0), "r"(c1), "r"(c2) : "memory");
}
#define FILL_HEAD "{\n.reg .pred p, q;\n.reg .u32 n;\nmov.u32 n, 0;\nWAIT_%=:\nadd.u32 n, n, 1;\nmbarrier.try_wait.parity.shared::cta.b64 p, [%0+%1], %3;\n" \
                  "setp.lt.u32 q, n, 4194304;\nand.pred q, q, !p;\n@q bra WAIT_%=;\n@!p st.shared.u32 [%0+1], n;\nelect.sync _|p, 0xffffffff;\n" \
                  "@p mbarrier.arrive.expect_tx.shared::cta.b64 _, [%2], %4;\n"
__device__ __forceinline__ void fill_gemm(uint32_t bb, uint32_t parity, uint32_t bytes, uint32_t dstb, const CUtensorMap* mb, int b0, int b1, int b2, uint32_t dsta, const CUtensorMap* ma, int a0, int a1, uint64_t pb, uint64_t pa) {
  asm volatile(FILL_HEAD
               "@p cp.async.bulk.tensor.3d.shared::cluster.global.mbarrier::complete_tx::bytes.multicast::cluster.L2::cache_hint [%5], [%6, {%7, %8, %9}], [%2], %14, %15;\n"
               "@p cp.async.bulk.tensor.2d.shared::cluster.global.mbarrier::complete_tx::bytes.L2::cache_hint [%10], [%11, {%12, %13}], [%2], %16;\n}\n"
               ::"r"(bb), "n"(BAR(B_EMPTY)), "r"(bb + BAR(B_FULL)), "r"(parity), "r"(bytes), "r"(dstb), "l"(mb), "r"(b0), "r"(b1), "r"(b2), "r"(dsta), "l"(ma), "r"(a0), "r"(a1), "h"((uint16_t)3), "l"(pb), "l"(pa) : "memory");
}
__device__ __forceinline__ void fill_kv(uint32_t bb, uint32_t parity, uint32_t dst, const CUtensorMap* m, int c0, int c1, uint16_t mask, uint64_t pol) {
  asm volatile(FILL_HEAD
               "@p cp.async.bulk.tensor.2d.shared::cluster.global.mbarrier::complete_tx::bytes.multicast::cluster.L2::cache_hint [%5], [%6, {%7, %8}], [%2], %9, %10;\n}\n"
               ::"r"(bb), "n"(BAR(B_EMPTY)), "r"(bb + BAR(B_FULL)), "r"(parity), "r"(32768), "r"(dst), "l"(m), "r"(c0), "r"(c1), "h"(mask), "l"(pol) : "memory");
}
__device__ __forceinline__ void tma_load_2d_h(uint32_t dst, const CUtensorMap* tm, int c0, int c1, uint32_t bar, uint64_t pol) {
  asm volatile("{\n.reg .pred p;\nelect.sync _|p, 0xffffffff;\n@p cp.async.bulk.tensor.2d.shared::cluster.global.mbarrier::complete_tx::bytes.L2::cache_hint [%0], [%1, {%3, %4}], [%2], %5;\n}\n" ::"r"(dst), "l"(tm), "r"(bar), "r"(c0), "r"(c1), "l"(pol) : "memory");
}
__device__ __forceinline__ void tma_store_3d(const CUtensorMap* tm, uint32_t src, int c0, int c1, int c2, uint64_t pol) {
  asm volatile("{\n.reg .pred p;\nelect.sync _|p, 0xffffffff;\n@p cp.async.bulk.tensor.3d.global.shared::cta.bulk_group.L2::cache_hint [%0, {%2, %3, %4}], [%1], %5;\n}\n" ::"l"(tm), "r"(src), "r"(c0), "r"(c1), "r"(c2), "l"(pol) : "memory");
}
__device__ __forceinline__ void bulk_load(uint32_t dst, const void* src, uint32_t bytes, uint32_t bar) {
  asm volatile("{\n.reg .pred p;\nelect.sync _|p, 0xffffffff;\n@p cp.async.bulk.shared::cluster.global.mbarrier::complete_tx::bytes [%0], [%1], %2, [%3];\n}\n" ::"r"(dst), "l"(src), "r"(bytes), "r"(bar) : "memory");
}
__device__ __forceinline__ void bulk_store(void* dst, uint32_t src, uint32_t bytes) {
  asm volatile("{\n.reg .pred p;\nelect.sync _|p, 0xffffffff;\n@p cp.async.bulk.global.shared::cta.bulk_group [%0], [%1], %2;\n}\n" ::"l"(dst), "r"(src), "r"(bytes) : "memory");
}
__device__ __forceinline__ void bulk_send(uint32_t dst, uint32_t src, uint32_t bytes, uint32_t bar) {
  asm volatile("{\n.reg .pred p;\nelect.sync _|p, 0xffffffff;\n@p cp.async.bulk.shared::cluster.shared::cta.mbarrier::complete_tx::bytes [%0], [%1], %2, [%3];\n}\n" ::"r"(dst), "r"(src), "r"(bytes), "r"(bar) : "memory");
}
__device__ __forceinline__ uint64_t policy_evict_first() { uint64_t p; asm volatile("createpolicy.fractional.L2::evict_first.b64 %0, 1.0;" : "=l"(p)); return p; }
constexpr uint64_t POL_NORMAL = 0x1000000000000000ull;
__device__ __forceinline__ uint32_t mapa(uint32_t addr, uint32_t rank) { uint32_t r; asm("mapa.shared::cluster.u32 %0, %1, %2;" : "=r"(r) : "r"(addr), "r"(rank)); return r; }
__device__ __forceinline__ void cluster_arrive_relaxed() { asm volatile("barrier.cluster.arrive.relaxed.aligned;" ::: "memory"); }
__device__ __forceinline__ void cluster_arrive() { asm volatile("barrier.cluster.arrive.release.aligned;" ::: "memory"); }
__device__ __forceinline__ void cluster_wait() { asm volatile("barrier.cluster.wait.acquire.aligned;" ::: "memory"); }
__device__ __forceinline__ void bulk_commit() { asm volatile("cp.async.bulk.commit_group;" ::: "memory"); }
template <int N> __device__ __forceinline__ void bulk_wait_read() { asm volatile("cp.async.bulk.wait_group.read %0;" ::"n"(N) : "memory"); }
__device__ __forceinline__ void bulk_wait_all() { asm volatile("cp.async.bulk.wait_group 0;" ::: "memory"); }
__device__ __forceinline__ void fence_async_smem() { asm volatile("fence.proxy.async.shared::cta;" ::: "memory"); }
__device__ __forceinline__ void fence_async_glob() { asm volatile("fence.proxy.async.global;" ::: "memory"); }
__device__ __forceinline__ void flag_toggle(uint32_t* p, uint32_t v) { asm volatile("{\n.reg .pred p;\nelect.sync _|p, 0xffffffff;\n@p red.release.gpu.global.xor.b32 [%0], %1;\n}\n" ::"l"(p), "r"(v) : "memory"); }
template <uint32_t O> __device__ __forceinline__ uint32_t lds_acquire(uint32_t a) { uint32_t v; asm volatile("ld.acquire.cta.shared::cta.u32 %0, [%1+%2];" : "=r"(v) : "r"(a), "n"(O) : "memory"); return v; }
__device__ __forceinline__ uint32_t item_full(uint32_t sb, int idx) {
  uint32_t c;
  asm volatile("ld.shared.u32 %0, [%1+%2];" : "=r"(c) : "r"(sb + idx * 4), "n"(OFF_LIST));
  return __reduce_or_sync(0xffffffffu, c);
}
__device__ __forceinline__ uint32_t item(uint32_t sb, int idx) { return item_full(sb, idx) & 4095; }
template <int N> __device__ __forceinline__ void reg_alloc() { asm volatile("setmaxnreg.inc.sync.aligned.u32 %0;" ::"n"(N)); }
template <int N> __device__ __forceinline__ void reg_dealloc() { asm volatile("setmaxnreg.dec.sync.aligned.u32 %0;" ::"n"(N)); }
template <int I0, int I1, int N> __device__ __forceinline__ void fence_regs(float (&d)[N]) {
#pragma unroll
  for (int i = I0; i < I1; i++) asm volatile("" : "+f"(d[i])::"memory");
}
template <int N> __device__ __forceinline__ void fence_regs(float (&d)[N]) { fence_regs<0, N, N>(d); }
template <int N> __device__ __forceinline__ void fence_regs(uint32_t (&d)[N]) {
#pragma unroll
  for (int i = 0; i < N; i++) asm volatile("" : "+r"(d[i])::"memory");
}
__device__ __forceinline__ uint32_t pack_bf16(float lo, float hi) { uint32_t r; asm("cvt.rn.bf16x2.f32 %0, %1, %2;" : "=r"(r) : "f"(hi), "f"(lo)); return r; }
__device__ __forceinline__ uint32_t v_pack(float lo, float hi) { uint32_t r; asm volatile("cvt.rn.bf16x2.f32 %0, %1, %2;" : "=r"(r) : "f"(hi), "f"(lo)); return r; }
template <uint32_t O> __device__ __forceinline__ void stmatrix_x4(uint32_t a, uint32_t r0, uint32_t r1, uint32_t r2, uint32_t r3) {
  asm volatile("stmatrix.sync.aligned.m8n8.x4.shared.b16 [%0+%5], {%1, %2, %3, %4};" ::"r"(a), "r"(r0), "r"(r1), "r"(r2), "r"(r3), "n"(O) : "memory");
}
template <uint32_t O> __device__ __forceinline__ void stmatrix_x4_after(uint32_t a, uint32_t r0, uint32_t r1, uint32_t r2, uint32_t r3, float dep, uint32_t on) {
  asm volatile("{\n.reg .pred p, q;\n.reg .u32 a;\nsetp.ne.u32 p, %7, 0;\nsetp.ne.u32 q, %6, 0xffffffff;\nselp.u32 a, %0, 0, q;\n@p stmatrix.sync.aligned.m8n8.x4.shared.b16 [a+%5], {%1, %2, %3, %4};\n}\n"
               ::"r"(a), "r"(r0), "r"(r1), "r"(r2), "r"(r3), "n"(O), "r"(__float_as_uint(dep)), "r"(on) : "memory");
}
template <uint32_t O> __device__ __forceinline__ void stmatrix_x4_trans(uint32_t a, uint32_t r0, uint32_t r1, uint32_t r2, uint32_t r3) {
  asm volatile("stmatrix.sync.aligned.m8n8.x4.trans.shared.b16 [%0+%5], {%1, %2, %3, %4};" ::"r"(a), "r"(r0), "r"(r1), "r"(r2), "r"(r3), "n"(O) : "memory");
}
template <uint32_t O> __device__ __forceinline__ void sts64(uint32_t a, const uint32_t* r) { asm volatile("st.shared.v2.u32 [%0+%3], {%1, %2};" ::"r"(a), "r"(r[0]), "r"(r[1]), "n"(O) : "memory"); }
template <uint32_t O> __device__ __forceinline__ void lds64(uint32_t* r, uint32_t a) { asm volatile("ld.shared.v2.u32 {%0, %1}, [%2+%3];" : "=r"(r[0]), "=r"(r[1]) : "r"(a), "n"(O) : "memory"); }
template <uint32_t O> __device__ __forceinline__ void lds128(uint32_t* r, uint32_t a) { asm volatile("ld.shared.v4.u32 {%0, %1, %2, %3}, [%4+%5];" : "=r"(r[0]), "=r"(r[1]), "=r"(r[2]), "=r"(r[3]) : "r"(a), "n"(O) : "memory"); }
__device__ __forceinline__ uint32_t transpose8(uint32_t a) { uint32_t d; asm volatile("movmatrix.sync.aligned.m8n8.trans.b16 %0, %1;" : "=r"(d) : "r"(a)); return d; }
__device__ __forceinline__ float ex2(float x) { float y; asm("ex2.approx.ftz.f32 %0, %1;" : "=f"(y) : "f"(x)); return y; }
__device__ __forceinline__ float rcp(float x) { float y; asm("rcp.approx.ftz.f32 %0, %1;" : "=f"(y) : "f"(x)); return y; }
__device__ __forceinline__ void bar_sync(int id, int n) { asm volatile("bar.sync %0, %1;" ::"r"(id), "r"(n) : "memory"); }
__device__ __forceinline__ void bar_arrive(int id, int n) { asm volatile("bar.arrive %0, %1;" ::"r"(id), "r"(n) : "memory"); }
__device__ __forceinline__ void mma16816(float (&c)[4], uint32_t a0, uint32_t a1, uint32_t a2, uint32_t a3, uint32_t b0, uint32_t b1) {
  asm("mma.sync.aligned.m16n8k16.row.col.f32.bf16.bf16.f32 {%0, %1, %2, %3}, {%4, %5, %6, %7}, {%8, %9}, {%0, %1, %2, %3};"
      : "+f"(c[0]), "+f"(c[1]), "+f"(c[2]), "+f"(c[3]) : "r"(a0), "r"(a1), "r"(a2), "r"(a3), "r"(b0), "r"(b1));
}
__device__ __forceinline__ void mma16816z(float (&c)[4], uint32_t a0, uint32_t a1, uint32_t a2, uint32_t a3, uint32_t b0, uint32_t b1, const uint32_t (&z)[4]) {
  asm("mma.sync.aligned.m16n8k16.row.col.f32.bf16.bf16.f32 {%0, %1, %2, %3}, {%4, %5, %6, %7}, {%8, %9}, {%10, %11, %12, %13};"
      : "=f"(c[0]), "=f"(c[1]), "=f"(c[2]), "=f"(c[3]) : "r"(a0), "r"(a1), "r"(a2), "r"(a3), "r"(b0), "r"(b1),
        "f"(__uint_as_float(z[0])), "f"(__uint_as_float(z[1])), "f"(__uint_as_float(z[2])), "f"(__uint_as_float(z[3])));
}
__device__ __forceinline__ uint4 ldg128(const void* p) { uint4 v; asm volatile("ld.global.cg.v4.u32 {%0, %1, %2, %3}, [%4];" : "=r"(v.x), "=r"(v.y), "=r"(v.z), "=r"(v.w) : "l"(p) : "memory"); return v; }
__device__ __forceinline__ uint32_t ldg16(const void* p) { uint16_t v; asm volatile("ld.global.cg.u16 %0, [%1];" : "=h"(v) : "l"(p) : "memory"); return v; }
__device__ __forceinline__ float quad_sum(float v) {
  v += __shfl_xor_sync(0xffffffffu, v, 1);
  v += __shfl_xor_sync(0xffffffffu, v, 2);
  return v;
}
__device__ __forceinline__ bool elect_one() { uint32_t p; asm volatile("{\n.reg .pred p;\nelect.sync _|p, 0xffffffff;\nselp.u32 %0, 1, 0, p;\n}\n" : "=r"(p)); return p; }
#define UNLIKELY(x) __builtin_expect(!!(x), 0)

template <int OA, int OB> __device__ __forceinline__ void wg_gemm_init(float (&d)[128], uint64_t da, uint64_t db) {
  asm volatile("{\n.reg .pred p;\n.reg .b64 da, db;\nadd.s64 da, %128, %129;\nadd.s64 db, %130, %131;\nsetp.ne.b32 p, 0, 0;\n"
    "wgmma.mma_async.sync.aligned.m64n256k16.f32.bf16.bf16 {"
    "%0, %1, %2, %3, %4, %5, %6, %7, %8, %9, %10, %11, %12, %13, %14, %15, %16, %17, %18, %19, %20, %21, %22, %23, %24, %25, %26, %27, %28, %29, %30, %31, "
    "%32, %33, %34, %35, %36, %37, %38, %39, %40, %41, %42, %43, %44, %45, %46, %47, %48, %49, %50, %51, %52, %53, %54, %55, %56, %57, %58, %59, %60, %61, %62, %63, "
    "%64, %65, %66, %67, %68, %69, %70, %71, %72, %73, %74, %75, %76, %77, %78, %79, %80, %81, %82, %83, %84, %85, %86, %87, %88, %89, %90, %91, %92, %93, %94, %95, "
    "%96, %97, %98, %99, %100, %101, %102, %103, %104, %105, %106, %107, %108, %109, %110, %111, %112, %113, %114, %115, %116, %117, %118, %119, %120, %121, %122, %123, %124, %125, %126, %127}, "
    "da, db, p, 1, 1, 0, 1;\n}\n"
    : "=f"(d[0]), "=f"(d[1]), "=f"(d[2]), "=f"(d[3]), "=f"(d[4]), "=f"(d[5]), "=f"(d[6]), "=f"(d[7]), "=f"(d[8]), "=f"(d[9]), "=f"(d[10]), "=f"(d[11]), "=f"(d[12]), "=f"(d[13]), "=f"(d[14]), "=f"(d[15]),
      "=f"(d[16]), "=f"(d[17]), "=f"(d[18]), "=f"(d[19]), "=f"(d[20]), "=f"(d[21]), "=f"(d[22]), "=f"(d[23]), "=f"(d[24]), "=f"(d[25]), "=f"(d[26]), "=f"(d[27]), "=f"(d[28]), "=f"(d[29]), "=f"(d[30]), "=f"(d[31]),
      "=f"(d[32]), "=f"(d[33]), "=f"(d[34]), "=f"(d[35]), "=f"(d[36]), "=f"(d[37]), "=f"(d[38]), "=f"(d[39]), "=f"(d[40]), "=f"(d[41]), "=f"(d[42]), "=f"(d[43]), "=f"(d[44]), "=f"(d[45]), "=f"(d[46]), "=f"(d[47]),
      "=f"(d[48]), "=f"(d[49]), "=f"(d[50]), "=f"(d[51]), "=f"(d[52]), "=f"(d[53]), "=f"(d[54]), "=f"(d[55]), "=f"(d[56]), "=f"(d[57]), "=f"(d[58]), "=f"(d[59]), "=f"(d[60]), "=f"(d[61]), "=f"(d[62]), "=f"(d[63]),
      "=f"(d[64]), "=f"(d[65]), "=f"(d[66]), "=f"(d[67]), "=f"(d[68]), "=f"(d[69]), "=f"(d[70]), "=f"(d[71]), "=f"(d[72]), "=f"(d[73]), "=f"(d[74]), "=f"(d[75]), "=f"(d[76]), "=f"(d[77]), "=f"(d[78]), "=f"(d[79]),
      "=f"(d[80]), "=f"(d[81]), "=f"(d[82]), "=f"(d[83]), "=f"(d[84]), "=f"(d[85]), "=f"(d[86]), "=f"(d[87]), "=f"(d[88]), "=f"(d[89]), "=f"(d[90]), "=f"(d[91]), "=f"(d[92]), "=f"(d[93]), "=f"(d[94]), "=f"(d[95]),
      "=f"(d[96]), "=f"(d[97]), "=f"(d[98]), "=f"(d[99]), "=f"(d[100]), "=f"(d[101]), "=f"(d[102]), "=f"(d[103]), "=f"(d[104]), "=f"(d[105]), "=f"(d[106]), "=f"(d[107]), "=f"(d[108]), "=f"(d[109]), "=f"(d[110]), "=f"(d[111]),
      "=f"(d[112]), "=f"(d[113]), "=f"(d[114]), "=f"(d[115]), "=f"(d[116]), "=f"(d[117]), "=f"(d[118]), "=f"(d[119]), "=f"(d[120]), "=f"(d[121]), "=f"(d[122]), "=f"(d[123]), "=f"(d[124]), "=f"(d[125]), "=f"(d[126]), "=f"(d[127])
    : "l"(da), "n"(OA), "l"(db), "n"(OB));
}
template <int OA, int OB> __device__ __forceinline__ void wg_gemm_acc(float (&d)[128], uint64_t da, uint64_t db) {
  asm volatile("{\n.reg .pred p;\n.reg .b64 da, db;\nadd.s64 da, %128, %129;\nadd.s64 db, %130, %131;\nsetp.eq.b32 p, 0, 0;\n"
    "wgmma.mma_async.sync.aligned.m64n256k16.f32.bf16.bf16 {"
    "%0, %1, %2, %3, %4, %5, %6, %7, %8, %9, %10, %11, %12, %13, %14, %15, %16, %17, %18, %19, %20, %21, %22, %23, %24, %25, %26, %27, %28, %29, %30, %31, "
    "%32, %33, %34, %35, %36, %37, %38, %39, %40, %41, %42, %43, %44, %45, %46, %47, %48, %49, %50, %51, %52, %53, %54, %55, %56, %57, %58, %59, %60, %61, %62, %63, "
    "%64, %65, %66, %67, %68, %69, %70, %71, %72, %73, %74, %75, %76, %77, %78, %79, %80, %81, %82, %83, %84, %85, %86, %87, %88, %89, %90, %91, %92, %93, %94, %95, "
    "%96, %97, %98, %99, %100, %101, %102, %103, %104, %105, %106, %107, %108, %109, %110, %111, %112, %113, %114, %115, %116, %117, %118, %119, %120, %121, %122, %123, %124, %125, %126, %127}, "
    "da, db, p, 1, 1, 0, 1;\n}\n"
    : "+f"(d[0]), "+f"(d[1]), "+f"(d[2]), "+f"(d[3]), "+f"(d[4]), "+f"(d[5]), "+f"(d[6]), "+f"(d[7]), "+f"(d[8]), "+f"(d[9]), "+f"(d[10]), "+f"(d[11]), "+f"(d[12]), "+f"(d[13]), "+f"(d[14]), "+f"(d[15]),
      "+f"(d[16]), "+f"(d[17]), "+f"(d[18]), "+f"(d[19]), "+f"(d[20]), "+f"(d[21]), "+f"(d[22]), "+f"(d[23]), "+f"(d[24]), "+f"(d[25]), "+f"(d[26]), "+f"(d[27]), "+f"(d[28]), "+f"(d[29]), "+f"(d[30]), "+f"(d[31]),
      "+f"(d[32]), "+f"(d[33]), "+f"(d[34]), "+f"(d[35]), "+f"(d[36]), "+f"(d[37]), "+f"(d[38]), "+f"(d[39]), "+f"(d[40]), "+f"(d[41]), "+f"(d[42]), "+f"(d[43]), "+f"(d[44]), "+f"(d[45]), "+f"(d[46]), "+f"(d[47]),
      "+f"(d[48]), "+f"(d[49]), "+f"(d[50]), "+f"(d[51]), "+f"(d[52]), "+f"(d[53]), "+f"(d[54]), "+f"(d[55]), "+f"(d[56]), "+f"(d[57]), "+f"(d[58]), "+f"(d[59]), "+f"(d[60]), "+f"(d[61]), "+f"(d[62]), "+f"(d[63]),
      "+f"(d[64]), "+f"(d[65]), "+f"(d[66]), "+f"(d[67]), "+f"(d[68]), "+f"(d[69]), "+f"(d[70]), "+f"(d[71]), "+f"(d[72]), "+f"(d[73]), "+f"(d[74]), "+f"(d[75]), "+f"(d[76]), "+f"(d[77]), "+f"(d[78]), "+f"(d[79]),
      "+f"(d[80]), "+f"(d[81]), "+f"(d[82]), "+f"(d[83]), "+f"(d[84]), "+f"(d[85]), "+f"(d[86]), "+f"(d[87]), "+f"(d[88]), "+f"(d[89]), "+f"(d[90]), "+f"(d[91]), "+f"(d[92]), "+f"(d[93]), "+f"(d[94]), "+f"(d[95]),
      "+f"(d[96]), "+f"(d[97]), "+f"(d[98]), "+f"(d[99]), "+f"(d[100]), "+f"(d[101]), "+f"(d[102]), "+f"(d[103]), "+f"(d[104]), "+f"(d[105]), "+f"(d[106]), "+f"(d[107]), "+f"(d[108]), "+f"(d[109]), "+f"(d[110]), "+f"(d[111]),
      "+f"(d[112]), "+f"(d[113]), "+f"(d[114]), "+f"(d[115]), "+f"(d[116]), "+f"(d[117]), "+f"(d[118]), "+f"(d[119]), "+f"(d[120]), "+f"(d[121]), "+f"(d[122]), "+f"(d[123]), "+f"(d[124]), "+f"(d[125]), "+f"(d[126]), "+f"(d[127])
    : "l"(da), "n"(OA), "l"(db), "n"(OB));
}
template <int OA, int OB> __device__ __forceinline__ void wg_gemm_init(float (&d)[96], uint64_t da, uint64_t db) {
  asm volatile("{\n.reg .pred p;\n.reg .b64 da, db;\nadd.s64 da, %96, %97;\nadd.s64 db, %98, %99;\nsetp.ne.b32 p, 0, 0;\n"
    "wgmma.mma_async.sync.aligned.m64n192k16.f32.bf16.bf16 {"
    "%0, %1, %2, %3, %4, %5, %6, %7, %8, %9, %10, %11, %12, %13, %14, %15, %16, %17, %18, %19, %20, %21, %22, %23, %24, %25, %26, %27, %28, %29, %30, %31, "
    "%32, %33, %34, %35, %36, %37, %38, %39, %40, %41, %42, %43, %44, %45, %46, %47, %48, %49, %50, %51, %52, %53, %54, %55, %56, %57, %58, %59, %60, %61, %62, %63, "
    "%64, %65, %66, %67, %68, %69, %70, %71, %72, %73, %74, %75, %76, %77, %78, %79, %80, %81, %82, %83, %84, %85, %86, %87, %88, %89, %90, %91, %92, %93, %94, %95}, "
    "da, db, p, 1, 1, 0, 1;\n}\n"
    : "=f"(d[0]), "=f"(d[1]), "=f"(d[2]), "=f"(d[3]), "=f"(d[4]), "=f"(d[5]), "=f"(d[6]), "=f"(d[7]), "=f"(d[8]), "=f"(d[9]), "=f"(d[10]), "=f"(d[11]), "=f"(d[12]), "=f"(d[13]), "=f"(d[14]), "=f"(d[15]),
      "=f"(d[16]), "=f"(d[17]), "=f"(d[18]), "=f"(d[19]), "=f"(d[20]), "=f"(d[21]), "=f"(d[22]), "=f"(d[23]), "=f"(d[24]), "=f"(d[25]), "=f"(d[26]), "=f"(d[27]), "=f"(d[28]), "=f"(d[29]), "=f"(d[30]), "=f"(d[31]),
      "=f"(d[32]), "=f"(d[33]), "=f"(d[34]), "=f"(d[35]), "=f"(d[36]), "=f"(d[37]), "=f"(d[38]), "=f"(d[39]), "=f"(d[40]), "=f"(d[41]), "=f"(d[42]), "=f"(d[43]), "=f"(d[44]), "=f"(d[45]), "=f"(d[46]), "=f"(d[47]),
      "=f"(d[48]), "=f"(d[49]), "=f"(d[50]), "=f"(d[51]), "=f"(d[52]), "=f"(d[53]), "=f"(d[54]), "=f"(d[55]), "=f"(d[56]), "=f"(d[57]), "=f"(d[58]), "=f"(d[59]), "=f"(d[60]), "=f"(d[61]), "=f"(d[62]), "=f"(d[63]),
      "=f"(d[64]), "=f"(d[65]), "=f"(d[66]), "=f"(d[67]), "=f"(d[68]), "=f"(d[69]), "=f"(d[70]), "=f"(d[71]), "=f"(d[72]), "=f"(d[73]), "=f"(d[74]), "=f"(d[75]), "=f"(d[76]), "=f"(d[77]), "=f"(d[78]), "=f"(d[79]),
      "=f"(d[80]), "=f"(d[81]), "=f"(d[82]), "=f"(d[83]), "=f"(d[84]), "=f"(d[85]), "=f"(d[86]), "=f"(d[87]), "=f"(d[88]), "=f"(d[89]), "=f"(d[90]), "=f"(d[91]), "=f"(d[92]), "=f"(d[93]), "=f"(d[94]), "=f"(d[95])
    : "l"(da), "n"(OA), "l"(db), "n"(OB));
}
template <int OA, int OB> __device__ __forceinline__ void wg_gemm_acc(float (&d)[96], uint64_t da, uint64_t db) {
  asm volatile("{\n.reg .pred p;\n.reg .b64 da, db;\nadd.s64 da, %96, %97;\nadd.s64 db, %98, %99;\nsetp.eq.b32 p, 0, 0;\n"
    "wgmma.mma_async.sync.aligned.m64n192k16.f32.bf16.bf16 {"
    "%0, %1, %2, %3, %4, %5, %6, %7, %8, %9, %10, %11, %12, %13, %14, %15, %16, %17, %18, %19, %20, %21, %22, %23, %24, %25, %26, %27, %28, %29, %30, %31, "
    "%32, %33, %34, %35, %36, %37, %38, %39, %40, %41, %42, %43, %44, %45, %46, %47, %48, %49, %50, %51, %52, %53, %54, %55, %56, %57, %58, %59, %60, %61, %62, %63, "
    "%64, %65, %66, %67, %68, %69, %70, %71, %72, %73, %74, %75, %76, %77, %78, %79, %80, %81, %82, %83, %84, %85, %86, %87, %88, %89, %90, %91, %92, %93, %94, %95}, "
    "da, db, p, 1, 1, 0, 1;\n}\n"
    : "+f"(d[0]), "+f"(d[1]), "+f"(d[2]), "+f"(d[3]), "+f"(d[4]), "+f"(d[5]), "+f"(d[6]), "+f"(d[7]), "+f"(d[8]), "+f"(d[9]), "+f"(d[10]), "+f"(d[11]), "+f"(d[12]), "+f"(d[13]), "+f"(d[14]), "+f"(d[15]),
      "+f"(d[16]), "+f"(d[17]), "+f"(d[18]), "+f"(d[19]), "+f"(d[20]), "+f"(d[21]), "+f"(d[22]), "+f"(d[23]), "+f"(d[24]), "+f"(d[25]), "+f"(d[26]), "+f"(d[27]), "+f"(d[28]), "+f"(d[29]), "+f"(d[30]), "+f"(d[31]),
      "+f"(d[32]), "+f"(d[33]), "+f"(d[34]), "+f"(d[35]), "+f"(d[36]), "+f"(d[37]), "+f"(d[38]), "+f"(d[39]), "+f"(d[40]), "+f"(d[41]), "+f"(d[42]), "+f"(d[43]), "+f"(d[44]), "+f"(d[45]), "+f"(d[46]), "+f"(d[47]),
      "+f"(d[48]), "+f"(d[49]), "+f"(d[50]), "+f"(d[51]), "+f"(d[52]), "+f"(d[53]), "+f"(d[54]), "+f"(d[55]), "+f"(d[56]), "+f"(d[57]), "+f"(d[58]), "+f"(d[59]), "+f"(d[60]), "+f"(d[61]), "+f"(d[62]), "+f"(d[63]),
      "+f"(d[64]), "+f"(d[65]), "+f"(d[66]), "+f"(d[67]), "+f"(d[68]), "+f"(d[69]), "+f"(d[70]), "+f"(d[71]), "+f"(d[72]), "+f"(d[73]), "+f"(d[74]), "+f"(d[75]), "+f"(d[76]), "+f"(d[77]), "+f"(d[78]), "+f"(d[79]),
      "+f"(d[80]), "+f"(d[81]), "+f"(d[82]), "+f"(d[83]), "+f"(d[84]), "+f"(d[85]), "+f"(d[86]), "+f"(d[87]), "+f"(d[88]), "+f"(d[89]), "+f"(d[90]), "+f"(d[91]), "+f"(d[92]), "+f"(d[93]), "+f"(d[94]), "+f"(d[95])
    : "l"(da), "n"(OA), "l"(db), "n"(OB));
}
template <int OA, int OB> __device__ __forceinline__ void wg_qk_init(float (&d)[64], uint64_t da, uint64_t db) {
  asm volatile("{\n.reg .pred p;\n.reg .b64 da, db;\nadd.s64 da, %64, %65;\nadd.s64 db, %66, %67;\nsetp.ne.b32 p, 0, 0;\n"
    "wgmma.mma_async.sync.aligned.m64n128k16.f32.bf16.bf16 {"
    "%0, %1, %2, %3, %4, %5, %6, %7, %8, %9, %10, %11, %12, %13, %14, %15, %16, %17, %18, %19, %20, %21, %22, %23, %24, %25, %26, %27, %28, %29, %30, %31, "
    "%32, %33, %34, %35, %36, %37, %38, %39, %40, %41, %42, %43, %44, %45, %46, %47, %48, %49, %50, %51, %52, %53, %54, %55, %56, %57, %58, %59, %60, %61, %62, %63}, "
    "da, db, p, 1, 1, 0, 0;\n}\n"
    : "=f"(d[0]), "=f"(d[1]), "=f"(d[2]), "=f"(d[3]), "=f"(d[4]), "=f"(d[5]), "=f"(d[6]), "=f"(d[7]), "=f"(d[8]), "=f"(d[9]), "=f"(d[10]), "=f"(d[11]), "=f"(d[12]), "=f"(d[13]), "=f"(d[14]), "=f"(d[15]),
      "=f"(d[16]), "=f"(d[17]), "=f"(d[18]), "=f"(d[19]), "=f"(d[20]), "=f"(d[21]), "=f"(d[22]), "=f"(d[23]), "=f"(d[24]), "=f"(d[25]), "=f"(d[26]), "=f"(d[27]), "=f"(d[28]), "=f"(d[29]), "=f"(d[30]), "=f"(d[31]),
      "=f"(d[32]), "=f"(d[33]), "=f"(d[34]), "=f"(d[35]), "=f"(d[36]), "=f"(d[37]), "=f"(d[38]), "=f"(d[39]), "=f"(d[40]), "=f"(d[41]), "=f"(d[42]), "=f"(d[43]), "=f"(d[44]), "=f"(d[45]), "=f"(d[46]), "=f"(d[47]),
      "=f"(d[48]), "=f"(d[49]), "=f"(d[50]), "=f"(d[51]), "=f"(d[52]), "=f"(d[53]), "=f"(d[54]), "=f"(d[55]), "=f"(d[56]), "=f"(d[57]), "=f"(d[58]), "=f"(d[59]), "=f"(d[60]), "=f"(d[61]), "=f"(d[62]), "=f"(d[63])
    : "l"(da), "n"(OA), "l"(db), "n"(OB));
}
template <int OA, int OB> __device__ __forceinline__ void wg_qk_acc(float (&d)[64], uint64_t da, uint64_t db) {
  asm volatile("{\n.reg .pred p;\n.reg .b64 da, db;\nadd.s64 da, %64, %65;\nadd.s64 db, %66, %67;\nsetp.eq.b32 p, 0, 0;\n"
    "wgmma.mma_async.sync.aligned.m64n128k16.f32.bf16.bf16 {"
    "%0, %1, %2, %3, %4, %5, %6, %7, %8, %9, %10, %11, %12, %13, %14, %15, %16, %17, %18, %19, %20, %21, %22, %23, %24, %25, %26, %27, %28, %29, %30, %31, "
    "%32, %33, %34, %35, %36, %37, %38, %39, %40, %41, %42, %43, %44, %45, %46, %47, %48, %49, %50, %51, %52, %53, %54, %55, %56, %57, %58, %59, %60, %61, %62, %63}, "
    "da, db, p, 1, 1, 0, 0;\n}\n"
    : "+f"(d[0]), "+f"(d[1]), "+f"(d[2]), "+f"(d[3]), "+f"(d[4]), "+f"(d[5]), "+f"(d[6]), "+f"(d[7]), "+f"(d[8]), "+f"(d[9]), "+f"(d[10]), "+f"(d[11]), "+f"(d[12]), "+f"(d[13]), "+f"(d[14]), "+f"(d[15]),
      "+f"(d[16]), "+f"(d[17]), "+f"(d[18]), "+f"(d[19]), "+f"(d[20]), "+f"(d[21]), "+f"(d[22]), "+f"(d[23]), "+f"(d[24]), "+f"(d[25]), "+f"(d[26]), "+f"(d[27]), "+f"(d[28]), "+f"(d[29]), "+f"(d[30]), "+f"(d[31]),
      "+f"(d[32]), "+f"(d[33]), "+f"(d[34]), "+f"(d[35]), "+f"(d[36]), "+f"(d[37]), "+f"(d[38]), "+f"(d[39]), "+f"(d[40]), "+f"(d[41]), "+f"(d[42]), "+f"(d[43]), "+f"(d[44]), "+f"(d[45]), "+f"(d[46]), "+f"(d[47]),
      "+f"(d[48]), "+f"(d[49]), "+f"(d[50]), "+f"(d[51]), "+f"(d[52]), "+f"(d[53]), "+f"(d[54]), "+f"(d[55]), "+f"(d[56]), "+f"(d[57]), "+f"(d[58]), "+f"(d[59]), "+f"(d[60]), "+f"(d[61]), "+f"(d[62]), "+f"(d[63])
    : "l"(da), "n"(OA), "l"(db), "n"(OB));
}
template <int OA, int OB> __device__ __forceinline__ void wg_qk64_init(float (&d)[64], uint64_t da, uint64_t db) {
  asm volatile("{\n.reg .pred p;\n.reg .b64 da, db;\nadd.s64 da, %32, %33;\nadd.s64 db, %34, %35;\nsetp.ne.b32 p, 0, 0;\n"
    "wgmma.mma_async.sync.aligned.m64n64k16.f32.bf16.bf16 {"
    "%0, %1, %2, %3, %4, %5, %6, %7, %8, %9, %10, %11, %12, %13, %14, %15, %16, %17, %18, %19, %20, %21, %22, %23, %24, %25, %26, %27, %28, %29, %30, %31}, "
    "da, db, p, 1, 1, 0, 0;\n}\n"
    : "=f"(d[0]), "=f"(d[1]), "=f"(d[2]), "=f"(d[3]), "=f"(d[4]), "=f"(d[5]), "=f"(d[6]), "=f"(d[7]), "=f"(d[8]), "=f"(d[9]), "=f"(d[10]), "=f"(d[11]), "=f"(d[12]), "=f"(d[13]), "=f"(d[14]), "=f"(d[15]),
      "=f"(d[16]), "=f"(d[17]), "=f"(d[18]), "=f"(d[19]), "=f"(d[20]), "=f"(d[21]), "=f"(d[22]), "=f"(d[23]), "=f"(d[24]), "=f"(d[25]), "=f"(d[26]), "=f"(d[27]), "=f"(d[28]), "=f"(d[29]), "=f"(d[30]), "=f"(d[31])
    : "l"(da), "n"(OA), "l"(db), "n"(OB));
}
template <int OA, int OB> __device__ __forceinline__ void wg_qk64_acc(float (&d)[64], uint64_t da, uint64_t db) {
  asm volatile("{\n.reg .pred p;\n.reg .b64 da, db;\nadd.s64 da, %32, %33;\nadd.s64 db, %34, %35;\nsetp.eq.b32 p, 0, 0;\n"
    "wgmma.mma_async.sync.aligned.m64n64k16.f32.bf16.bf16 {"
    "%0, %1, %2, %3, %4, %5, %6, %7, %8, %9, %10, %11, %12, %13, %14, %15, %16, %17, %18, %19, %20, %21, %22, %23, %24, %25, %26, %27, %28, %29, %30, %31}, "
    "da, db, p, 1, 1, 0, 0;\n}\n"
    : "+f"(d[0]), "+f"(d[1]), "+f"(d[2]), "+f"(d[3]), "+f"(d[4]), "+f"(d[5]), "+f"(d[6]), "+f"(d[7]), "+f"(d[8]), "+f"(d[9]), "+f"(d[10]), "+f"(d[11]), "+f"(d[12]), "+f"(d[13]), "+f"(d[14]), "+f"(d[15]),
      "+f"(d[16]), "+f"(d[17]), "+f"(d[18]), "+f"(d[19]), "+f"(d[20]), "+f"(d[21]), "+f"(d[22]), "+f"(d[23]), "+f"(d[24]), "+f"(d[25]), "+f"(d[26]), "+f"(d[27]), "+f"(d[28]), "+f"(d[29]), "+f"(d[30]), "+f"(d[31])
    : "l"(da), "n"(OA), "l"(db), "n"(OB));
}
template <int OB> __device__ __forceinline__ void wg_pv_init(float (&d)[64], const uint32_t* a, uint64_t db) {
  asm volatile("{\n.reg .pred p;\n.reg .b64 da, db;\nadd.s64 db, %68, %69;\nsetp.ne.b32 p, 0, 0;\n"
    "wgmma.mma_async.sync.aligned.m64n128k16.f32.bf16.bf16 {"
    "%0, %1, %2, %3, %4, %5, %6, %7, %8, %9, %10, %11, %12, %13, %14, %15, %16, %17, %18, %19, %20, %21, %22, %23, %24, %25, %26, %27, %28, %29, %30, %31, "
    "%32, %33, %34, %35, %36, %37, %38, %39, %40, %41, %42, %43, %44, %45, %46, %47, %48, %49, %50, %51, %52, %53, %54, %55, %56, %57, %58, %59, %60, %61, %62, %63}, "
    "{%64, %65, %66, %67}, db, p, 1, 1, 1;\n}\n"
    : "=f"(d[0]), "=f"(d[1]), "=f"(d[2]), "=f"(d[3]), "=f"(d[4]), "=f"(d[5]), "=f"(d[6]), "=f"(d[7]), "=f"(d[8]), "=f"(d[9]), "=f"(d[10]), "=f"(d[11]), "=f"(d[12]), "=f"(d[13]), "=f"(d[14]), "=f"(d[15]),
      "=f"(d[16]), "=f"(d[17]), "=f"(d[18]), "=f"(d[19]), "=f"(d[20]), "=f"(d[21]), "=f"(d[22]), "=f"(d[23]), "=f"(d[24]), "=f"(d[25]), "=f"(d[26]), "=f"(d[27]), "=f"(d[28]), "=f"(d[29]), "=f"(d[30]), "=f"(d[31]),
      "=f"(d[32]), "=f"(d[33]), "=f"(d[34]), "=f"(d[35]), "=f"(d[36]), "=f"(d[37]), "=f"(d[38]), "=f"(d[39]), "=f"(d[40]), "=f"(d[41]), "=f"(d[42]), "=f"(d[43]), "=f"(d[44]), "=f"(d[45]), "=f"(d[46]), "=f"(d[47]),
      "=f"(d[48]), "=f"(d[49]), "=f"(d[50]), "=f"(d[51]), "=f"(d[52]), "=f"(d[53]), "=f"(d[54]), "=f"(d[55]), "=f"(d[56]), "=f"(d[57]), "=f"(d[58]), "=f"(d[59]), "=f"(d[60]), "=f"(d[61]), "=f"(d[62]), "=f"(d[63])
    : "r"(a[0]), "r"(a[1]), "r"(a[2]), "r"(a[3]), "l"(db), "n"(OB));
}
template <int OB> __device__ __forceinline__ void wg_pv_acc(float (&d)[64], const uint32_t* a, uint64_t db) {
  asm volatile("{\n.reg .pred p;\n.reg .b64 da, db;\nadd.s64 db, %68, %69;\nsetp.eq.b32 p, 0, 0;\n"
    "wgmma.mma_async.sync.aligned.m64n128k16.f32.bf16.bf16 {"
    "%0, %1, %2, %3, %4, %5, %6, %7, %8, %9, %10, %11, %12, %13, %14, %15, %16, %17, %18, %19, %20, %21, %22, %23, %24, %25, %26, %27, %28, %29, %30, %31, "
    "%32, %33, %34, %35, %36, %37, %38, %39, %40, %41, %42, %43, %44, %45, %46, %47, %48, %49, %50, %51, %52, %53, %54, %55, %56, %57, %58, %59, %60, %61, %62, %63}, "
    "{%64, %65, %66, %67}, db, p, 1, 1, 1;\n}\n"
    : "+f"(d[0]), "+f"(d[1]), "+f"(d[2]), "+f"(d[3]), "+f"(d[4]), "+f"(d[5]), "+f"(d[6]), "+f"(d[7]), "+f"(d[8]), "+f"(d[9]), "+f"(d[10]), "+f"(d[11]), "+f"(d[12]), "+f"(d[13]), "+f"(d[14]), "+f"(d[15]),
      "+f"(d[16]), "+f"(d[17]), "+f"(d[18]), "+f"(d[19]), "+f"(d[20]), "+f"(d[21]), "+f"(d[22]), "+f"(d[23]), "+f"(d[24]), "+f"(d[25]), "+f"(d[26]), "+f"(d[27]), "+f"(d[28]), "+f"(d[29]), "+f"(d[30]), "+f"(d[31]),
      "+f"(d[32]), "+f"(d[33]), "+f"(d[34]), "+f"(d[35]), "+f"(d[36]), "+f"(d[37]), "+f"(d[38]), "+f"(d[39]), "+f"(d[40]), "+f"(d[41]), "+f"(d[42]), "+f"(d[43]), "+f"(d[44]), "+f"(d[45]), "+f"(d[46]), "+f"(d[47]),
      "+f"(d[48]), "+f"(d[49]), "+f"(d[50]), "+f"(d[51]), "+f"(d[52]), "+f"(d[53]), "+f"(d[54]), "+f"(d[55]), "+f"(d[56]), "+f"(d[57]), "+f"(d[58]), "+f"(d[59]), "+f"(d[60]), "+f"(d[61]), "+f"(d[62]), "+f"(d[63])
    : "r"(a[0]), "r"(a[1]), "r"(a[2]), "r"(a[3]), "l"(db), "n"(OB));
}

struct Cons {
  uint32_t d0, da;
  uint32_t sb;
  uint32_t rel;
  uint32_t p0, p1;
  uint32_t lead, round, fpar;
};

template <uint32_t OFF, uint32_t GROUP> __device__ __forceinline__ void tile_write(const uint32_t (&pk)[32], uint32_t base) {
  const uint32_t lane = threadIdx.x & 31, wq = (threadIdx.x >> 5) & 3;
  const uint32_t a = base + (wq * 16 + (lane & 15)) * 128 + (((lane >> 4) ^ (lane & 7)) << 4);
#define TW(j) stmatrix_x4<OFF + (j >> 2) * GROUP>(a ^ ((j & 3) * 32), pk[4 * j + 0], pk[4 * j + 1], pk[4 * j + 2], pk[4 * j + 3])
  TW(0); TW(1); TW(2); TW(3); TW(4); TW(5); TW(6); TW(7);
#undef TW
}
template <uint32_t OFF, uint32_t GROUP, int A0> __device__ __forceinline__ void tile_pack_write(const float (&acc)[128], uint32_t (&pk)[32], uint32_t base) {
  const uint32_t lane = threadIdx.x & 31, wq = (threadIdx.x >> 5) & 3;
  const uint32_t a = base + (wq * 16 + (lane & 15)) * 128 + (((lane >> 4) ^ (lane & 7)) << 4);
#define TW(j) \
  pk[4 * j + 0] = v_pack(acc[A0 + 8 * j + 0], acc[A0 + 8 * j + 1]); pk[4 * j + 1] = v_pack(acc[A0 + 8 * j + 2], acc[A0 + 8 * j + 3]); \
  pk[4 * j + 2] = v_pack(acc[A0 + 8 * j + 4], acc[A0 + 8 * j + 5]); pk[4 * j + 3] = v_pack(acc[A0 + 8 * j + 6], acc[A0 + 8 * j + 7]); \
  stmatrix_x4<OFF + (j >> 2) * GROUP>(a ^ ((j & 3) * 32), pk[4 * j + 0], pk[4 * j + 1], pk[4 * j + 2], pk[4 * j + 3])
  TW(0); TW(1); TW(2); TW(3); TW(4); TW(5); TW(6); TW(7);
#undef TW
}
__device__ __forceinline__ void stage_write(const uint32_t (&pk)[32], int w, const Cons& cs) {
  mbar_wait<BAR(B_STGE)>(cs.sb + w * 8, (cs.round & 1) ^ 1);
  tile_write<OFF_STG, 8192>(pk, cs.sb + w * 16384);
}
__device__ __forceinline__ void stage_publish(int w, Cons& cs) {
  fence_async_smem();
  __syncwarp();
  mbar_arrive_if<BAR(B_STGF)>(cs.sb + w * 8, (threadIdx.x & 31) == 0);
  cs.round++;
}

template <int ST, bool INIT, bool FIRST = INIT, int NA> __device__ __forceinline__ void g_issue(float (&acc)[NA], const Cons& cs) {
  constexpr int B2 = NA == 128 ? 256 : 768, Z = FIRST ? 128 : 0;
  uint32_t a, b;
  asm volatile("add.u32 %0, %2, %4;\nadd.u32 %1, %3, %5;" : "=r"(a), "=r"(b) : "r"(cs.da), "r"(cs.d0), "n"(dlo(OFF_A + ST * 16384, NA + (FIRST ? 16 : 0))), "n"(dlo(OFF_B + ST * 32768, NA == 128 ? 8192 : 4096) + Z));
  const uint64_t A = desc(a), B = desc(b);
  wg_fence();
  if (INIT) wg_gemm_init<0, -Z>(acc, A, B); else wg_gemm_acc<0, -Z>(acc, A, B);
  wg_gemm_acc<2, 128 - Z>(acc, A, B);
  wg_gemm_acc<4, B2 - Z>(acc, A, B);
  wg_gemm_acc<6, B2 + 128 - Z>(acc, A, B);
  wg_commit();
}
template <int NA, class F>
__device__ __forceinline__ uint32_t gemm_tile(float (&acc)[NA], int nk4, int idx, int w, Cons& cs, uint32_t pend, const uint32_t (&pkA)[32], const uint32_t (&pkB)[32], F&& before_end) {
  const uint32_t sb = cs.sb, rel = cs.rel;
  constexpr int SA = NA == 128 ? STGA : STGAL, SBB = NA == 128 ? STGB : STGBL;
#define HOOK(n) \
  if (n == 0 && (pend & 8)) stage_publish(w, cs); \
  if (n == 0 && (pend & 16) && w == 0) bar_sync(5, 256); \
  if (n == SA && (pend & 1)) stage_write(pkA, w, cs); \
  if (n == SA + 1 && (pend & 1)) { stage_publish(w, cs); pend &= 6; } \
  if (n == SBB && (pend & 2)) { stage_write(pkB, w, cs); pend = 4; } \
  if (n == SBB + 1 && (pend & 4)) { stage_publish(w, cs); pend = 0; }
  mbar_wait<BAR(B_FULL + 0)>(sb, cs.p0);
  g_issue<0, true>(acc, cs);
  HOOK(0);
  mbar_wait<BAR(B_FULL + 1)>(sb, cs.p1);
  g_issue<1, false, true>(acc, cs);
  HOOK(2);
  wg_wait<1>();
  mbar_arrive_cl<BAR(B_EMPTY + 0)>(rel);
  HOOK(3);
  mbar_wait<BAR(B_FULL + 2)>(sb, cs.p0);
  g_issue<2, false, true>(acc, cs);
  HOOK(4);
  wg_wait<1>();
  mbar_arrive_cl<BAR(B_EMPTY + 1)>(rel);
  HOOK(5);
  mbar_wait<BAR(B_FULL + 3)>(sb, cs.p1);
  g_issue<3, false, true>(acc, cs);
  HOOK(6);
  const uint32_t ncode = item(sb, idx + 1);
  wg_wait<1>();
  mbar_arrive_cl<BAR(B_EMPTY + 2)>(rel);
  HOOK(7);
  cs.p0 ^= 1; cs.p1 ^= 1;
  const bool final_tile = NA == 128 && (ncode >> 9) == K_END;
#pragma unroll 1
  for (int q = 1; q < nk4; q++) {
    const bool tail = q == nk4 - 1;
    mbar_wait<BAR(B_FULL + 0)>(sb, cs.p0);
    g_issue<0, false>(acc, cs);
    HOOK(8);
    wg_wait<1>();
    mbar_arrive_cl<BAR(B_EMPTY + 3)>(rel);
    HOOK(9);
    mbar_wait<BAR(B_FULL + 1)>(sb, cs.p1);
    uint32_t rel0 = rel;
    if (final_tile && tail && w == 1) {
      wg_wait<0>();
      mbar_arrive_cl<BAR(B_EMPTY + 0)>(rel);
      rel0 = 0;
      mbar_wait<BAR(B_LEAD)>(sb, cs.lead);
    }
    g_issue<1, false>(acc, cs);
    HOOK(10);
    wg_wait<1>();
    mbar_arrive_cl<BAR(B_EMPTY + 0)>(rel0);
    HOOK(11);
    mbar_wait<BAR(B_FULL + 2)>(sb, cs.p0);
    uint32_t rel1 = rel;
    if (!final_tile && tail && w == 1) {
      wg_wait<0>();
      mbar_arrive_cl<BAR(B_EMPTY + 1)>(rel);
      rel1 = 0;
      mbar_wait<BAR(B_LEAD)>(sb, cs.lead);
    }
    g_issue<2, false>(acc, cs);
    HOOK(12);
    wg_wait<1>();
    mbar_arrive_cl<BAR(B_EMPTY + 1)>(rel1);
    HOOK(13);
    mbar_wait<BAR(B_FULL + 3)>(sb, cs.p1);
    g_issue<3, false>(acc, cs);
    mbar_arrive_if<BAR(B_LEAD)>(sb, tail && threadIdx.x == 128);
    HOOK(14);
    wg_wait<1>();
    mbar_arrive_cl<BAR(B_EMPTY + 2)>(rel);
    cs.p0 ^= 1; cs.p1 ^= 1;
  }
#undef HOOK
  cs.lead ^= 1;
  before_end();
  wg_wait<0>();
  fence_regs(acc);
  mbar_arrive_cl<BAR(B_EMPTY + 3)>(rel);
  return ncode;
}

__device__ __forceinline__ void local_probs(bool first, const float (&S)[3][4], uint32_t (&pb)[4]) {
  const int lane = threadIdx.x & 31, g = lane >> 2, t = lane & 3;
  const bool c0 = 2 * t > g, c1 = 2 * t + 1 > g;
  float x0 = c0 ? S[0][0] : S[1][0], x1 = c1 ? S[0][1] : S[1][1], y0 = c0 ? S[1][2] : S[2][2], y1 = c1 ? S[1][3] : S[2][3];
  if (first && c0) x0 = -INFINITY;
  if (first && c1) x1 = -INFINITY;
  float m0 = fmaxf(x0, x1), m1 = fmaxf(y0, y1);
  m0 = fmaxf(fmaxf(m0, __shfl_xor_sync(0xffffffffu, m0, 1)), fmaxf(__shfl_xor_sync(0xffffffffu, m0, 2), __shfl_xor_sync(0xffffffffu, m0, 3)));
  m1 = fmaxf(fmaxf(m1, __shfl_xor_sync(0xffffffffu, m1, 1)), fmaxf(__shfl_xor_sync(0xffffffffu, m1, 2), __shfl_xor_sync(0xffffffffu, m1, 3)));
  constexpr float C = 0.17677669529663687f * 1.4426950408889634f;
  const float b0 = -m0 * C, b1 = -m1 * C;
  x0 = ex2(fmaf(x0, C, b0)); x1 = ex2(fmaf(x1, C, b0)); y0 = ex2(fmaf(y0, C, b1)); y1 = ex2(fmaf(y1, C, b1));
  const float l0 = rcp(quad_sum(x0 + x1)), l1 = rcp(quad_sum(y0 + y1));
  const uint32_t px = pack_bf16(x0 * l0, x1 * l0), py = pack_bf16(y0 * l1, y1 * l1);
  const uint32_t m = (c0 ? 0xffffu : 0u) | (c1 ? 0xffff0000u : 0u);
  pb[0] = px & m; pb[1] = px & ~m; pb[2] = py & m; pb[3] = py & ~m;
}
struct Loc { uint32_t xa, ra, oa; };
__device__ __forceinline__ Loc local_prepare(uint32_t code, int w, Cons& cs) {
  const uint32_t lane = threadIdx.x & 31, wq = (threadIdx.x >> 5) & 3;
  const bool has_halo = (code & 15) != 0;
  Loc l;
  l.xa = cs.sb + OFF_STG + 8192 + w * 16384 + wq * 2048 + lane * 8;
  l.ra = l.xa - (wq == 0 ? 16384 - 3 * 2048 : 2048);
  if (w + wq == 0) l.ra = has_halo ? cs.sb + OFF_HALO + lane * 8 : l.xa;
  l.oa = cs.sb + w * 16384 + (wq * 16 + (lane & 7)) * 128 + (((lane >> 3) ^ (lane & 7)) << 4);
  asm volatile("{\n.reg .pred p;\nsetp.eq.u32 p, %0, 0;\n@p st.shared.u32 [%1], %2;\n}\n" ::"r"(l.xa), "r"(l.ra), "r"(l.oa) : "memory");
  mbar_wait<BAR(B_STGE)>(cs.sb + w * 8, (cs.round & 1) ^ 1);
  if (has_halo && w == 0) mbar_wait<BAR(B_HFULL)>(cs.sb, cs.fpar >> 1);
  cs.fpar ^= has_halo ? 2 : 0;
  return l;
}
__device__ __forceinline__ void local_epilogue(const float (&acc)[96], uint32_t code, int w, Cons& cs, const Loc& l) {
  const uint32_t cw = (threadIdx.x >> 5) - 4;
  const bool has_halo = (code & 15) != 0;
  uint32_t kf[3][8], vt[3][8];
#pragma unroll
  for (int j = 0; j < 8; j++) { kf[2][j] = pack_bf16(acc[32 + 4 * j + 2], acc[32 + 4 * j + 3]); vt[2][j] = transpose8(pack_bf16(acc[64 + 4 * j + 2], acc[64 + 4 * j + 3])); }
  sts64<0>(l.xa, &kf[2][0]); sts64<256>(l.xa, &kf[2][2]); sts64<512>(l.xa, &kf[2][4]); sts64<768>(l.xa, &kf[2][6]);
  sts64<1024>(l.xa, &vt[2][0]); sts64<1280>(l.xa, &vt[2][2]); sts64<1536>(l.xa, &vt[2][4]); sts64<1792>(l.xa, &vt[2][6]);
  if (cw == 3) bar_arrive(4, 160);
  uint32_t q[8][2];
#pragma unroll
  for (int j = 0; j < 8; j++) {
    q[j][0] = pack_bf16(acc[4 * j], acc[4 * j + 1]); q[j][1] = pack_bf16(acc[4 * j + 2], acc[4 * j + 3]);
    kf[1][j] = pack_bf16(acc[32 + 4 * j], acc[32 + 4 * j + 1]);
  }
  bar_sync(3 + w, 128 + 32 * w);
  uint32_t z[4];
  lds128<OFF_FILLS + 16>(z, cs.sb);
  lds64<0>(&kf[0][0], l.ra); lds64<512>(&kf[0][4], l.ra); lds64<256>(&kf[0][2], l.ra); lds64<768>(&kf[0][6], l.ra);
  lds64<1024>(&vt[0][0], l.ra); lds64<1280>(&vt[0][2], l.ra); lds64<1536>(&vt[0][4], l.ra); lds64<1792>(&vt[0][6], l.ra);
  float S[2][3][4];
#pragma unroll
  for (int n = 2; n >= 0; n--)
#pragma unroll
    for (int u = 0; u < 2; u++) mma16816z(S[u][n], q[4 * u][0], q[4 * u][1], q[4 * u + 1][0], q[4 * u + 1][1], kf[n][4 * u], kf[n][4 * u + 1], z);
#pragma unroll
  for (int n = 2; n >= 0; n--)
#pragma unroll
    for (int u = 0; u < 2; u++) mma16816(S[u][n], q[4 * u + 2][0], q[4 * u + 2][1], q[4 * u + 3][0], q[4 * u + 3][1], kf[n][4 * u + 2], kf[n][4 * u + 3]);
#pragma unroll
  for (int j = 0; j < 8; j++) vt[1][j] = transpose8(pack_bf16(acc[64 + 4 * j], acc[64 + 4 * j + 1]));
  uint32_t pb[2][4];
#pragma unroll
  for (int u = 0; u < 2; u++) local_probs(cw == 0 && !has_halo, S[u], pb[u]);
  const uint32_t oa = l.oa;
#pragma unroll
  for (int u = 0; u < 2; u++)
#pragma unroll
    for (int hf = 0; hf < 2; hf++) {
      float O[2][4];
#pragma unroll
      for (int mt = 0; mt < 2; mt++) {
        O[mt][0] = O[mt][1] = O[mt][2] = O[mt][3] = 0.f;
        mma16816(O[mt], vt[hf][4 * u + 2 * mt], vt[hf][4 * u + 2 * mt + 1], vt[hf + 1][4 * u + 2 * mt], vt[hf + 1][4 * u + 2 * mt + 1], pb[u][2 * hf], pb[u][2 * hf + 1]);
      }
      const uint32_t o0 = pack_bf16(O[0][0], O[0][1]), o1 = pack_bf16(O[0][2], O[0][3]), o2 = pack_bf16(O[1][0], O[1][1]), o3 = pack_bf16(O[1][2], O[1][3]);
      if (hf == 0) stmatrix_x4_trans<OFF_STG>(oa ^ (u * 64), o0, o1, o2, o3); else stmatrix_x4_trans<OFF_STG + 1024>(oa ^ (u * 64), o0, o1, o2, o3);
    }
  mbar_arrive_if<BAR(B_HEMPTY)>(cs.sb, has_halo && threadIdx.x == 128);
}

constexpr float SCALE_LOG2 = 0.08838834764831845f * 1.4426950408889634f;
#define SUM_LO 8.673617379884035e-19f
#define SUM_HI 1152921504606846976.f
template <int J0> __device__ __forceinline__ void causal_mask(float (&S)[64], int r) {
#pragma unroll
  for (int j = 0; j < 8; j++) {
    if (8 * j > r) S[4 * (J0 + j) + 0] = -INFINITY;
    if (8 * j + 1 > r) S[4 * (J0 + j) + 1] = -INFINITY;
    if (8 * j - 8 > r) S[4 * (J0 + j) + 2] = -INFINITY;
    if (8 * j - 7 > r) S[4 * (J0 + j) + 3] = -INFINITY;
  }
}
__device__ __forceinline__ float v_ex2(float x) { float y; asm volatile("ex2.approx.ftz.f32 %0, %1;" : "=f"(y) : "f"(x)); return y; }
__device__ __forceinline__ float v_add(float a, float b) { float y; asm volatile("add.f32 %0, %1, %2;" : "=f"(y) : "f"(a), "f"(b)); return y; }
__device__ __forceinline__ float v_mul(float a, float b) { float y; asm volatile("mul.f32 %0, %1, %2;" : "=f"(y) : "f"(a), "f"(b)); return y; }
template <int MJ> __device__ __forceinline__ float exp_el(float x, int j, int e, int r) {
  float p = v_ex2(x);
  if (j >= MJ) asm volatile("{\n.reg .pred q;\nsetp.lt.s32 q, %1, %2;\n@q mov.b32 %0, 0f00000000;\n}\n" : "+f"(p) : "r"(r), "r"(8 * (j - MJ) + (e & 1) - 4 * (e & 2)));
  return p;
}
template <int J0, int J1, int MJ = 16> __device__ __forceinline__ void exp_inplace(float (&S)[64], float& l0, float& l1, int r = 0) {
#pragma unroll
  for (int j = J0; j < J1; j++) {
#pragma unroll
    for (int e = 0; e < 4; e++) S[4 * j + e] = exp_el<MJ>(S[4 * j + e], j, e, r);
    l0 = v_add(l0, S[4 * j + 0]); l1 = v_add(l1, S[4 * j + 2]); l0 = v_add(l0, S[4 * j + 1]); l1 = v_add(l1, S[4 * j + 3]);
  }
}
template <int JS, int MJ, bool OUT>
__device__ __forceinline__ void exp_pack(float (&S)[64], uint32_t (&P)[32], float& l0, float& l1, int r, const float (&O)[64], float a0, float a1, uint32_t (&pk)[32]) {
#pragma unroll
  for (int j = JS; j < 16; j++) {
    const float p0 = exp_el<MJ>(S[4 * j + 0], j, 0, r), p1 = exp_el<MJ>(S[4 * j + 1], j, 1, r), p2 = exp_el<MJ>(S[4 * j + 2], j, 2, r), p3 = exp_el<MJ>(S[4 * j + 3], j, 3, r);
#pragma unroll
    for (int k = (j - JS) * JS / (16 - JS); k < (j + 1 - JS) * JS / (16 - JS); k++) { P[2 * k] = v_pack(S[4 * k + 0], S[4 * k + 1]); P[2 * k + 1] = v_pack(S[4 * k + 2], S[4 * k + 3]); }
    if (OUT) {
#pragma unroll
      for (int k = (j - JS) * 16 / (16 - JS); k < (j + 1 - JS) * 16 / (16 - JS); k++) {
        pk[2 * k] = v_pack(v_mul(O[4 * k + 0], a0), v_mul(O[4 * k + 1], a0)); pk[2 * k + 1] = v_pack(v_mul(O[4 * k + 2], a1), v_mul(O[4 * k + 3], a1));
      }
    }
    l0 = v_add(l0, p0); l1 = v_add(l1, p2); l0 = v_add(l0, p1); l1 = v_add(l1, p3);
    P[2 * j] = v_pack(p0, p1); P[2 * j + 1] = v_pack(p2, p3);
  }
}
__device__ __forceinline__ void pin_after(float a, float b) {
  asm volatile("{\n.reg .pred p;\nsetp.eq.u32 p, %0, 0xffffffff;\n@p st.shared.b32 [%1], %1;\n}\n" ::"r"(__float_as_uint(a)), "r"(__float_as_uint(b)) : "memory");
}
template <bool HALF, int SITE> __device__ __forceinline__ void issue_qk(float (&S)[64], uint32_t qlo, uint32_t klo) {
  uint32_t q, k;
  asm volatile("add.u32 %0, %2, %4;\nadd.u32 %1, %3, %4;" : "=r"(q), "=r"(k) : "r"(qlo), "r"(klo), "n"(SITE << 16));
  const uint64_t qd = desc(q), kd = desc(k);
  wg_fence();
  if (HALF) wg_qk64_init<0, 0>(S, qd, kd); else wg_qk_init<0, 0>(S, qd, kd);
#define QK(o) if (HALF) wg_qk64_acc<o, o>(S, qd, kd); else wg_qk_acc<o, o>(S, qd, kd)
  QK(2); QK(4); QK(6); QK(1024); QK(1026); QK(1028); QK(1030);
#undef QK
  wg_commit();
}
template <int NK, int ACC, int SITE> __device__ __forceinline__ void issue_pv(float (&O)[64], const uint32_t (&P)[32], uint32_t vlo) {
  constexpr int Z = 128 * SITE;
  uint32_t v;
  asm volatile("add.u32 %0, %1, %2;" : "=r"(v) : "r"(vlo), "n"(Z));
  const uint64_t vd = desc(v);
  wg_fence();
  if (ACC) wg_pv_acc<-Z>(O, &P[0], vd); else wg_pv_init<-Z>(O, &P[0], vd);
  wg_pv_acc<128 - Z>(O, &P[4], vd); wg_pv_acc<256 - Z>(O, &P[8], vd); wg_pv_acc<384 - Z>(O, &P[12], vd);
  if (NK == 8) { wg_pv_acc<512 - Z>(O, &P[16], vd); wg_pv_acc<640 - Z>(O, &P[20], vd); wg_pv_acc<768 - Z>(O, &P[24], vd); wg_pv_acc<896 - Z>(O, &P[28], vd); }
  wg_commit();
}
__device__ __forceinline__ uint32_t row_norm(float l0, float l1, float& a0, float& a1) {
  const float q0 = quad_sum(l0), q1 = quad_sum(l1);
  a0 = rcp(q0); a1 = rcp(q1);
  return __reduce_or_sync(0xffffffffu, (q0 >= SUM_LO && q0 <= SUM_HI && q1 >= SUM_LO && q1 <= SUM_HI) ? 0u : 1u);
}
__device__ __forceinline__ void slow_item(float (&O)[64], float& a0, float& a1, int head, int tile, uint32_t qbase, int w) {
  const int lane = threadIdx.x & 31, g = lane >> 2, t = lane & 3;
  const int rw = w * 64 + (int)__reduce_or_sync(0xffffffffu, (threadIdx.x >> 1) & 48);
  const int row0 = tile * 128 + rw;
  const uint32_t qa_ = qbase + (rw + g) * 128 + ((t ^ g) << 4);
  const __nv_bfloat16* kp = g_kv + ((size_t)head * SEQ + g) * 256 + 8 * t;
  const __nv_bfloat16* vp = g_kv + ((size_t)head * SEQ + 2 * t) * 256 + 128 + g;
  float m0 = -INFINITY, m1 = -INFINITY, l0 = 0.f, l1 = 0.f;
#pragma unroll
  for (int i = 0; i < 64; i++) O[i] = 0.f;
#pragma unroll 1
  for (int key0 = 0; key0 < row0 + 16; key0 += 16) {
    float c[2][4] = {{0.f, 0.f, 0.f, 0.f}, {0.f, 0.f, 0.f, 0.f}};
#pragma unroll 1
    for (int cc = 0; cc < 4; cc++) {
      uint32_t qa[4], qb[4];
      const uint32_t a = (qa_ ^ ((cc & 1) * 64)) + (cc >> 1) * 16384;
      lds128<0>(qa, a); lds128<1024>(qb, a);
#pragma unroll
      for (int n = 0; n < 2; n++) {
        const uint4 kf = ldg128(kp + (size_t)(key0 + 8 * n) * 256 + cc * 32);
        mma16816(c[n], qa[0], qb[0], qa[1], qb[1], kf.x, kf.y);
        mma16816(c[n], qa[2], qb[2], qa[3], qb[3], kf.z, kf.w);
      }
    }
#pragma unroll
    for (int n = 0; n < 2; n++)
#pragma unroll
      for (int e = 0; e < 4; e++)
        if (key0 + 8 * n + 2 * t + (e & 1) > row0 + g + (e >> 1) * 8) c[n][e] = -INFINITY;
    float x0 = fmaxf(fmaxf(c[0][0], c[0][1]), fmaxf(c[1][0], c[1][1])), x1 = fmaxf(fmaxf(c[0][2], c[0][3]), fmaxf(c[1][2], c[1][3]));
    x0 = fmaxf(x0, __shfl_xor_sync(0xffffffffu, x0, 1)); x1 = fmaxf(x1, __shfl_xor_sync(0xffffffffu, x1, 1));
    x0 = fmaxf(x0, __shfl_xor_sync(0xffffffffu, x0, 2)); x1 = fmaxf(x1, __shfl_xor_sync(0xffffffffu, x1, 2));
    const float n0 = fmaxf(m0, x0), n1 = fmaxf(m1, x1);
    const float r0 = ex2(m0 - n0), r1 = ex2(m1 - n1);
    m0 = n0; m1 = n1;
#pragma unroll
    for (int n = 0; n < 2; n++) { c[n][0] = ex2(c[n][0] - n0); c[n][1] = ex2(c[n][1] - n0); c[n][2] = ex2(c[n][2] - n1); c[n][3] = ex2(c[n][3] - n1); }
    l0 = l0 * r0 + ((c[0][0] + c[0][1]) + (c[1][0] + c[1][1]));
    l1 = l1 * r1 + ((c[0][2] + c[0][3]) + (c[1][2] + c[1][3]));
    const uint32_t p0 = pack_bf16(c[0][0], c[0][1]), p1 = pack_bf16(c[0][2], c[0][3]), p2 = pack_bf16(c[1][0], c[1][1]), p3 = pack_bf16(c[1][2], c[1][3]);
#pragma unroll
    for (int j = 0; j < 16; j++) {
      const __nv_bfloat16* v = vp + (size_t)key0 * 256 + j * 8;
      const uint32_t b0 = ldg16(v) | (ldg16(v + 256) << 16), b1 = ldg16(v + 8 * 256) | (ldg16(v + 9 * 256) << 16);
      float o[4] = {O[4 * j] * r0, O[4 * j + 1] * r0, O[4 * j + 2] * r1, O[4 * j + 3] * r1};
      mma16816(o, p0, p1, p2, p3, b0, b1);
      O[4 * j] = o[0]; O[4 * j + 1] = o[1]; O[4 * j + 2] = o[2]; O[4 * j + 3] = o[3];
    }
  }
  a0 = rcp(quad_sum(l0)); a1 = rcp(quad_sum(l1));
}
__device__ __forceinline__ void att_output(const float (&O)[64], float a0, float a1, uint32_t (&pk)[32]) {
#pragma unroll
  for (int k = 0; k < 16; k++) { pk[2 * k] = v_pack(v_mul(O[4 * k + 0], a0), v_mul(O[4 * k + 1], a0)); pk[2 * k + 1] = v_pack(v_mul(O[4 * k + 2], a1), v_mul(O[4 * k + 3], a1)); }
}
template <int J1> __device__ __forceinline__ void exp_stage(float (&S)[64], float& l0, float& l1, const uint32_t (&P)[32], int w, const Cons& cs, uint32_t on) {
  const uint32_t lane = threadIdx.x & 31, wq = (threadIdx.x >> 5) & 3;
  const uint32_t a = cs.sb + w * 16384 + (wq * 16 + (lane & 15)) * 128 + (((lane >> 4) ^ (lane & 7)) << 4);
#define ES(c) \
  exp_inplace<c * J1 / 8, (c + 1) * J1 / 8>(S, l0, l1); \
  stmatrix_x4_after<OFF_STG + (c >> 2) * 8192>(a ^ ((c & 3) * 32), P[4 * c + 0], P[4 * c + 1], P[4 * c + 2], P[4 * c + 3], (c & 1) ? l1 : l0, on)
  ES(0); ES(1); ES(2); ES(3); ES(4); ES(5); ES(6); ES(7);
#undef ES
}
struct Att { uint32_t qd, kd, vd, c8, cb, xc, xp, pub; };
__device__ __forceinline__ void att_advance(Att& t) {
  constexpr uint32_t SLOT = 32768 >> 4;
  t.kd ^= SLOT; t.vd ^= SLOT; t.c8 ^= 8; t.cb ^= 8;
  const uint32_t x = t.xc; t.xc = t.xp ^ 1; t.xp = x;
}
__device__ __forceinline__ void head_sums(float& l0, float& l1, float& a0, float& a1, uint32_t& unsafe, const Cons& cs) {
  unsafe = row_norm(l0, l1, a0, a1);
  mbar_arrive_if<BAR(B_QEMPTY)>(cs.sb, (threadIdx.x & 31) == 0 && !unsafe);
  l0 = l1 = 0.f;
}
template <bool SECOND>
__device__ __forceinline__ uint32_t diag_full(float (&S)[64], float (&O)[64], uint32_t (&P)[32], uint32_t (&pk)[32], float& l0, float& l1, float& a0, float& a1, uint32_t& unsafe, Att& t, int r, Cons& cs) {
  constexpr int JD = SECOND ? JDIAG2 : JDIAG, w = 1;
  bar_sync(2, 256);
  issue_qk<false, 2 + SECOND>(S, t.qd, t.kd);
  if (!SECOND && t.pub) { stage_publish(w, cs); t.pub = 0; }
  mbar_wait<BAR(B_FULL + 2)>(t.cb ^ 8, t.xp);
  issue_pv<8, 1, 4 + SECOND>(O, P, t.vd);
  bar_arrive(1, 256);
  att_advance(t);
  wg_wait<1>();
  fence_regs(S);
  mbar_arrive_cl<BAR(B_EMPTY)>(cs.rel, t.c8 ^ 8);
  if (SECOND) head_sums(l0, l1, a0, a1, unsafe, cs);
  exp_inplace<0, JD, 8>(S, l0, l1, r);
  pin_after(l0, l1);
  wg_wait<0>();
  fence_regs(O);
  fence_regs(P);
  mbar_arrive_cl<BAR(B_EMPTY + 2)>(cs.rel, t.c8);
  uint32_t ready = mbar_test<BAR(B_FULL)>(t.cb, t.xc);
  if (!SECOND) ready &= mbar_test<BAR(B_QFULL)>(cs.sb, cs.fpar & 1);
  exp_pack<JD, 8, SECOND>(S, P, l0, l1, r, O, a0, a1, pk);
  return __reduce_or_sync(0xffffffffu, ready ^ 1);
}
__device__ __forceinline__ void diag_half(bool second, float (&S)[64], float (&O)[64], uint32_t (&P)[32], float& l0, float& l1, float& a0, float& a1, uint32_t& unsafe, Att& t, int r, Cons& cs) {
  constexpr int w = 0;
  bar_sync(1, 256);
  issue_qk<true, 4>(S, t.qd, t.kd);
  mbar_wait<BAR(B_FULL + 2)>(t.cb ^ 8, t.xp);
  if (second) issue_pv<4, 1, 1>(O, P, t.vd); else issue_pv<8, 1, 3>(O, P, t.vd);
  bar_arrive(2, 256);
  if (t.pub) { stage_publish(w, cs); t.pub = 0; }
  att_advance(t);
  if (second) head_sums(l0, l1, a0, a1, unsafe, cs);
  wg_wait<1>();
  fence_regs<0, 32>(S);
  mbar_arrive_cl<BAR(B_EMPTY)>(cs.rel, t.c8 ^ 8);
  exp_inplace<0, 8, 0>(S, l0, l1, r);
  pin_after(l0, l1);
  wg_wait<0>();
  fence_regs(O);
  fence_regs(P);
  mbar_arrive_cl<BAR(B_EMPTY + 2)>(cs.rel, t.c8);
#pragma unroll
  for (int k = 0; k < 8; k++) { P[2 * k] = v_pack(S[4 * k + 0], S[4 * k + 1]); P[2 * k + 1] = v_pack(S[4 * k + 2], S[4 * k + 3]); }
}
__device__ __forceinline__ void attention(uint32_t code, uint32_t rank, int idx, int w, Cons& cs, uint32_t (&P)[32], uint32_t (&pk)[32]) {
  const int lane = threadIdx.x & 31, wq = (threadIdx.x >> 5) & 3;
  constexpr int JS = JSPLIT, JE = JEDGE;
  const uint32_t sb = cs.sb;
  const int y = (code & 15) * 2 + rank;
  const int r = wq * 16 + (lane >> 2) - 2 * (lane & 3);
  float O[64], S[64];
  float l0 = 0.f, l1 = 0.f;
  Att t = {cs.da + dlo(OFF_A, 16), cs.d0 + dlo(OFF_B, 16), cs.d0 + dlo(OFF_B + 98304, 16384), 0, sb, cs.p0, cs.p1, 0};
  uint32_t unsafe = 0, late;
  int ns;
  auto stage_step = [&](uint32_t on) {
    att_advance(t);
    t.pub = 1;
    wg_wait<1>();
    fence_regs(S);
    mbar_arrive_cl<BAR(B_EMPTY)>(cs.rel, t.c8 ^ 8);
    exp_stage<JE>(S, l0, l1, pk, w, cs, on);
    pin_after(l0, l1);
    wg_wait<0>();
    fence_regs(O);
    fence_regs(P);
    mbar_arrive_cl<BAR(B_EMPTY + 2)>(cs.rel, t.c8);
    const uint32_t ready = mbar_test<BAR(B_FULL)>(t.cb, t.xc);
    exp_pack<JE, 16, false>(S, P, l0, l1, r, O, 0.f, 0.f, pk);
    late = __reduce_or_sync(0xffffffffu, ready ^ 1);
  };
  bar_sync(3 - w, 128 + 128 * w);
  if (y >= 2) {
    issue_qk<false, 6>(O, t.qd, cs.d0 + dlo(OFF_B + 32768, 16));
    mbar_wait<BAR(B_FULL)>(sb, t.xc);
    issue_qk<false, 7>(S, t.qd, t.kd);
    bar_arrive(1 + (w ^ 1), 256);
    wg_wait<1>();
    fence_regs(O);
    mbar_arrive_cl<BAR(B_EMPTY + 1)>(cs.rel);
    exp_stage<JP>(O, l0, l1, pk, w, cs, w ^ 1);
    pin_after(l0, l1);
    const uint32_t rd = mbar_test<BAR(B_FULL + 3)>(sb, t.xp);
    exp_pack<JP, 16, false>(O, P, l0, l1, r, O, 0.f, 0.f, pk);
    if (UNLIKELY(__reduce_or_sync(0xffffffffu, rd ^ 1))) mbar_wait<BAR(B_FULL + 3)>(sb, t.xp);
    bar_sync(1 + w, 256);
    issue_pv<8, 0, 6>(O, P, t.vd);
    bar_arrive(1 + (w ^ 1), 256);
    stage_step(w);
    ns = y - 2;
  } else {
    issue_qk<false, 8>(S, t.qd, cs.d0 + dlo(OFF_B + 32768, 16));
    bar_arrive(1 + (w ^ 1), 256);
    wg_wait<0>();
    fence_regs(S);
    mbar_arrive_cl<BAR(B_EMPTY + 1)>(cs.rel);
    causal_mask<0>(S, r + 64 * w + 128 * y);
    causal_mask<8>(S, r + 64 * w + 128 * y - 64);
    exp_pack<0, 16, false>(S, P, l0, l1, r, S, 0.f, 0.f, pk);
#pragma unroll
    for (int i = 0; i < 64; i++) O[i] = 0.f;
    late = 1;
    ns = 0;
  }
#pragma unroll 1
  for (uint32_t head = 0;; head++) {
    while (ns > 0) {
      if (UNLIKELY(late)) mbar_wait<BAR(B_FULL)>(t.cb, t.xc);
      bar_sync(1 + w, 256);
      issue_qk<false, 9>(S, t.qd, t.kd);
      if (t.pub) { stage_publish(w, cs); t.pub = 0; }
      mbar_wait<BAR(B_FULL + 2)>(t.cb ^ 8, t.xp);
      issue_pv<8, 1, 0>(O, P, t.vd);
      bar_arrive(1 + (w ^ 1), 256);
      ns--;
      att_advance(t);
      wg_wait<1>();
      fence_regs(S);
      mbar_arrive_cl<BAR(B_EMPTY)>(cs.rel, t.c8 ^ 8);
      exp_inplace<0, JS>(S, l0, l1);
      pin_after(l0, l1);
      wg_wait<0>();
      fence_regs(O);
      fence_regs(P);
      mbar_arrive_cl<BAR(B_EMPTY + 2)>(cs.rel, t.c8);
      const uint32_t rd = mbar_test<BAR(B_FULL)>(t.cb, t.xc);
      exp_pack<JS, 16, false>(S, P, l0, l1, 0, O, 0.f, 0.f, pk);
      late = __reduce_or_sync(0xffffffffu, rd ^ 1);
    }
    float a0 = 0.f, a1 = 0.f;
    if (head == 0) {
      if (w == 1) {
        if (y != 0) {
          if (UNLIKELY(late)) mbar_wait<BAR(B_FULL)>(t.cb, t.xc);
          late = diag_full<false>(S, O, P, pk, l0, l1, a0, a1, unsafe, t, r, cs);
        }
        t.qd += 32768 >> 4;
        if (UNLIKELY(late)) { mbar_wait<BAR(B_QFULL)>(sb, cs.fpar & 1); mbar_wait<BAR(B_FULL)>(t.cb, t.xc); }
        late = diag_full<true>(S, O, P, pk, l0, l1, a0, a1, unsafe, t, r, cs);
      } else {
#pragma unroll 1
        for (int second = y == 0; second < 2; second++) {
          if (second) {
            t.qd += 32768 >> 4;
            mbar_wait<BAR(B_QFULL)>(sb, cs.fpar & 1);
          }
          if (late) mbar_wait<BAR(B_FULL)>(t.cb, t.xc);
          diag_half(second, S, O, P, l0, l1, a0, a1, unsafe, t, r, cs);
          late = 1;
        }
      }
    } else {
      bar_sync(1 + w, 256);
      mbar_wait<BAR(B_FULL + 2)>(t.cb ^ 8, t.xp);
      if (y != 1 || w) issue_pv<8, 1, 7>(O, P, t.vd); else issue_pv<4, 1, 2>(O, P, t.vd);
      if (w == 0) bar_arrive(2, 256);
      if (t.pub) stage_publish(w, cs);
      unsafe = row_norm(l0, l1, a0, a1);
      mbar_arrive_if<BAR(B_QEMPTY + 1)>(sb, lane == 0 && !unsafe);
      wg_wait<0>();
      fence_regs(O);
      fence_regs(P);
      mbar_arrive_cl<BAR(B_EMPTY + 2)>(cs.rel, t.c8 ^ 8);
    }
    if (head >= w) att_output(O, a0, a1, pk);
    if (UNLIKELY(unsafe)) {
      slow_item(S, a0, a1, ((code >> 4) & 31) * 2 + head, y ^ head, sb + OFF_A + head * 32768, w);
      __syncwarp();
      mbar_arrive_if<BAR(B_QEMPTY)>(sb + head * 8, lane == 0);
      att_output(S, a0, a1, pk);
    }
    if (head) break;
    if (y != 1) {
      if (UNLIKELY(late)) mbar_wait<BAR(B_FULL)>(t.cb, t.xc);
      bar_sync(1 + w, 256);
      issue_qk<false, 10>(S, t.qd, t.kd);
      mbar_wait<BAR(B_STGE)>(sb + w * 8, (cs.round & 1) ^ 1);
      mbar_wait<BAR(B_FULL + 2)>(t.cb ^ 8, t.xp);
      if (w == 0) issue_pv<4, 0, 3>(O, P, t.vd); else issue_pv<8, 0, 6>(O, P, t.vd);
      bar_arrive(1 + (w ^ 1), 256);
      stage_step(1);
      ns = (y ^ 1) - 1;
    } else {
      stage_write(pk, w, cs);
      t.pub = 1;
#pragma unroll
      for (int i = 0; i < 64; i++) O[i] = 0.f;
    }
  }
  cs.p1 = t.xp ^ 1; cs.p0 = t.xc;
  cs.fpar ^= 1;
}

struct Src { const CUtensorMap *ma, *mb; int a0, a1, b0, b1, b2; uint32_t hb; };
__device__ __forceinline__ Src gemm_src(const Params& p, uint32_t code, uint32_t rank, uint32_t h) {
  const int kind = code >> 9, x = (code >> 4) & 31, m = code & 15;
  Src s;
  s.ma = &p.maps[M_AX + kind];
  s.mb = &p.maps[(kind == K_KV && h) ? M_WUV : M_WQKV + kind];
  if (kind == K_QL) { s.a0 = rank * 1024; s.a1 = m * 128; s.b0 = x * 64; s.b1 = h * 32; s.b2 = 0; s.hb = 12288; }
  else { s.a0 = 0; s.a1 = (2 * m + rank) * 128; s.b0 = 0; s.b1 = 0; s.b2 = kind == K_KV ? x * 2 : x * 4 + h * 2; s.hb = 16384; }
  return s;
}
__global__ void __cluster_dims__(2, 1, 1) __launch_bounds__(384, 1) mega_kernel(const __grid_constant__ Params p) {
  extern __shared__ __align__(1024) uint8_t smem_raw[];
  const uint32_t sb = smem_u32(smem_raw), sb0 = sb;
  const uint32_t bid = blockIdx.x, rank = bid & 1;
  const int warp = __shfl_sync(0xffffffffu, threadIdx.x >> 5, 0);
#define BI(b) mbar_init<BAR(b)>(sb, bar_count(b))
  static_assert(B_COUNT == 25, "barrier set-up");
  if (warp == 0) {
    const uint32_t c0 = p.sched[bid >> 1][threadIdx.x & 1];
    if (elect_one()) {
      BI(0); BI(1); BI(2); BI(3);
      asm volatile("fence.mbarrier_init.release.cluster;" ::: "memory");
    }
    __syncwarp();
    const uint32_t code0 = __shfl_sync(0xffffffffu, c0, 0) & 4095;
    const Src u = gemm_src(p, code0, rank, 0), v = gemm_src(p, code0, rank, 1);
#pragma unroll
    for (int s = 0; s < EARLYN; s++) {
      if (elect_one()) {
        const uint32_t bar = sb + BAR(B_FULL) + s * 8;
        mbar_expect_tx<0>(bar, 16384 + 2 * u.hb);
        tma_load_2d(sb + OFF_A + s * 16384, u.ma, u.a0 + s * 64, u.a1, bar);
        tma_load_3d(sb + OFF_B + s * 32768, u.mb, u.b0, u.b1 + s * 64, u.b2, bar);
        tma_load_3d(sb + OFF_B + s * 32768 + u.hb, v.mb, v.b0, v.b1 + s * 64, v.b2, bar);
      }
    }
  }
  if (threadIdx.x == 32 || threadIdx.x == 64 || threadIdx.x == 96) {
    if (threadIdx.x == 32) { BI(4); BI(5); BI(6); BI(7); BI(8); BI(9); BI(21); }
    else if (threadIdx.x == 64) { BI(10); BI(11); BI(12); BI(13); BI(14); BI(15); BI(22); }
    else {
      BI(16); BI(17); BI(18); BI(19); BI(20); BI(23); BI(24);
      asm volatile("st.shared.u32 [%0+%2], %1;\nst.shared.v4.u32 [%0+%3], {%1, %1, %1, %1};" ::"r"(sb), "r"(0), "n"(OFF_FILLS), "n"(OFF_FILLS + 16) : "memory");
      if ((sb & 0xffffffu) != SB) __trap();
    }
    asm volatile("fence.mbarrier_init.release.cluster;" ::: "memory");
  }
#undef BI
  if (warp == 4) {
    const int i = threadIdx.x - 128;
    if (i < MAX_ITEMS / 4) {
      const uint4 v = *reinterpret_cast<const uint4*>(&p.sched[bid >> 1][4 * i]);
      asm volatile("st.shared.v4.u32 [%0+%5], {%1, %2, %3, %4};" ::"r"(sb + i * 16), "r"(v.x), "r"(v.y), "r"(v.z), "r"(v.w), "n"(OFF_LIST) : "memory");
    }
    asm volatile("st.shared.v2.u32 [%0+%2], {%1, %1};" ::"r"(sb + i * 8), "r"(0), "n"(OFF_MASK) : "memory");
  }
  bar_sync(0, 384);
  cluster_arrive_relaxed();
  const int wg = warp >> 2;
  if (wg == 0) {
    reg_dealloc<REG_PROD>();
    cluster_wait();
    const int lane = threadIdx.x & 31;
    auto need = [&](uint32_t& have, int i, int b) {
      if (!((have >> b) & 1)) {
        uint32_t n = 0;
        while (have = __reduce_or_sync(0xffffffffu, lds_acquire<OFF_MASK>(sb + i * 4)), !((have >> b) & 1)) { __nanosleep(32); if (++n > (1u << 22)) __trap(); }
        fence_async_glob();
      }
    };
    if (warp == 0) {
      uint32_t e0 = 1, e1 = 1;
      uint32_t qe = 0, after_att = 0, fills = 0;
      const uint64_t pol_first = policy_evict_first(), pol_normal = POL_NORMAL;
      for (int idx = 0;; idx++) {
        const uint32_t full = item_full(sb, idx), code = full & 4095;
        const int kind = code >> 9, x = (code >> 4) & 31, m = code & 15, y = 2 * m + rank;
        if (kind == K_END) break;
        const uint32_t last = kind >= K_OA ? 0u : full;
        {
          const Src u = gemm_src(p, code, rank, rank);
          const uint64_t pa = (last & 0x1000) ? pol_first : pol_normal, pb = (last & 0x2000) ? pol_first : pol_normal;
          const int nk = kind == K_KV ? 8 : kind == K_OB ? 64 : 16;
          uint32_t have = kind >= K_OA ? 0u : 0xffffffffu;
#pragma unroll 1
          for (int k = idx == 0 ? EARLYN : 0; k < nk; k++) {
            const uint32_t s = k & 3;
            int kk = k;
            if (k >= 64 - 4 * HLATE) { const int j = (k >> 1) - (32 - 2 * HLATE); kk = (32 - 2 * HLATE + (j < HLATE ? 2 * j : 2 * (j - HLATE) + 1)) * 2 + (k & 1); }
            need(have, (kind == K_OA ? F_QL : F_CTX) + y, kind == K_OA ? k : kk >> 1);
            if (after_att && !(k & 1)) {
              mbar_wait_b<BAR(B_QEMPTY)>(sb + k * 4, qe);
              if (k == 2) { after_att = 0; qe ^= 1; }
            }
            fill_gemm(sb + s * 8, (s & 1) ? e1 : e0, 16384 + 2 * u.hb, sb + OFF_B + s * 32768 + rank * u.hb, u.mb, u.b0, u.b1 + kk * 64, u.b2, sb + OFF_A + s * 16384, u.ma, u.a0 + kk * 64, u.a1, pb, pa);
            asm volatile("st.volatile.shared.u32 [%0+%2], %1;" ::"r"(sb), "r"(++fills), "n"(OFF_FILLS) : "memory");
            if (s == 3) { e0 ^= 1; e1 ^= 1; }
          }
        }
        if (kind == K_QF) {
          uint32_t have = 0, xc = e1, xp = e0 ^ 1;
#pragma unroll 1
          for (int j = 0; j < 8 * m + 8; j++) {
            const int i = j >> 1, v = j & 1;
            if (v ? i == 0 : i == 4 * m + 3) continue;
            const int ib = i - v;
            if (i == 2 * m + 1 + rank && !v) have = 0;
            const int h = 2 * x + (ib >= 2 * m + 1 + (int)rank), blk = ib <= 2 * m + 1 ? ib : 4 * m + 2 - ib;
            const int row = h * SEQ + blk * 128;
            if (!v) need(have, F_KV + h, blk);
            const uint32_t b = 2 * v + ((ib + 1) & 1);
            const uint32_t dst = sb + OFF_B + b * 32768;
            const bool own = ib == 2 * m + 1;
            const uint64_t pol = ((last >> (16 + (h & 1) * 8 + (blk >> 1))) & 1) ? pol_first : pol_normal;
            fill_kv(sb + b * 8, v ? xp : xc, dst + rank * 16384, &p.maps[M_KV_LD], (2 * v + rank) * 64, row, own ? 1 + rank : 3, pol);
            if (own) tma_load_2d_h(dst + (rank ^ 1) * 16384, &p.maps[M_KV_LD], (2 * v + (rank ^ 1)) * 64, row, sb + BAR(B_FULL) + b * 8, pol);
            if (v || i == 0) { const uint32_t t = xc; xc = xp ^ 1; xp = t; }
          }
          e0 ^= 1;
          after_att = 1;
        }
      }
    } else if (warp == 2) {
      const uint32_t epoch = g_flags.epoch[bid];
      const uint64_t full = (lane >> 3) == 2 ? ~0ull : 0x0000ffff0000ffffull, flip = 0ull - (epoch & 1);
      uint64_t seen = 0;
      uint32_t tries = 0, hp = 1, hcode;
      int hidx = -1;
      auto next_halo = [&]() { do hcode = item(sb, ++hidx); while ((hcode >> 9) != K_END && ((hcode >> 9) != K_QL || (hcode & 15) == 0)); };
      next_halo();
      while (true) {
        const bool all = __all_sync(0xffffffffu, seen == full);
        if (all && (hcode >> 9) == K_END) break;
        if (!all) {
          uint64_t v;
          asm volatile("ld.acquire.gpu.global.u64 %0, [%1];" : "=l"(v) : "l"(&g_flags.m[2 * lane]) : "memory");
          v = (v ^ flip) & full;
          if (v != seen) { seen = v; asm volatile("st.release.cta.shared::cta.u64 [%0+%2], %1;" ::"r"(sb + lane * 8), "l"(v), "n"(OFF_MASK) : "memory"); }
        }
        if ((hcode >> 9) != K_END) {
          const int x = (hcode >> 4) & 31, m = hcode & 15;
          bool there = __any_sync(0xffffffffu, lane == F_QL / 2 + m - 1 && ((seen >> (32 * rank + x)) & 1));
          if (there && __all_sync(0xffffffffu, mbar_test<BAR(B_HEMPTY)>(sb, hp))) {
            __syncwarp();
            fence_async_glob();
            if (elect_one()) mbar_expect_tx<BAR(B_HFULL)>(sb, 2048);
            bulk_load(sb + OFF_HALO, g_halo + ((2 * m + rank - 2) * 16 + x) * 2048, 2048, sb + BAR(B_HFULL));
            hp ^= 1;
            next_halo();
          }
        }
        __nanosleep(WATCH_NS);
        if (++tries > (1u << 20)) __trap();
      }
      if (lane == 0) g_flags.epoch[bid] = epoch + 1;
    } else if (warp == 3) {
      uint32_t n = 0;
      for (int idx = 0;; idx++) {
        const uint32_t code = item(sb, idx);
        const int kind = code >> 9, x = (code >> 4) & 31, y = 2 * (code & 15) + rank;
        if (kind == K_END) break;
        if (kind > K_KV) continue;
#pragma unroll 1
        for (int r = 0; r <= (kind == K_QF); r++, n++) {
          mbar_wait_long<BAR(B_RELF)>(sb + (n & 1) * 8, (n >> 1) & 1);
          mbar_arrive_if<BAR(B_RELE)>(sb + (n & 1) * 8, lane == 0);
          flag_toggle(&g_flags.m[kind == K_QL ? F_QL + y : kind == K_KV ? F_KV + x : F_CTX + (y ^ r)], 1u << (kind == K_QL ? x : kind == K_KV ? y : 2 * x + r));
        }
      }
    } else {
      {
        uint32_t round = 0, fpar = 0, nrel = 0;
        const uint32_t rb = mapa(sb, rank ^ 1);
        const uint64_t pol_first = policy_evict_first(), pol_normal = POL_NORMAL;
        auto pace = [&]() {
          uint32_t c0, c, t0, t;
          asm volatile("ld.volatile.shared.u32 %0, [%1+%2];" : "=r"(c0) : "r"(sb), "n"(OFF_FILLS) : "memory");
          asm volatile("mov.u32 %0, %clock;" : "=r"(t0));
          do {
            asm volatile("ld.volatile.shared.u32 %0, [%1+%2];" : "=r"(c) : "r"(sb), "n"(OFF_FILLS) : "memory");
            asm volatile("mov.u32 %0, %clock;" : "=r"(t));
          } while (__all_sync(0xffffffffu, c == c0 && t - t0 < PACE_MAX));
        };
        for (int idx = 0;; idx++) {
          const uint32_t code = item(sb, idx);
          const int kind = code >> 9, x = (code >> 4) & 31, m = code & 15, y = 2 * m + rank;
          if (kind == K_END) break;
          const bool last = (item(sb, idx + 1) >> 9) == K_END;
          if (kind == K_QF) {
            if (elect_one()) mbar_expect_tx<BAR(B_QFULL)>(sb, 32768);
            mbar_wait_long<BAR(B_QX)>(sb, fpar);
#pragma unroll 1
            for (int v = 0; v < 2; v++) {
              mbar_wait_b<BAR(B_STGF)>(sb + v * 8, round & 1);
              bulk_send(rb + OFF_A + 32768 + v * 8192, sb + OFF_STG + v * 16384, 8192, rb + BAR(B_QFULL));
              bulk_send(rb + OFF_A + 49152 + v * 8192, sb + OFF_STG + v * 16384 + 8192, 8192, rb + BAR(B_QFULL));
            }
            mbar_wait_b<BAR(B_QFULL)>(sb, fpar);
            mbar_arrive_cl<BAR(B_STGE)>(lane < 2 ? rb : 0, lane * 8);
            round++; fpar ^= 1;
          }
          const CUtensorMap* mc = &p.maps[M_OA_ST + kind];
          const uint64_t pol = (kind >= K_OA || kind == K_QF) ? pol_first : pol_normal;
          int row = kind == K_KV ? x * SEQ + y * 128 : kind == K_OA ? m * 128 : y * 128;
          int cg = kind == K_QL ? x : kind == K_QF ? x * 4 : kind == K_KV ? 0 : kind == K_OA ? rank * 32 + x * 4 : 16 + x * 4;
          const int nr = kind == K_QL ? 1 : 2;
#pragma unroll 1
          for (int r = 0; r < nr; r++) {
            mbar_wait_long<BAR(B_STGF)>(sb, round & 1);
            if (last && kind >= K_KV) {
              tma_store_3d(mc, sb + OFF_STG, 0, row, cg, pol);
              mbar_wait_b<BAR(B_FIN)>(sb, 0);
              tma_store_3d(mc, sb + OFF_B, 0, row, cg + 2, pol);
              mbar_wait_b<BAR(B_STGF + 1)>(sb, round & 1);
              tma_store_3d(mc, sb + OFF_STG + 16384, 0, row + 64, cg, pol);
              mbar_wait_b<BAR(B_FIN + 1)>(sb, 0);
              tma_store_3d(mc, sb + OFF_B + 16384, 0, row + 64, cg + 2, pol);
              bulk_commit();
              r = 1;
            } else {
              const bool paced = !last && (kind >= K_KV || r == 1);
              if (paced) pace();
              tma_store_3d(mc, sb + OFF_STG, 0, row, cg, pol);
              bulk_commit();
              mbar_wait_b<BAR(B_STGF + 1)>(sb, round & 1);
              if (paced) pace();
              tma_store_3d(mc, sb + OFF_STG + 16384, 0, row + 64, cg, pol);
              if (kind == K_QL) bulk_store(g_halo + (y * 16 + x) * 2048, sb + OFF_STG + 16384 + 8192 + 3 * 2048, 2048);
              bulk_commit();
              bulk_wait_read<1>();
              mbar_arrive_if<BAR(B_STGE)>(sb, lane == 0);
              bulk_wait_read<0>();
              mbar_arrive_if<BAR(B_STGE + 1)>(sb, lane == 0);
              round++;
            }
            if (kind == K_QF || (kind <= K_KV && r == nr - 1)) {
              bulk_wait_all();
              mbar_wait_b<BAR(B_RELE)>(sb + (nrel & 1) * 8, ((nrel >> 1) & 1) ^ 1);
              __syncwarp();
              mbar_arrive_if<BAR(B_RELF)>(sb + (nrel & 1) * 8, lane == 0);
              nrel++;
            }
            cg += 2;
            if (kind == K_QF) row ^= 128;
          }
        }
        bulk_wait_all();
      }
      cluster_arrive_relaxed();
      cluster_wait();
    }
  } else {
    reg_alloc<REG_CONS>();
    cluster_wait();
    const int w = wg - 1;
    Cons cs;
    cs.sb = __reduce_or_sync(0xffffffffu, sb0);
    const uint32_t sb = cs.sb;
    cs.d0 = (sb & 0x3ffff) >> 4;
    cs.da = cs.d0 + w * 512;
    cs.rel = (threadIdx.x & 127) == 0 ? sb : (threadIdx.x & 127) == 1 ? mapa(sb, rank ^ 1) : 0;
    cs.p0 = cs.p1 = cs.lead = cs.round = cs.fpar = 0;
    uint32_t pkA[32], pkB[32], pend = 0;
#pragma unroll
    for (int i = 0; i < 32; i++) pkA[i] = pkB[i] = 0;
    uint32_t code = item(sb, 0);
    int idx = 0;
    do {
      const int kind = code >> 9;
      uint32_t ncode;
      if (kind == K_QL) {
        float acc[96];
        Loc l;
        ncode = gemm_tile(acc, 4, idx, w, cs, pend, pkA, pkB, [&] { l = local_prepare(code, w, cs); });
        local_epilogue(acc, code, w, cs, l);
        pend = 24;
        if (w == 1 && (ncode >> 9) != K_END) bar_arrive(5, 256);
        if ((ncode >> 9) >= K_OA) { stage_publish(w, cs); pend = 16; }
      } else {
        float acc[128];
        ncode = gemm_tile(acc, kind == K_KV ? 2 : kind == K_OB ? 16 : 4, idx, w, cs, pend, pkA, pkB, [] {});
        if (kind == K_QF) {
          mbar_arrive_cl<BAR(B_QX)>((threadIdx.x & 1) ? cs.rel : 0);
          tile_pack_write<OFF_A, 16384, 0>(acc, pkB, sb + w * 8192);
#pragma unroll
          for (int i = 0; i < 32; i++) pkA[i] = v_pack(acc[64 + 2 * i], acc[64 + 2 * i + 1]);
          mbar_wait<BAR(B_STGE)>(sb + w * 8, (cs.round & 1) ^ 1);
          if ((code & 15) == 0) { tile_write<OFF_STG, 8192>(pkA, sb + w * 16384); stage_publish(w, cs); }
          mbar_wait<BAR(B_FULL + 1)>(sb, cs.p1);
          fence_async_smem();
          attention(code, rank, idx, w, cs, pkB, pkA);
          pend = 1;
        } else {
          if (kind == K_KV) {
#pragma unroll
            for (int i = 0; i < 64; i++) acc[i] *= SCALE_LOG2;
          }
#pragma unroll
          for (int i = 0; i < 32; i++) pkA[i] = pack_bf16(acc[2 * i], acc[2 * i + 1]);
#pragma unroll
          for (int i = 0; i < 32; i++) pkB[i] = pack_bf16(acc[64 + 2 * i], acc[64 + 2 * i + 1]);
          pend = 3;
        }
      }
      code = ncode;
      idx++;
    } while ((code >> 9) != K_END);
    if (pend & 1) { stage_write(pkA, w, cs); stage_publish(w, cs); }
    if (pend & 2) {
      mbar_wait<BAR(B_EMPTY)>(sb, cs.p0 ^ 1);
      tile_write<OFF_B, 8192>(pkB, sb + w * 16384);
      fence_async_smem();
      __syncwarp();
      mbar_arrive_if<BAR(B_FIN)>(sb + w * 8, (threadIdx.x & 31) == 0);
    }
    cluster_arrive();
  }
}

typedef CUresult (*EncodeFn)(CUtensorMap*, CUtensorMapDataType, cuuint32_t, void*, const cuuint64_t*, const cuuint64_t*, const cuuint32_t*,
                             const cuuint32_t*, CUtensorMapInterleave, CUtensorMapSwizzle, CUtensorMapL2promotion, CUtensorMapFloatOOBfill);

void make_map_2d(EncodeFn enc, CUtensorMap* tm, const void* ptr, uint64_t cols, uint64_t rows) {
  cuuint64_t dims[2] = {cols, rows};
  cuuint64_t str[1] = {cols * 2};
  cuuint32_t box[2] = {64, 128};
  cuuint32_t es[2] = {1, 1};
  enc(tm, CU_TENSOR_MAP_DATA_TYPE_BFLOAT16, 2, const_cast<void*>(ptr), dims, str, box, es, CU_TENSOR_MAP_INTERLEAVE_NONE, CU_TENSOR_MAP_SWIZZLE_128B,
      CU_TENSOR_MAP_L2_PROMOTION_L2_256B, CU_TENSOR_MAP_FLOAT_OOB_FILL_NONE);
}
void make_map_3d(EncodeFn enc, CUtensorMap* tm, const void* ptr, uint64_t cols, uint64_t rows, uint64_t part, uint32_t br, uint32_t bg) {
  cuuint64_t dims[3] = {part, rows, cols / part};
  cuuint64_t str[2] = {cols * 2, part * 2};
  cuuint32_t box[3] = {64, br, bg};
  cuuint32_t es[3] = {1, 1, 1};
  enc(tm, CU_TENSOR_MAP_DATA_TYPE_BFLOAT16, 3, const_cast<void*>(ptr), dims, str, box, es, CU_TENSOR_MAP_INTERLEAVE_NONE, CU_TENSOR_MAP_SWIZZLE_128B,
      CU_TENSOR_MAP_L2_PROMOTION_L2_256B, CU_TENSOR_MAP_FLOAT_OOB_FILL_NONE);
}

static const uint32_t h_sched[NPAIR][MAX_ITEMS] = {
  {0x420,0x200,0xf3,0x4c3,0x76,0x521,0x523,0x533,0x290,0x5b0,0x5f3,0x835,0xe00,0xe00,0xe00,0xe00,0xe00,0xe00,0xe00,0xe00},
  {0x497,0x231,0x2496,0x75,0x4e5,0x40252,0x2b0,0x825,0xe00,0xe00,0xe00,0xe00,0xe00,0xe00,0xe00,0xe00,0xe00,0xe00,0xe00,0xe00},
  {0x437,0x413,0x492,0x465,0x83,0x4c2,0x6,0x4f5,0x293,0x5d5,0x815,0xe00,0xe00,0xe00,0xe00,0xe00,0xe00,0xe00,0xe00,0xe00},
  {0x400,0x220,0xb3,0x15,0x4b2,0x505,0x12260,0x5c2,0x5a3,0x5c5,0x5d2,0x805,0xe00,0xe00,0xe00,0xe00,0xe00,0xe00,0xe00,0xe00},
  {0x424,0x233,0xf5,0x4d5,0x511,0x530,0x552,0x808002e7,0x614,0xe00,0xe00,0xe00,0xe00,0xe00,0xe00,0xe00,0xe00,0xe00,0xe00,0xe00},
  {0x410,0x462,0x12,0x2467,0x256,0x4002f6,0x603,0xe00,0xe00,0xe00,0xe00,0xe00,0xe00,0xe00,0xe00,0xe00,0xe00,0xe00,0xe00,0xe00},
  {0xd0,0x235,0x2a4,0x830,0xe00,0xe00,0xe00,0xe00,0xe00,0xe00,0xe00,0xe00,0xe00,0xe00,0xe00,0xe00,0xe00,0xe00,0xe00,0xe00},
  {0x443,0x403,0xe2,0x73,0x65,0x96,0x4f1,0x2a5,0x402d2,0x611,0xe00,0xe00,0xe00,0xe00,0xe00,0xe00,0xe00,0xe00,0xe00,0xe00},
  {0x10,0x91,0x13,0xf4,0x4c4,0x250,0x527,0x402a2,0x834,0xe00,0xe00,0xe00,0xe00,0xe00,0xe00,0xe00,0xe00,0xe00,0xe00,0xe00},
  {0x421,0x215,0x295,0x812f3,0x627,0xe00,0xe00,0xe00,0xe00,0xe00,0xe00,0xe00,0xe00,0xe00,0xe00,0xe00,0xe00,0xe00,0xe00,0xe00},
  {0x476,0xff800207,0x545,0x4002c6,0x2087,0x610,0xe00,0xe00,0xe00,0xe00,0xe00,0xe00,0xe00,0xe00,0xe00,0xe00,0xe00,0xe00,0xe00,0xe00},
  {0x454,0x11,0xa2,0x54,0x4e1,0x4c6,0x4d0,0x4f2,0xfff002a7,0x2017,0x20e7,0xe00,0xe00,0xe00,0xe00,0xe00,0xe00,0xe00,0xe00,0xe00},
  {0x481,0x213,0xe5,0x4f4,0x524,0x535,0x2546,0x570,0x5c4,0x2002e5,0x634,0xe00,0xe00,0xe00,0xe00,0xe00,0xe00,0xe00,0xe00,0xe00},
  {0x450,0x412,0x52,0x4a0,0x254,0x585,0x5e2,0x574,0x25e7,0x1002f4,0x623,0xe00,0xe00,0xe00,0xe00,0xe00,0xe00,0xe00,0xe00,0xe00},
  {0xf0,0x234,0x200285,0x800,0xe00,0xe00,0xe00,0xe00,0xe00,0xe00,0xe00,0xe00,0xe00,0xe00,0xe00,0xe00,0xe00,0xe00,0xe00,0xe00},
  {0x423,0x433,0x22,0xc3,0x4c1,0xb5,0xe6,0x561,0x583,0x2b3,0x5d0,0x202f1,0x626,0xe00,0xe00,0xe00,0xe00,0xe00,0xe00,0xe00},
  {0x60,0x41,0xe3,0xe4,0x26,0x503,0x24f7,0x532,0x5c0,0x5c1,0x2567,0x5a6,0x5d7,0x824,0xe00,0xe00,0xe00,0xe00,0xe00,0xe00},
  {0x425,0x214,0x504,0x4f6,0x560,0x808002c7,0x20d7,0x616,0xe00,0xe00,0xe00,0xe00,0xe00,0xe00,0xe00,0xe00,0xe00,0xe00,0xe00,0xe00},
  {0x416,0x206,0x510,0x534,0x6002b6,0x20b7,0x630,0xe00,0xe00,0xe00,0xe00,0xe00,0xe00,0xe00,0xe00,0xe00,0xe00,0xe00,0xe00,0xe00},
  {0x436,0x51,0xb2,0x34,0x4a5,0x4b6,0xffc00287,0x15f1,0x35f0,0x2027,0x20f7,0xe00,0xe00,0xe00,0xe00,0xe00,0xe00,0xe00,0xe00,0xe00},
  {0x473,0x203,0x85,0x522,0x514,0x531,0x556,0x808002f7,0x607,0xe00,0xe00,0xe00,0xe00,0xe00,0xe00,0xe00,0xe00,0xe00,0xe00,0xe00},
  {0x460,0x432,0x405,0x33,0x255,0x565,0x5e4,0x25a7,0x1002e4,0x617,0xe00,0xe00,0xe00,0xe00,0xe00,0xe00,0xe00,0xe00,0xe00,0xe00},
  {0x70,0xff800237,0x555,0x322a1,0x810,0xe00,0xe00,0xe00,0xe00,0xe00,0xe00,0xe00,0xe00,0xe00,0xe00,0xe00,0xe00,0xe00,0xe00,0xe00},
  {0x417,0x435,0x62,0x93,0x55,0xa6,0x541,0x2a6,0x202e1,0x615,0xe00,0xe00,0xe00,0xe00,0xe00,0xe00,0xe00,0xe00,0xe00,0xe00},
  {0x40,0x71,0x53,0x44,0x56,0x4f3,0x24d7,0x582,0x550,0x2551,0x2587,0x2576,0x5f5,0x804,0xe00,0xe00,0xe00,0xe00,0xe00,0xe00},
  {0x440,0xff800217,0x808002b7,0x20c7,0x606,0xe00,0xe00,0xe00,0xe00,0xe00,0xe00,0xe00,0xe00,0xe00,0xe00,0xe00,0xe00,0xe00,0xe00,0xe00},
  {0x446,0xff800227,0x554,0x584,0x586,0x1f22b4,0x20a7,0x600,0xe00,0xe00,0xe00,0xe00,0xe00,0xe00,0xe00,0xe00,0xe00,0xe00,0xe00,0xe00},
  {0x466,0xe1,0x240,0x4e0,0x36,0x4e7,0x513,0x525,0x547,0x5a2,0x4002d6,0x613,0xe00,0xe00,0xe00,0xe00,0xe00,0xe00,0xe00,0xe00},
  {0x480,0x402,0x464,0x2406,0xa3,0x266,0x2002f5,0x601,0xe00,0xe00,0xe00,0xe00,0xe00,0xe00,0xe00,0xe00,0xe00,0xe00,0xe00,0xe00},
  {0x470,0x414,0x12230,0x486,0x4b5,0x80253,0x2c1,0x802e3,0x631,0xe00,0xe00,0xe00,0xe00,0xe00,0xe00,0xe00,0xe00,0xe00,0xe00,0xe00},
  {0x0,0x236,0x20281,0x596,0x5b1,0x820,0xe00,0xe00,0xe00,0xe00,0xe00,0xe00,0xe00,0xe00,0xe00,0xe00,0xe00,0xe00,0xe00,0xe00},
  {0x453,0x415,0x32,0xd3,0x25,0x4c5,0x4d6,0x32251,0x2002c5,0x2077,0x625,0xe00,0xe00,0xe00,0xe00,0xe00,0xe00,0xe00,0xe00,0xe00},
  {0x422,0x204,0xb6,0x20271,0x5e3,0x5c6,0x5b5,0x814,0xe00,0xe00,0xe00,0xe00,0xe00,0xe00,0xe00,0xe00,0xe00,0xe00,0xe00,0xe00},
  {0x434,0x216,0x12270,0x2b2,0x402f2,0x636,0xe00,0xe00,0xe00,0xe00,0xe00,0xe00,0xe00,0xe00,0xe00,0xe00,0xe00,0xe00,0xe00,0xe00},
  {0x456,0x226,0x580,0x536,0x564,0x566,0x1f22c4,0x2097,0x620,0xe00,0xe00,0xe00,0xe00,0xe00,0xe00,0xe00,0xe00,0xe00,0xe00,0xe00},
  {0x474,0x81,0x92,0x14,0x4b4,0x4e3,0x520,0x506,0x2515,0x553,0x557,0x5c3,0x2002d5,0x633,0xe00,0xe00,0xe00,0xe00,0xe00,0xe00},
  {0x90,0x493,0xff800247,0x2b1,0x807,0xe00,0xe00,0xe00,0xe00,0xe00,0xe00,0xe00,0xe00,0xe00,0xe00,0xe00,0xe00,0xe00,0xe00,0xe00},
  {0x447,0x21,0xf2,0x485,0x4a3,0x66,0xf6,0x517,0x563,0x5e0,0x590,0x577,0x2d0,0x25d1,0x2037,0x2047,0x602,0xe00,0xe00,0xe00},
  {0x411,0x243,0xc6,0x284,0x5b4,0x836,0xe00,0xe00,0xe00,0xe00,0xe00,0xe00,0xe00,0xe00,0xe00,0xe00,0xe00,0xe00,0xe00,0xe00},
  {0x427,0x211,0x74,0xff800277,0x801,0xe00,0xe00,0xe00,0xe00,0xe00,0xe00,0xe00,0xe00,0xe00,0xe00,0xe00,0xe00,0xe00,0xe00,0xe00},
  {0x461,0x222,0xd5,0x4b1,0x4d4,0x543,0x802a3,0x812,0xe00,0xe00,0xe00,0xe00,0xe00,0xe00,0xe00,0xe00,0xe00,0xe00,0xe00,0xe00},
  {0x30,0xa1,0x23,0x4c0,0x4a6,0x4b0,0x4d2,0xffe00297,0x2007,0x2057,0x621,0xe00,0xe00,0xe00,0xe00,0xe00,0xe00,0xe00,0xe00,0xe00},
  {0x442,0x1,0x72,0x4a2,0x4c7,0x24a7,0x100274,0x5a5,0x5b6,0x823,0xe00,0xe00,0xe00,0xe00,0xe00,0xe00,0xe00,0xe00,0xe00,0xe00},
  {0xe0,0x490,0x407,0x494,0x495,0x4a4,0x501,0x502,0x20261,0x573,0x4002e6,0x624,0xe00,0xe00,0xe00,0xe00,0xe00,0xe00,0xe00,0xe00},
  {0x445,0x31,0x42,0x4,0x95,0x4e4,0x540,0x2507,0x2526,0x5a1,0x591,0x597,0x2d3,0x2067,0x612,0xe00,0xe00,0xe00,0xe00,0xe00},
  {0x471,0x61,0x244,0x100294,0x826,0xe00,0xe00,0xe00,0xe00,0xe00,0xe00,0xe00,0xe00,0xe00,0xe00,0xe00,0xe00,0xe00,0xe00,0xe00},
  {0x401,0x201,0x94,0x275,0x593,0x5f2,0x811,0xe00,0xe00,0xe00,0xe00,0xe00,0xe00,0xe00,0xe00,0xe00,0xe00,0xe00,0xe00,0xe00},
  {0x431,0x202,0xc5,0x380265,0x5f7,0x832,0xe00,0xe00,0xe00,0xe00,0xe00,0xe00,0xe00,0xe00,0xe00,0xe00,0xe00,0xe00,0xe00,0xe00},
  {0x80,0xb1,0x63,0xb4,0x500,0x4d3,0x40272,0x2c0,0x817,0xe00,0xe00,0xe00,0xe00,0xe00,0xe00,0xe00,0xe00,0xe00,0xe00,0xe00},
  {0x430,0x482,0x2,0x43,0xfff00257,0x5d4,0x803,0xe00,0xe00,0xe00,0xe00,0xe00,0xe00,0xe00,0xe00,0xe00,0xe00,0xe00,0xe00,0xe00},
  {0xa0,0x463,0x246,0x2b5,0x122f0,0x605,0xe00,0xe00,0xe00,0xe00,0xe00,0xe00,0xe00,0xe00,0xe00,0xe00,0xe00,0xe00,0xe00,0xe00},
  {0x475,0xf1,0x82,0x24,0x45,0x80273,0x2c3,0x122e0,0x632,0xe00,0xe00,0xe00,0xe00,0xe00,0xe00,0xe00,0xe00,0xe00,0xe00,0xe00},
  {0x444,0x223,0xd6,0x4d1,0x516,0x562,0x32291,0x5f4,0x806,0xe00,0xe00,0xe00,0xe00,0xe00,0xe00,0xe00,0xe00,0xe00,0xe00,0xe00},
  {0x491,0x241,0xd4,0x276,0x5b2,0x831,0xe00,0xe00,0xe00,0xe00,0xe00,0xe00,0xe00,0xe00,0xe00,0xe00,0xe00,0xe00,0xe00,0xe00},
  {0x451,0x212,0x35,0x286,0x822,0xe00,0xe00,0xe00,0xe00,0xe00,0xe00,0xe00,0xe00,0xe00,0xe00,0xe00,0xe00,0xe00,0xe00,0xe00},
  {0x50,0xd1,0x3,0xa4,0x16,0x4e6,0x512,0x544,0x2537,0x5e1,0x5a4,0x595,0x5d3,0x837,0xe00,0xe00,0xe00,0xe00,0xe00,0xe00},
  {0x472,0xc1,0xc2,0x4a1,0x2487,0x4b3,0x264,0x5e5,0x5d6,0x833,0xe00,0xe00,0xe00,0xe00,0xe00,0xe00,0xe00,0xe00,0xe00,0xe00},
  {0xb0,0x483,0x245,0x280,0x575,0x5c7,0x1802d4,0x635,0xe00,0xe00,0xe00,0xe00,0xe00,0xe00,0xe00,0xe00,0xe00,0xe00,0xe00,0xe00},
  {0x20,0x404,0xd2,0x64,0xa5,0x40262,0xe08002d7,0x622,0xe00,0xe00,0xe00,0xe00,0xe00,0xe00,0xe00,0xe00,0xe00,0xe00,0xe00,0xe00},
  {0x477,0x224,0x86,0x542,0x40292,0x2594,0x816,0xe00,0xe00,0xe00,0xe00,0xe00,0xe00,0xe00,0xe00,0xe00,0xe00,0xe00,0xe00,0xe00},
  {0x457,0x221,0xc4,0xffc00267,0x821,0xe00,0xe00,0xe00,0xe00,0xe00,0xe00,0xe00,0xe00,0xe00,0xe00,0xe00,0xe00,0xe00,0xe00,0xe00},
  {0x441,0x232,0x5,0x4b7,0x283,0x5e6,0x5b7,0x802,0xe00,0xe00,0xe00,0xe00,0xe00,0xe00,0xe00,0xe00,0xe00,0xe00,0xe00,0xe00},
  {0x426,0x210,0x484,0x84,0x263,0x2a0,0x5b3,0x827,0xe00,0xe00,0xe00,0xe00,0xe00,0xe00,0xe00,0xe00,0xe00,0xe00,0xe00,0xe00},
  {0xc0,0x242,0x4e2,0x46,0x4f0,0x581,0x5a0,0x571,0x572,0x592,0x5f6,0x813,0xe00,0xe00,0xe00,0xe00,0xe00,0xe00,0xe00,0xe00},
  {0x452,0x205,0x296,0x412e2,0x637,0xe00,0xe00,0xe00,0xe00,0xe00,0xe00,0xe00,0xe00,0xe00,0xe00,0xe00,0xe00,0xe00,0xe00,0xe00},
  {0x455,0x225,0x40282,0x2c2,0x322d1,0x604,0xe00,0xe00,0xe00,0xe00,0xe00,0xe00,0xe00,0xe00,0xe00,0xe00,0xe00,0xe00,0xe00,0xe00},
};

struct HostState { bool init; Params p; void* out; const void* in[9]; };
HostState g_hs;

void build_state(void* const* d_in, void* d_out) {
  void* fn = nullptr;
  cudaDriverEntryPointQueryResult qr;
  cudaGetDriverEntryPoint("cuTensorMapEncodeTiled", &fn, cudaEnableDefault, &qr);
  EncodeFn enc = (EncodeFn)fn;
  void *kv, *ctx, *oA;
  cudaGetSymbolAddress(&kv, g_kv);
  cudaGetSymbolAddress(&ctx, g_ctx);
  cudaGetSymbolAddress(&oA, g_oA);
  Params& p = g_hs.p;
  make_map_2d(enc, &p.maps[M_AX], d_in[0], 2048, SEQ / 2);
  make_map_2d(enc, &p.maps[M_BX], d_in[3], 1024, SEQ);
  make_map_2d(enc, &p.maps[M_CKV], d_in[4], 512, SEQ);
  make_map_2d(enc, &p.maps[M_OA], oA, 1024, SEQ);
  make_map_2d(enc, &p.maps[M_CTX], ctx, 4096, SEQ);
  make_map_3d(enc, &p.maps[M_WQKV], d_in[1], 3072, 1024, 1024, 32, 3);
  make_map_3d(enc, &p.maps[M_WQ], d_in[5], 4096, 1024, 64, 64, 2);
  make_map_3d(enc, &p.maps[M_WUK], d_in[6], 4096, 512, 64, 64, 2);
  make_map_3d(enc, &p.maps[M_WUV], d_in[7], 4096, 512, 64, 64, 2);
  make_map_3d(enc, &p.maps[M_WOA], d_in[2], 1024, 1024, 64, 64, 2);
  make_map_3d(enc, &p.maps[M_WOB], d_in[8], 1024, 4096, 64, 64, 2);
  make_map_2d(enc, &p.maps[M_KV_LD], kv, 256, 32 * SEQ);
  make_map_3d(enc, &p.maps[M_OA_ST], oA, 1024, SEQ, 64, 64, 1);
  make_map_3d(enc, &p.maps[M_CTX_ST], ctx, 4096, SEQ, 64, 64, 2);
  make_map_3d(enc, &p.maps[M_KV_ST], kv, 256, 32 * SEQ, 64, 64, 2);
  make_map_3d(enc, &p.maps[M_OUTA_ST], d_out, 4096, SEQ / 2, 64, 64, 2);
  make_map_3d(enc, &p.maps[M_OUTB_ST], d_out, 2048, SEQ, 64, 64, 2);
  for (int c = 0; c < NPAIR; c++)
    for (int i = 0; i < MAX_ITEMS; i++) p.sched[c][i] = h_sched[c][i];
  cudaFuncSetAttribute(mega_kernel, cudaFuncAttributeMaxDynamicSharedMemorySize, SMEM_BYTES);
}

}

extern "C" void kernel_launch(void* const* d_in, const int* in_sizes, int n_in, void* d_out, int out_size) {
  (void)in_sizes; (void)n_in; (void)out_size;
  bool same = g_hs.init && g_hs.out == d_out;
  for (int i = 0; i < 9 && same; i++) same = (g_hs.in[i] == d_in[i]);
  if (!same) {
    build_state(d_in, d_out);
    g_hs.init = true; g_hs.out = d_out;
    for (int i = 0; i < 9; i++) g_hs.in[i] = d_in[i];
  }
  mega_kernel<<<NCTA, 384, SMEM_BYTES, cudaStreamPerThread>>>(g_hs.p);
}
```

```cpp
#include <cuda_runtime.h>
#include <cuda_bf16.h>
#include <cuda.h>
#include <stdint.h>

namespace {

constexpr int SEQ = 2048;
constexpr int NCTA = 132, NPAIR = 66;
constexpr int MAX_ITEMS = 20;

__device__ __align__(1024) __nv_bfloat16 g_kv[32 * SEQ * 256];
__device__ __align__(1024) __nv_bfloat16 g_ctx[SEQ * 4096];
__device__ __align__(1024) __nv_bfloat16 g_oA[SEQ * 1024];
__device__ __align__(1024) uint8_t g_halo[16 * 16 * 2048];
struct Flags { uint32_t m[64]; uint32_t epoch[NCTA]; };
__device__ __align__(128) Flags g_flags;
enum { F_KV = 0, F_CTX = 32, F_QL = 48 };

enum { K_QL = 0, K_QF = 1, K_KV = 2, K_OA = 3, K_OB = 4, K_END = 7 };
enum { M_AX = 0, M_BX, M_CKV, M_OA, M_CTX, M_WQKV, M_WQ, M_WUK, M_WOA, M_WOB, M_WUV, M_KV_LD, M_OA_ST, M_CTX_ST, M_KV_ST, M_OUTA_ST, M_OUTB_ST, M_COUNT };

struct Params {
  CUtensorMap maps[M_COUNT];
  alignas(16) uint32_t sched[NPAIR][MAX_ITEMS];
};


constexpr uint32_t SB = 1024;
constexpr uint32_t OFF_A = 0;
constexpr uint32_t OFF_B = 65536;
constexpr uint32_t OFF_STG = 196608;
constexpr uint32_t OFF_HALO = 229376;
constexpr uint32_t OFF_BAR = 231424;
constexpr uint32_t OFF_MASK = OFF_BAR + 256;
constexpr uint32_t OFF_LIST = OFF_BAR + 512;
constexpr uint32_t OFF_FILLS = OFF_BAR + 608;
constexpr uint32_t SMEM_BYTES = OFF_BAR + 640;
enum { B_FULL = 0, B_EMPTY = 4, B_QEMPTY = 8, B_STGE = 10, B_STGF = 12, B_FIN = 14, B_QFULL = 16, B_QX = 17, B_LEAD = 18, B_HFULL = 19, B_HEMPTY = 20, B_RELF = 21, B_RELE = 23, B_COUNT = 25 };
__host__ __device__ constexpr uint32_t BAR(int b) { return OFF_BAR + b * 8; }
__host__ __device__ constexpr int bar_count(int b) { return b < B_EMPTY ? 1 : b < B_QEMPTY ? 4 : b < B_STGE ? 8 : b < B_STGF ? 1 : b < B_QFULL ? 4 : b == B_QX ? 2 : 1; }
constexpr int REG_CONS = 232, REG_PROD = 40;
constexpr int PACE_MAX = 1100;
constexpr int WATCH_NS = 250;
constexpr int EARLYN = 3;
constexpr int HLATE = 3;
constexpr int STGA = 3, STGB = 8, STGAL = 4, STGBL = 12;
constexpr int JSPLIT = 14, JEDGE = 14, JP = 14, JDIAG = 10, JDIAG2 = 8;

__device__ __forceinline__ uint32_t smem_u32(const void* p) { return (uint32_t)__cvta_generic_to_shared(p); }
__device__ __forceinline__ void wg_fence() { asm volatile("wgmma.fence.sync.aligned;" ::: "memory"); }
__device__ __forceinline__ void wg_commit() { asm volatile("wgmma.commit_group.sync.aligned;" ::: "memory"); }
template <int N> __device__ __forceinline__ void wg_wait() { asm volatile("wgmma.wait_group.sync.aligned %0;" ::"n"(N) : "memory"); }
__device__ __forceinline__ uint64_t desc(uint32_t lo) { uint64_t d; asm volatile("mov.b64 %0, {%1, 0x40000040};" : "=l"(d) : "r"(lo)); return d; }
__host__ __device__ constexpr uint32_t dlo(uint32_t off, uint32_t lbo) { return (off >> 4) | ((lbo >> 4) << 16); }
template <uint32_t O> __device__ __forceinline__ void mbar_init(uint32_t a, uint32_t cnt) { asm volatile("mbarrier.init.shared::cta.b64 [%0+%2], %1;" ::"r"(a), "r"(cnt), "n"(O) : "memory"); }
template <uint32_t O> __device__ __forceinline__ void mbar_expect_tx(uint32_t a, uint32_t bytes) { asm volatile("mbarrier.arrive.expect_tx.shared::cta.b64 _, [%0+%2], %1;" ::"r"(a), "r"(bytes), "n"(O) : "memory"); }
template <uint32_t O> __device__ __forceinline__ void mbar_arrive_if(uint32_t a, bool pred) {
  asm volatile("{\n.reg .pred p;\nsetp.ne.u32 p, %1, 0;\n@p mbarrier.arrive.shared::cta.b64 _, [%0+%2];\n}\n" ::"r"(a), "r"((uint32_t)pred), "n"(O) : "memory");
}
template <uint32_t O> __device__ __forceinline__ void mbar_arrive_cl(uint32_t a, uint32_t off = 0) {
  asm volatile("{\n.reg .pred p;\nsetp.ne.u32 p, %2, 0;\n@p mbarrier.arrive.shared::cluster.b64 _, [%0+%1];\n}\n" ::"r"(a + off), "n"(O), "r"(a) : "memory");
}
template <uint32_t O> __device__ __forceinline__ bool mbar_test(uint32_t a, uint32_t parity) {
  uint32_t ok;
  asm volatile("{\n.reg .pred p;\nmbarrier.test_wait.parity.shared::cta.b64 p, [%1+%3], %2;\nselp.u32 %0, 1, 0, p;\n}\n" : "=r"(ok) : "r"(a), "r"(parity), "n"(O) : "memory");
  return ok;
}
template <uint32_t O> __device__ __forceinline__ void mbar_wait(uint32_t a, uint32_t parity) {
  asm volatile("{\n.reg .pred p;\nWAIT_%=:\nmbarrier.try_wait.parity.shared::cta.b64 p, [%0+%2], %1;\n@!p bra WAIT_%=;\n}\n" ::"r"(a), "r"(parity), "n"(O) : "memory");
}
template <uint32_t O> __device__ __forceinline__ void mbar_wait_b(uint32_t a, uint32_t parity) {
  asm volatile("{\n.reg .pred p, q;\n.reg .u32 n;\nmov.u32 n, 0;\nWAIT_%=:\nadd.u32 n, n, 1;\nmbarrier.try_wait.parity.shared::cta.b64 p, [%0+%2], %1;\n"
               "setp.lt.u32 q, n, 4194304;\nand.pred q, q, !p;\n@q bra WAIT_%=;\n@!p st.shared.u32 [%0+1], n;\n}\n" ::"r"(a), "r"(parity), "n"(O) : "memory");
}
template <uint32_t O> __device__ __forceinline__ void mbar_wait_long(uint32_t a, uint32_t parity) {
  asm volatile("{\n.reg .pred p, q;\n.reg .u32 n;\nmov.u32 n, 0;\nWAIT_%=:\nadd.u32 n, n, 1;\nmbarrier.try_wait.parity.shared::cta.b64 p, [%0+%2], %1, 4000;\n"
               "setp.lt.u32 q, n, 524288;\nand.pred q, q, !p;\n@q bra WAIT_%=;\n@!p st.shared.u32 [%0+1], n;\n}\n" ::"r"(a), "r"(parity), "n"(O) : "memory");
}
__device__ __forceinline__ void tma_load_2d(uint32_t dst, const CUtensorMap* tm, int c0, int c1, uint32_t bar) {
  asm volatile("cp.async.bulk.tensor.2d.shared::cluster.global.mbarrier::complete_tx::bytes [%0], [%1, {%3, %4}], [%2];" ::"r"(dst), "l"(tm), "r"(bar), "r"(c0), "r"(c1) : "memory");
}
__device__ __forceinline__ void tma_load_3d(uint32_t dst, const CUtensorMap* tm, int c0, int c1, int c2, uint32_t bar) {
  asm volatile("cp.async.bulk.tensor.3d.shared::cluster.global.mbarrier::complete_tx::bytes [%0], [%1, {%3, %4, %5}], [%2];" ::"r"(dst), "l"(tm), "r"(bar), "r"(c0), "r"(c1), "r"(c2) : "memory");
}
#define FILL_HEAD "{\n.reg .pred p, q;\n.reg .u32 n;\nmov.u32 n, 0;\nWAIT_%=:\nadd.u32 n, n, 1;\nmbarrier.try_wait.parity.shared::cta.b64 p, [%0+%1], %3;\n" \
                  "setp.lt.u32 q, n, 4194304;\nand.pred q, q, !p;\n@q bra WAIT_%=;\n@!p st.shared.u32 [%0+1], n;\nelect.sync _|p, 0xffffffff;\n" \
                  "@p mbarrier.arrive.expect_tx.shared::cta.b64 _, [%2], %4;\n"
__device__ __forceinline__ void fill_gemm(uint32_t bb, uint32_t parity, uint32_t bytes, uint32_t dstb, const CUtensorMap* mb, int b0, int b1, int b2, uint32_t dsta, const CUtensorMap* ma, int a0, int a1, uint64_t pb, uint64_t pa) {
  asm volatile(FILL_HEAD
               "@p cp.async.bulk.tensor.3d.shared::cluster.global.mbarrier::complete_tx::bytes.multicast::cluster.L2::cache_hint [%5], [%6, {%7, %8, %9}], [%2], %14, %15;\n"
               "@p cp.async.bulk.tensor.2d.shared::cluster.global.mbarrier::complete_tx::bytes.L2::cache_hint [%10], [%11, {%12, %13}], [%2], %16;\n}\n"
               ::"r"(bb), "n"(BAR(B_EMPTY)), "r"(bb + BAR(B_FULL)), "r"(parity), "r"(bytes), "r"(dstb), "l"(mb), "r"(b0), "r"(b1), "r"(b2), "r"(dsta), "l"(ma), "r"(a0), "r"(a1), "h"((uint16_t)3), "l"(pb), "l"(pa) : "memory");
}
__device__ __forceinline__ void fill_kv(uint32_t bb, uint32_t parity, uint32_t dst, const CUtensorMap* m, int c0, int c1, uint16_t mask, uint64_t pol) {
  asm volatile(FILL_HEAD
               "@p cp.async.bulk.tensor.2d.shared::cluster.global.mbarrier::complete_tx::bytes.multicast::cluster.L2::cache_hint [%5], [%6, {%7, %8}], [%2], %9, %10;\n}\n"
               ::"r"(bb), "n"(BAR(B_EMPTY)), "r"(bb + BAR(B_FULL)), "r"(parity), "r"(32768), "r"(dst), "l"(m), "r"(c0), "r"(c1), "h"(mask), "l"(pol) : "memory");
}
__device__ __forceinline__ void tma_load_2d_h(uint32_t dst, const CUtensorMap* tm, int c0, int c1, uint32_t bar, uint64_t pol) {
  asm volatile("{\n.reg .pred p;\nelect.sync _|p, 0xffffffff;\n@p cp.async.bulk.tensor.2d.shared::cluster.global.mbarrier::complete_tx::bytes.L2::cache_hint [%0], [%1, {%3, %4}], [%2], %5;\n}\n" ::"r"(dst), "l"(tm), "r"(bar), "r"(c0), "r"(c1), "l"(pol) : "memory");
}
__device__ __forceinline__ void tma_store_3d(const CUtensorMap* tm, uint32_t src, int c0, int c1, int c2, uint64_t pol) {
  asm volatile("{\n.reg .pred p;\nelect.sync _|p, 0xffffffff;\n@p cp.async.bulk.tensor.3d.global.shared::cta.bulk_group.L2::cache_hint [%0, {%2, %3, %4}], [%1], %5;\n}\n" ::"l"(tm), "r"(src), "r"(c0), "r"(c1), "r"(c2), "l"(pol) : "memory");
}
__device__ __forceinline__ void bulk_load(uint32_t dst, const void* src, uint32_t bytes, uint32_t bar) {
  asm volatile("{\n.reg .pred p;\nelect.sync _|p, 0xffffffff;\n@p cp.async.bulk.shared::cluster.global.mbarrier::complete_tx::bytes [%0], [%1], %2, [%3];\n}\n" ::"r"(dst), "l"(src), "r"(bytes), "r"(bar) : "memory");
}
__device__ __forceinline__ void bulk_store(void* dst, uint32_t src, uint32_t bytes) {
  asm volatile("{\n.reg .pred p;\nelect.sync _|p, 0xffffffff;\n@p cp.async.bulk.global.shared::cta.bulk_group [%0], [%1], %2;\n}\n" ::"l"(dst), "r"(src), "r"(bytes) : "memory");
}
__device__ __forceinline__ void bulk_send(uint32_t dst, uint32_t src, uint32_t bytes, uint32_t bar) {
  asm volatile("{\n.reg .pred p;\nelect.sync _|p, 0xffffffff;\n@p cp.async.bulk.shared::cluster.shared::cta.mbarrier::complete_tx::bytes [%0], [%1], %2, [%3];\n}\n" ::"r"(dst), "r"(src), "r"(bytes), "r"(bar) : "memory");
}
__device__ __forceinline__ uint64_t policy_evict_first() { uint64_t p; asm volatile("createpolicy.fractional.L2::evict_first.b64 %0, 1.0;" : "=l"(p)); return p; }
constexpr uint64_t POL_NORMAL = 0x1000000000000000ull;
__device__ __forceinline__ uint32_t mapa(uint32_t addr, uint32_t rank) { uint32_t r; asm("mapa.shared::cluster.u32 %0, %1, %2;" : "=r"(r) : "r"(addr), "r"(rank)); return r; }
__device__ __forceinline__ void cluster_arrive_relaxed() { asm volatile("barrier.cluster.arrive.relaxed.aligned;" ::: "memory"); }
__device__ __forceinline__ void cluster_arrive() { asm volatile("barrier.cluster.arrive.release.aligned;" ::: "memory"); }
__device__ __forceinline__ void cluster_wait() { asm volatile("barrier.cluster.wait.acquire.aligned;" ::: "memory"); }
__device__ __forceinline__ void bulk_commit() { asm volatile("cp.async.bulk.commit_group;" ::: "memory"); }
template <int N> __device__ __forceinline__ void bulk_wait_read() { asm volatile("cp.async.bulk.wait_group.read %0;" ::"n"(N) : "memory"); }
__device__ __forceinline__ void bulk_wait_all() { asm volatile("cp.async.bulk.wait_group 0;" ::: "memory"); }
__device__ __forceinline__ void fence_async_smem() { asm volatile("fence.proxy.async.shared::cta;" ::: "memory"); }
__device__ __forceinline__ void fence_async_glob() { asm volatile("fence.proxy.async.global;" ::: "memory"); }
__device__ __forceinline__ void flag_toggle(uint32_t* p, uint32_t v) { asm volatile("{\n.reg .pred p;\nelect.sync _|p, 0xffffffff;\n@p red.release.gpu.global.xor.b32 [%0], %1;\n}\n" ::"l"(p), "r"(v) : "memory"); }
template <uint32_t O> __device__ __forceinline__ uint32_t lds_acquire(uint32_t a) { uint32_t v; asm volatile("ld.acquire.cta.shared::cta.u32 %0, [%1+%2];" : "=r"(v) : "r"(a), "n"(O) : "memory"); return v; }
__device__ __forceinline__ uint32_t item_full(uint32_t sb, int idx) {
  uint32_t c;
  asm volatile("ld.shared.u32 %0, [%1+%2];" : "=r"(c) : "r"(sb + idx * 4), "n"(OFF_LIST));
  return __reduce_or_sync(0xffffffffu, c);
}
__device__ __forceinline__ uint32_t item(uint32_t sb, int idx) { return item_full(sb, idx) & 4095; }
template <int N> __device__ __forceinline__ void reg_alloc() { asm volatile("setmaxnreg.inc.sync.aligned.u32 %0;" ::"n"(N)); }
template <int N> __device__ __forceinline__ void reg_dealloc() { asm volatile("setmaxnreg.dec.sync.aligned.u32 %0;" ::"n"(N)); }
template <int I0, int I1, int N> __device__ __forceinline__ void fence_regs(float (&d)[N]) {
#pragma unroll
  for (int i = I0; i < I1; i++) asm volatile("" : "+f"(d[i])::"memory");
}
template <int N> __device__ __forceinline__ void fence_regs(float (&d)[N]) { fence_regs<0, N, N>(d); }
template <int N> __device__ __forceinline__ void fence_regs(uint32_t (&d)[N]) {
#pragma unroll
  for (int i = 0; i < N; i++) asm volatile("" : "+r"(d[i])::"memory");
}
__device__ __forceinline__ uint32_t pack_bf16(float lo, float hi) { uint32_t r; asm("cvt.rn.bf16x2.f32 %0, %1, %2;" : "=r"(r) : "f"(hi), "f"(lo)); return r; }
__device__ __forceinline__ uint32_t v_pack(float lo, float hi) { uint32_t r; asm volatile("cvt.rn.bf16x2.f32 %0, %1, %2;" : "=r"(r) : "f"(hi), "f"(lo)); return r; }
template <uint32_t O> __device__ __forceinline__ void stmatrix_x4(uint32_t a, uint32_t r0, uint32_t r1, uint32_t r2, uint32_t r3) {
  asm volatile("stmatrix.sync.aligned.m8n8.x4.shared.b16 [%0+%5], {%1, %2, %3, %4};" ::"r"(a), "r"(r0), "r"(r1), "r"(r2), "r"(r3), "n"(O) : "memory");
}
template <uint32_t O> __device__ __forceinline__ void stmatrix_x4_after(uint32_t a, uint32_t r0, uint32_t r1, uint32_t r2, uint32_t r3, float dep, uint32_t on) {
  asm volatile("{\n.reg .pred p, q;\n.reg .u32 a;\nsetp.ne.u32 p, %7, 0;\nsetp.ne.u32 q, %6, 0xffffffff;\nselp.u32 a, %0, 0, q;\n@p stmatrix.sync.aligned.m8n8.x4.shared.b16 [a+%5], {%1, %2, %3, %4};\n}\n"
               ::"r"(a), "r"(r0), "r"(r1), "r"(r2), "r"(r3), "n"(O), "r"(__float_as_uint(dep)), "r"(on) : "memory");
}
template <uint32_t O> __device__ __forceinline__ void stmatrix_x4_trans(uint32_t a, uint32_t r0, uint32_t r1, uint32_t r2, uint32_t r3) {
  asm volatile("stmatrix.sync.aligned.m8n8.x4.trans.shared.b16 [%0+%5], {%1, %2, %3, %4};" ::"r"(a), "r"(r0), "r"(r1), "r"(r2), "r"(r3), "n"(O) : "memory");
}
template <uint32_t O> __device__ __forceinline__ void sts64(uint32_t a, const uint32_t* r) { asm volatile("st.shared.v2.u32 [%0+%3], {%1, %2};" ::"r"(a), "r"(r[0]), "r"(r[1]), "n"(O) : "memory"); }
template <uint32_t O> __device__ __forceinline__ void lds64(uint32_t* r, uint32_t a) { asm volatile("ld.shared.v2.u32 {%0, %1}, [%2+%3];" : "=r"(r[0]), "=r"(r[1]) : "r"(a), "n"(O) : "memory"); }
template <uint32_t O> __device__ __forceinline__ void lds128(uint32_t* r, uint32_t a) { asm volatile("ld.shared.v4.u32 {%0, %1, %2, %3}, [%4+%5];" : "=r"(r[0]), "=r"(r[1]), "=r"(r[2]), "=r"(r[3]) : "r"(a), "n"(O) : "memory"); }
__device__ __forceinline__ uint32_t transpose8(uint32_t a) { uint32_t d; asm volatile("movmatrix.sync.aligned.m8n8.trans.b16 %0, %1;" : "=r"(d) : "r"(a)); return d; }
__device__ __forceinline__ float ex2(float x) { float y; asm("ex2.approx.ftz.f32 %0, %1;" : "=f"(y) : "f"(x)); return y; }
__device__ __forceinline__ float rcp(float x) { float y; asm("rcp.approx.ftz.f32 %0, %1;" : "=f"(y) : "f"(x)); return y; }
__device__ __forceinline__ void bar_sync(int id, int n) { asm volatile("bar.sync %0, %1;" ::"r"(id), "r"(n) : "memory"); }
__device__ __forceinline__ void bar_arrive(int id, int n) { asm volatile("bar.arrive %0, %1;" ::"r"(id), "r"(n) : "memory"); }
__device__ __forceinline__ void mma16816(float (&c)[4], uint32_t a0, uint32_t a1, uint32_t a2, uint32_t a3, uint32_t b0, uint32_t b1) {
  asm("mma.sync.aligned.m16n8k16.row.col.f32.bf16.bf16.f32 {%0, %1, %2, %3}, {%4, %5, %6, %7}, {%8, %9}, {%0, %1, %2, %3};"
      : "+f"(c[0]), "+f"(c[1]), "+f"(c[2]), "+f"(c[3]) : "r"(a0), "r"(a1), "r"(a2), "r"(a3), "r"(b0), "r"(b1));
}
__device__ __forceinline__ void mma16816z(float (&c)[4], uint32_t a0, uint32_t a1, uint32_t a2, uint32_t a3, uint32_t b0, uint32_t b1, const uint32_t (&z)[4]) {
  asm("mma.sync.aligned.m16n8k16.row.col.f32.bf16.bf16.f32 {%0, %1, %2, %3}, {%4, %5, %6, %7}, {%8, %9}, {%10, %11, %12, %13};"
      : "=f"(c[0]), "=f"(c[1]), "=f"(c[2]), "=f"(c[3]) : "r"(a0), "r"(a1), "r"(a2), "r"(a3), "r"(b0), "r"(b1),
        "f"(__uint_as_float(z[0])), "f"(__uint_as_float(z[1])), "f"(__uint_as_float(z[2])), "f"(__uint_as_float(z[3])));
}
__device__ __forceinline__ uint4 ldg128(const void* p) { uint4 v; asm volatile("ld.global.cg.v4.u32 {%0, %1, %2, %3}, [%4];" : "=r"(v.x), "=r"(v.y), "=r"(v.z), "=r"(v.w) : "l"(p) : "memory"); return v; }
__device__ __forceinline__ uint32_t ldg16(const void* p) { uint16_t v; asm volatile("ld.global.cg.u16 %0, [%1];" : "=h"(v) : "l"(p) : "memory"); return v; }
__device__ __forceinline__ float quad_sum(float v) {
  v += __shfl_xor_sync(0xffffffffu, v, 1);
  v += __shfl_xor_sync(0xffffffffu, v, 2);
  return v;
}
__device__ __forceinline__ bool elect_one() { uint32_t p; asm volatile("{\n.reg .pred p;\nelect.sync _|p, 0xffffffff;\nselp.u32 %0, 1, 0, p;\n}\n" : "=r"(p)); return p; }
#define UNLIKELY(x) __builtin_expect(!!(x), 0)

template <int OA, int OB> __device__ __forceinline__ void wg_gemm_init(float (&d)[128], uint64_t da, uint64_t db) {
  asm volatile("{\n.reg .pred p;\n.reg .b64 da, db;\nadd.s64 da, %128, %129;\nadd.s64 db, %130, %131;\nsetp.ne.b32 p, 0, 0;\n"
    "wgmma.mma_async.sync.aligned.m64n256k16.f32.bf16.bf16 {"
    "%0, %1, %2, %3, %4, %5, %6, %7, %8, %9, %10, %11, %12, %13, %14, %15, %16, %17, %18, %19, %20, %21, %22, %23, %24, %25, %26, %27, %28, %29, %30, %31, "
    "%32, %33, %34, %35, %36, %37, %38, %39, %40, %41, %42, %43, %44, %45, %46, %47, %48, %49, %50, %51, %52, %53, %54, %55, %56, %57, %58, %59, %60, %61, %62, %63, "
    "%64, %65, %66, %67, %68, %69, %70, %71, %72, %73, %74, %75, %76, %77, %78, %79, %80, %81, %82, %83, %84, %85, %86, %87, %88, %89, %90, %91, %92, %93, %94, %95, "
    "%96, %97, %98, %99, %100, %101, %102, %103, %104, %105, %106, %107, %108, %109, %110, %111, %112, %113, %114, %115, %116, %117, %118, %119, %120, %121, %122, %123, %124, %125, %126, %127}, "
    "da, db, p, 1, 1, 0, 1;\n}\n"
    : "=f"(d[0]), "=f"(d[1]), "=f"(d[2]), "=f"(d[3]), "=f"(d[4]), "=f"(d[5]), "=f"(d[6]), "=f"(d[7]), "=f"(d[8]), "=f"(d[9]), "=f"(d[10]), "=f"(d[11]), "=f"(d[12]), "=f"(d[13]), "=f"(d[14]), "=f"(d[15]),
      "=f"(d[16]), "=f"(d[17]), "=f"(d[18]), "=f"(d[19]), "=f"(d[20]), "=f"(d[21]), "=f"(d[22]), "=f"(d[23]), "=f"(d[24]), "=f"(d[25]), "=f"(d[26]), "=f"(d[27]), "=f"(d[28]), "=f"(d[29]), "=f"(d[30]), "=f"(d[31]),
      "=f"(d[32]), "=f"(d[33]), "=f"(d[34]), "=f"(d[35]), "=f"(d[36]), "=f"(d[37]), "=f"(d[38]), "=f"(d[39]), "=f"(d[40]), "=f"(d[41]), "=f"(d[42]), "=f"(d[43]), "=f"(d[44]), "=f"(d[45]), "=f"(d[46]), "=f"(d[47]),
      "=f"(d[48]), "=f"(d[49]), "=f"(d[50]), "=f"(d[51]), "=f"(d[52]), "=f"(d[53]), "=f"(d[54]), "=f"(d[55]), "=f"(d[56]), "=f"(d[57]), "=f"(d[58]), "=f"(d[59]), "=f"(d[60]), "=f"(d[61]), "=f"(d[62]), "=f"(d[63]),
      "=f"(d[64]), "=f"(d[65]), "=f"(d[66]), "=f"(d[67]), "=f"(d[68]), "=f"(d[69]), "=f"(d[70]), "=f"(d[71]), "=f"(d[72]), "=f"(d[73]), "=f"(d[74]), "=f"(d[75]), "=f"(d[76]), "=f"(d[77]), "=f"(d[78]), "=f"(d[79]),
      "=f"(d[80]), "=f"(d[81]), "=f"(d[82]), "=f"(d[83]), "=f"(d[84]), "=f"(d[85]), "=f"(d[86]), "=f"(d[87]), "=f"(d[88]), "=f"(d[89]), "=f"(d[90]), "=f"(d[91]), "=f"(d[92]), "=f"(d[93]), "=f"(d[94]), "=f"(d[95]),
      "=f"(d[96]), "=f"(d[97]), "=f"(d[98]), "=f"(d[99]), "=f"(d[100]), "=f"(d[101]), "=f"(d[102]), "=f"(d[103]), "=f"(d[104]), "=f"(d[105]), "=f"(d[106]), "=f"(d[107]), "=f"(d[108]), "=f"(d[109]), "=f"(d[110]), "=f"(d[111]),
      "=f"(d[112]), "=f"(d[113]), "=f"(d[114]), "=f"(d[115]), "=f"(d[116]), "=f"(d[117]), "=f"(d[118]), "=f"(d[119]), "=f"(d[120]), "=f"(d[121]), "=f"(d[122]), "=f"(d[123]), "=f"(d[124]), "=f"(d[125]), "=f"(d[126]), "=f"(d[127])
    : "l"(da), "n"(OA), "l"(db), "n"(OB));
}
template <int OA, int OB> __device__ __forceinline__ void wg_gemm_acc(float (&d)[128], uint64_t da, uint64_t db) {
  asm volatile("{\n.reg .pred p;\n.reg .b64 da, db;\nadd.s64 da, %128, %129;\nadd.s64 db, %130, %131;\nsetp.eq.b32 p, 0, 0;\n"
    "wgmma.mma_async.sync.aligned.m64n256k16.f32.bf16.bf16 {"
    "%0, %1, %2, %3, %4, %5, %6, %7, %8, %9, %10, %11, %12, %13, %14, %15, %16, %17, %18, %19, %20, %21, %22, %23, %24, %25, %26, %27, %28, %29, %30, %31, "
    "%32, %33, %34, %35, %36, %37, %38, %39, %40, %41, %42, %43, %44, %45, %46, %47, %48, %49, %50, %51, %52, %53, %54, %55, %56, %57, %58, %59, %60, %61, %62, %63, "
    "%64, %65, %66, %67, %68, %69, %70, %71, %72, %73, %74, %75, %76, %77, %78, %79, %80, %81, %82, %83, %84, %85, %86, %87, %88, %89, %90, %91, %92, %93, %94, %95, "
    "%96, %97, %98, %99, %100, %101, %102, %103, %104, %105, %106, %107, %108, %109, %110, %111, %112, %113, %114, %115, %116, %117, %118, %119, %120, %121, %122, %123, %124, %125, %126, %127}, "
    "da, db, p, 1, 1, 0, 1;\n}\n"
    : "+f"(d[0]), "+f"(d[1]), "+f"(d[2]), "+f"(d[3]), "+f"(d[4]), "+f"(d[5]), "+f"(d[6]), "+f"(d[7]), "+f"(d[8]), "+f"(d[9]), "+f"(d[10]), "+f"(d[11]), "+f"(d[12]), "+f"(d[13]), "+f"(d[14]), "+f"(d[15]),
      "+f"(d[16]), "+f"(d[17]), "+f"(d[18]), "+f"(d[19]), "+f"(d[20]), "+f"(d[21]), "+f"(d[22]), "+f"(d[23]), "+f"(d[24]), "+f"(d[25]), "+f"(d[26]), "+f"(d[27]), "+f"(d[28]), "+f"(d[29]), "+f"(d[30]), "+f"(d[31]),
      "+f"(d[32]), "+f"(d[33]), "+f"(d[34]), "+f"(d[35]), "+f"(d[36]), "+f"(d[37]), "+f"(d[38]), "+f"(d[39]), "+f"(d[40]), "+f"(d[41]), "+f"(d[42]), "+f"(d[43]), "+f"(d[44]), "+f"(d[45]), "+f"(d[46]), "+f"(d[47]),
      "+f"(d[48]), "+f"(d[49]), "+f"(d[50]), "+f"(d[51]), "+f"(d[52]), "+f"(d[53]), "+f"(d[54]), "+f"(d[55]), "+f"(d[56]), "+f"(d[57]), "+f"(d[58]), "+f"(d[59]), "+f"(d[60]), "+f"(d[61]), "+f"(d[62]), "+f"(d[63]),
      "+f"(d[64]), "+f"(d[65]), "+f"(d[66]), "+f"(d[67]), "+f"(d[68]), "+f"(d[69]), "+f"(d[70]), "+f"(d[71]), "+f"(d[72]), "+f"(d[73]), "+f"(d[74]), "+f"(d[75]), "+f"(d[76]), "+f"(d[77]), "+f"(d[78]), "+f"(d[79]),
      "+f"(d[80]), "+f"(d[81]), "+f"(d[82]), "+f"(d[83]), "+f"(d[84]), "+f"(d[85]), "+f"(d[86]), "+f"(d[87]), "+f"(d[88]), "+f"(d[89]), "+f"(d[90]), "+f"(d[91]), "+f"(d[92]), "+f"(d[93]), "+f"(d[94]), "+f"(d[95]),
      "+f"(d[96]), "+f"(d[97]), "+f"(d[98]), "+f"(d[99]), "+f"(d[100]), "+f"(d[101]), "+f"(d[102]), "+f"(d[103]), "+f"(d[104]), "+f"(d[105]), "+f"(d[106]), "+f"(d[107]), "+f"(d[108]), "+f"(d[109]), "+f"(d[110]), "+f"(d[111]),
      "+f"(d[112]), "+f"(d[113]), "+f"(d[114]), "+f"(d[115]), "+f"(d[116]), "+f"(d[117]), "+f"(d[118]), "+f"(d[119]), "+f"(d[120]), "+f"(d[121]), "+f"(d[122]), "+f"(d[123]), "+f"(d[124]), "+f"(d[125]), "+f"(d[126]), "+f"(d[127])
    : "l"(da), "n"(OA), "l"(db), "n"(OB));
}
template <int OA, int OB> __device__ __forceinline__ void wg_gemm_init(float (&d)[96], uint64_t da, uint64_t db) {
  asm volatile("{\n.reg .pred p;\n.reg .b64 da, db;\nadd.s64 da, %96, %97;\nadd.s64 db, %98, %99;\nsetp.ne.b32 p, 0, 0;\n"
    "wgmma.mma_async.sync.aligned.m64n192k16.f32.bf16.bf16 {"
    "%0, %1, %2, %3, %4, %5, %6, %7, %8, %9, %10, %11, %12, %13, %14, %15, %16, %17, %18, %19, %20, %21, %22, %23, %24, %25, %26, %27, %28, %29, %30, %31, "
    "%32, %33, %34, %35, %36, %37, %38, %39, %40, %41, %42, %43, %44, %45, %46, %47, %48, %49, %50, %51, %52, %53, %54, %55, %56, %57, %58, %59, %60, %61, %62, %63, "
    "%64, %65, %66, %67, %68, %69, %70, %71, %72, %73, %74, %75, %76, %77, %78, %79, %80, %81, %82, %83, %84, %85, %86, %87, %88, %89, %90, %91, %92, %93, %94, %95}, "
    "da, db, p, 1, 1, 0, 1;\n}\n"
    : "=f"(d[0]), "=f"(d[1]), "=f"(d[2]), "=f"(d[3]), "=f"(d[4]), "=f"(d[5]), "=f"(d[6]), "=f"(d[7]), "=f"(d[8]), "=f"(d[9]), "=f"(d[10]), "=f"(d[11]), "=f"(d[12]), "=f"(d[13]), "=f"(d[14]), "=f"(d[15]),
      "=f"(d[16]), "=f"(d[17]), "=f"(d[18]), "=f"(d[19]), "=f"(d[20]), "=f"(d[21]), "=f"(d[22]), "=f"(d[23]), "=f"(d[24]), "=f"(d[25]), "=f"(d[26]), "=f"(d[27]), "=f"(d[28]), "=f"(d[29]), "=f"(d[30]), "=f"(d[31]),
      "=f"(d[32]), "=f"(d[33]), "=f"(d[34]), "=f"(d[35]), "=f"(d[36]), "=f"(d[37]), "=f"(d[38]), "=f"(d[39]), "=f"(d[40]), "=f"(d[41]), "=f"(d[42]), "=f"(d[43]), "=f"(d[44]), "=f"(d[45]), "=f"(d[46]), "=f"(d[47]),
      "=f"(d[48]), "=f"(d[49]), "=f"(d[50]), "=f"(d[51]), "=f"(d[52]), "=f"(d[53]), "=f"(d[54]), "=f"(d[55]), "=f"(d[56]), "=f"(d[57]), "=f"(d[58]), "=f"(d[59]), "=f"(d[60]), "=f"(d[61]), "=f"(d[62]), "=f"(d[63]),
      "=f"(d[64]), "=f"(d[65]), "=f"(d[66]), "=f"(d[67]), "=f"(d[68]), "=f"(d[69]), "=f"(d[70]), "=f"(d[71]), "=f"(d[72]), "=f"(d[73]), "=f"(d[74]), "=f"(d[75]), "=f"(d[76]), "=f"(d[77]), "=f"(d[78]), "=f"(d[79]),
      "=f"(d[80]), "=f"(d[81]), "=f"(d[82]), "=f"(d[83]), "=f"(d[84]), "=f"(d[85]), "=f"(d[86]), "=f"(d[87]), "=f"(d[88]), "=f"(d[89]), "=f"(d[90]), "=f"(d[91]), "=f"(d[92]), "=f"(d[93]), "=f"(d[94]), "=f"(d[95])
    : "l"(da), "n"(OA), "l"(db), "n"(OB));
}
template <int OA, int OB> __device__ __forceinline__ void wg_gemm_acc(float (&d)[96], uint64_t da, uint64_t db) {
  asm volatile("{\n.reg .pred p;\n.reg .b64 da, db;\nadd.s64 da, %96, %97;\nadd.s64 db, %98, %99;\nsetp.eq.b32 p, 0, 0;\n"
    "wgmma.mma_async.sync.aligned.m64n192k16.f32.bf16.bf16 {"
    "%0, %1, %2, %3, %4, %5, %6, %7, %8, %9, %10, %11, %12, %13, %14, %15, %16, %17, %18, %19, %20, %21, %22, %23, %24, %25, %26, %27, %28, %29, %30, %31, "
    "%32, %33, %34, %35, %36, %37, %38, %39, %40, %41, %42, %43, %44, %45, %46, %47, %48, %49, %50, %51, %52, %53, %54, %55, %56, %57, %58, %59, %60, %61, %62, %63, "
    "%64, %65, %66, %67, %68, %69, %70, %71, %72, %73, %74, %75, %76, %77, %78, %79, %80, %81, %82, %83, %84, %85, %86, %87, %88, %89, %90, %91, %92, %93, %94, %95}, "
    "da, db, p, 1, 1, 0, 1;\n}\n"
    : "+f"(d[0]), "+f"(d[1]), "+f"(d[2]), "+f"(d[3]), "+f"(d[4]), "+f"(d[5]), "+f"(d[6]), "+f"(d[7]), "+f"(d[8]), "+f"(d[9]), "+f"(d[10]), "+f"(d[11]), "+f"(d[12]), "+f"(d[13]), "+f"(d[14]), "+f"(d[15]),
      "+f"(d[16]), "+f"(d[17]), "+f"(d[18]), "+f"(d[19]), "+f"(d[20]), "+f"(d[21]), "+f"(d[22]), "+f"(d[23]), "+f"(d[24]), "+f"(d[25]), "+f"(d[26]), "+f"(d[27]), "+f"(d[28]), "+f"(d[29]), "+f"(d[30]), "+f"(d[31]),
      "+f"(d[32]), "+f"(d[33]), "+f"(d[34]), "+f"(d[35]), "+f"(d[36]), "+f"(d[37]), "+f"(d[38]), "+f"(d[39]), "+f"(d[40]), "+f"(d[41]), "+f"(d[42]), "+f"(d[43]), "+f"(d[44]), "+f"(d[45]), "+f"(d[46]), "+f"(d[47]),
      "+f"(d[48]), "+f"(d[49]), "+f"(d[50]), "+f"(d[51]), "+f"(d[52]), "+f"(d[53]), "+f"(d[54]), "+f"(d[55]), "+f"(d[56]), "+f"(d[57]), "+f"(d[58]), "+f"(d[59]), "+f"(d[60]), "+f"(d[61]), "+f"(d[62]), "+f"(d[63]),
      "+f"(d[64]), "+f"(d[65]), "+f"(d[66]), "+f"(d[67]), "+f"(d[68]), "+f"(d[69]), "+f"(d[70]), "+f"(d[71]), "+f"(d[72]), "+f"(d[73]), "+f"(d[74]), "+f"(d[75]), "+f"(d[76]), "+f"(d[77]), "+f"(d[78]), "+f"(d[79]),
      "+f"(d[80]), "+f"(d[81]), "+f"(d[82]), "+f"(d[83]), "+f"(d[84]), "+f"(d[85]), "+f"(d[86]), "+f"(d[87]), "+f"(d[88]), "+f"(d[89]), "+f"(d[90]), "+f"(d[91]), "+f"(d[92]), "+f"(d[93]), "+f"(d[94]), "+f"(d[95])
    : "l"(da), "n"(OA), "l"(db), "n"(OB));
}
template <int OA, int OB> __device__ __forceinline__ void wg_qk_init(float (&d)[64], uint64_t da, uint64_t db) {
  asm volatile("{\n.reg .pred p;\n.reg .b64 da, db;\nadd.s64 da, %64, %65;\nadd.s64 db, %66, %67;\nsetp.ne.b32 p, 0, 0;\n"
    "wgmma.mma_async.sync.aligned.m64n128k16.f32.bf16.bf16 {"
    "%0, %1, %2, %3, %4, %5, %6, %7, %8, %9, %10, %11, %12, %13, %14, %15, %16, %17, %18, %19, %20, %21, %22, %23, %24, %25, %26, %27, %28, %29, %30, %31, "
    "%32, %33, %34, %35, %36, %37, %38, %39, %40, %41, %42, %43, %44, %45, %46, %47, %48, %49, %50, %51, %52, %53, %54, %55, %56, %57, %58, %59, %60, %61, %62, %63}, "
    "da, db, p, 1, 1, 0, 0;\n}\n"
    : "=f"(d[0]), "=f"(d[1]), "=f"(d[2]), "=f"(d[3]), "=f"(d[4]), "=f"(d[5]), "=f"(d[6]), "=f"(d[7]), "=f"(d[8]), "=f"(d[9]), "=f"(d[10]), "=f"(d[11]), "=f"(d[12]), "=f"(d[13]), "=f"(d[14]), "=f"(d[15]),
      "=f"(d[16]), "=f"(d[17]), "=f"(d[18]), "=f"(d[19]), "=f"(d[20]), "=f"(d[21]), "=f"(d[22]), "=f"(d[23]), "=f"(d[24]), "=f"(d[25]), "=f"(d[26]), "=f"(d[27]), "=f"(d[28]), "=f"(d[29]), "=f"(d[30]), "=f"(d[31]),
      "=f"(d[32]), "=f"(d[33]), "=f"(d[34]), "=f"(d[35]), "=f"(d[36]), "=f"(d[37]), "=f"(d[38]), "=f"(d[39]), "=f"(d[40]), "=f"(d[41]), "=f"(d[42]), "=f"(d[43]), "=f"(d[44]), "=f"(d[45]), "=f"(d[46]), "=f"(d[47]),
      "=f"(d[48]), "=f"(d[49]), "=f"(d[50]), "=f"(d[51]), "=f"(d[52]), "=f"(d[53]), "=f"(d[54]), "=f"(d[55]), "=f"(d[56]), "=f"(d[57]), "=f"(d[58]), "=f"(d[59]), "=f"(d[60]), "=f"(d[61]), "=f"(d[62]), "=f"(d[63])
    : "l"(da), "n"(OA), "l"(db), "n"(OB));
}
template <int OA, int OB> __device__ __forceinline__ void wg_qk_acc(float (&d)[64], uint64_t da, uint64_t db) {
  asm volatile("{\n.reg .pred p;\n.reg .b64 da, db;\nadd.s64 da, %64, %65;\nadd.s64 db, %66, %67;\nsetp.eq.b32 p, 0, 0;\n"
    "wgmma.mma_async.sync.aligned.m64n128k16.f32.bf16.bf16 {"
    "%0, %1, %2, %3, %4, %5, %6, %7, %8, %9, %10, %11, %12, %13, %14, %15, %16, %17, %18, %19, %20, %21, %22, %23, %24, %25, %26, %27, %28, %29, %30, %31, "
    "%32, %33, %34, %35, %36, %37, %38, %39, %40, %41, %42, %43, %44, %45, %46, %47, %48, %49, %50, %51, %52, %53, %54, %55, %56, %57, %58, %59, %60, %61, %62, %63}, "
    "da, db, p, 1, 1, 0, 0;\n}\n"
    : "+f"(d[0]), "+f"(d[1]), "+f"(d[2]), "+f"(d[3]), "+f"(d[4]), "+f"(d[5]), "+f"(d[6]), "+f"(d[7]), "+f"(d[8]), "+f"(d[9]), "+f"(d[10]), "+f"(d[11]), "+f"(d[12]), "+f"(d[13]), "+f"(d[14]), "+f"(d[15]),
      "+f"(d[16]), "+f"(d[17]), "+f"(d[18]), "+f"(d[19]), "+f"(d[20]), "+f"(d[21]), "+f"(d[22]), "+f"(d[23]), "+f"(d[24]), "+f"(d[25]), "+f"(d[26]), "+f"(d[27]), "+f"(d[28]), "+f"(d[29]), "+f"(d[30]), "+f"(d[31]),
      "+f"(d[32]), "+f"(d[33]), "+f"(d[34]), "+f"(d[35]), "+f"(d[36]), "+f"(d[37]), "+f"(d[38]), "+f"(d[39]), "+f"(d[40]), "+f"(d[41]), "+f"(d[42]), "+f"(d[43]), "+f"(d[44]), "+f"(d[45]), "+f"(d[46]), "+f"(d[47]),
      "+f"(d[48]), "+f"(d[49]), "+f"(d[50]), "+f"(d[51]), "+f"(d[52]), "+f"(d[53]), "+f"(d[54]), "+f"(d[55]), "+f"(d[56]), "+f"(d[57]), "+f"(d[58]), "+f"(d[59]), "+f"(d[60]), "+f"(d[61]), "+f"(d[62]), "+f"(d[63])
    : "l"(da), "n"(OA), "l"(db), "n"(OB));
}
template <int OA, int OB> __device__ __forceinline__ void wg_qk64_init(float (&d)[64], uint64_t da, uint64_t db) {
  asm volatile("{\n.reg .pred p;\n.reg .b64 da, db;\nadd.s64 da, %32, %33;\nadd.s64 db, %34, %35;\nsetp.ne.b32 p, 0, 0;\n"
    "wgmma.mma_async.sync.aligned.m64n64k16.f32.bf16.bf16 {"
    "%0, %1, %2, %3, %4, %5, %6, %7, %8, %9, %10, %11, %12, %13, %14, %15, %16, %17, %18, %19, %20, %21, %22, %23, %24, %25, %26, %27, %28, %29, %30, %31}, "
    "da, db, p, 1, 1, 0, 0;\n}\n"
    : "=f"(d[0]), "=f"(d[1]), "=f"(d[2]), "=f"(d[3]), "=f"(d[4]), "=f"(d[5]), "=f"(d[6]), "=f"(d[7]), "=f"(d[8]), "=f"(d[9]), "=f"(d[10]), "=f"(d[11]), "=f"(d[12]), "=f"(d[13]), "=f"(d[14]), "=f"(d[15]),
      "=f"(d[16]), "=f"(d[17]), "=f"(d[18]), "=f"(d[19]), "=f"(d[20]), "=f"(d[21]), "=f"(d[22]), "=f"(d[23]), "=f"(d[24]), "=f"(d[25]), "=f"(d[26]), "=f"(d[27]), "=f"(d[28]), "=f"(d[29]), "=f"(d[30]), "=f"(d[31])
    : "l"(da), "n"(OA), "l"(db), "n"(OB));
}
template <int OA, int OB> __device__ __forceinline__ void wg_qk64_acc(float (&d)[64], uint64_t da, uint64_t db) {
  asm volatile("{\n.reg .pred p;\n.reg .b64 da, db;\nadd.s64 da, %32, %33;\nadd.s64 db, %34, %35;\nsetp.eq.b32 p, 0, 0;\n"
    "wgmma.mma_async.sync.aligned.m64n64k16.f32.bf16.bf16 {"
    "%0, %1, %2, %3, %4, %5, %6, %7, %8, %9, %10, %11, %12, %13, %14, %15, %16, %17, %18, %19, %20, %21, %22, %23, %24, %25, %26, %27, %28, %29, %30, %31}, "
    "da, db, p, 1, 1, 0, 0;\n}\n"
    : "+f"(d[0]), "+f"(d[1]), "+f"(d[2]), "+f"(d[3]), "+f"(d[4]), "+f"(d[5]), "+f"(d[6]), "+f"(d[7]), "+f"(d[8]), "+f"(d[9]), "+f"(d[10]), "+f"(d[11]), "+f"(d[12]), "+f"(d[13]), "+f"(d[14]), "+f"(d[15]),
      "+f"(d[16]), "+f"(d[17]), "+f"(d[18]), "+f"(d[19]), "+f"(d[20]), "+f"(d[21]), "+f"(d[22]), "+f"(d[23]), "+f"(d[24]), "+f"(d[25]), "+f"(d[26]), "+f"(d[27]), "+f"(d[28]), "+f"(d[29]), "+f"(d[30]), "+f"(d[31])
    : "l"(da), "n"(OA), "l"(db), "n"(OB));
}
template <int OB> __device__ __forceinline__ void wg_pv_init(float (&d)[64], const uint32_t* a, uint64_t db) {
  asm volatile("{\n.reg .pred p;\n.reg .b64 da, db;\nadd.s64 db, %68, %69;\nsetp.ne.b32 p, 0, 0;\n"
    "wgmma.mma_async.sync.aligned.m64n128k16.f32.bf16.bf16 {"
    "%0, %1, %2, %3, %4, %5, %6, %7, %8, %9, %10, %11, %12, %13, %14, %15, %16, %17, %18, %19, %20, %21, %22, %23, %24, %25, %26, %27, %28, %29, %30, %31, "
    "%32, %33, %34, %35, %36, %37, %38, %39, %40, %41, %42, %43, %44, %45, %46, %47, %48, %49, %50, %51, %52, %53, %54, %55, %56, %57, %58, %59, %60, %61, %62, %63}, "
    "{%64, %65, %66, %67}, db, p, 1, 1, 1;\n}\n"
    : "=f"(d[0]), "=f"(d[1]), "=f"(d[2]), "=f"(d[3]), "=f"(d[4]), "=f"(d[5]), "=f"(d[6]), "=f"(d[7]), "=f"(d[8]), "=f"(d[9]), "=f"(d[10]), "=f"(d[11]), "=f"(d[12]), "=f"(d[13]), "=f"(d[14]), "=f"(d[15]),
      "=f"(d[16]), "=f"(d[17]), "=f"(d[18]), "=f"(d[19]), "=f"(d[20]), "=f"(d[21]), "=f"(d[22]), "=f"(d[23]), "=f"(d[24]), "=f"(d[25]), "=f"(d[26]), "=f"(d[27]), "=f"(d[28]), "=f"(d[29]), "=f"(d[30]), "=f"(d[31]),
      "=f"(d[32]), "=f"(d[33]), "=f"(d[34]), "=f"(d[35]), "=f"(d[36]), "=f"(d[37]), "=f"(d[38]), "=f"(d[39]), "=f"(d[40]), "=f"(d[41]), "=f"(d[42]), "=f"(d[43]), "=f"(d[44]), "=f"(d[45]), "=f"(d[46]), "=f"(d[47]),
      "=f"(d[48]), "=f"(d[49]), "=f"(d[50]), "=f"(d[51]), "=f"(d[52]), "=f"(d[53]), "=f"(d[54]), "=f"(d[55]), "=f"(d[56]), "=f"(d[57]), "=f"(d[58]), "=f"(d[59]), "=f"(d[60]), "=f"(d[61]), "=f"(d[62]), "=f"(d[63])
    : "r"(a[0]), "r"(a[1]), "r"(a[2]), "r"(a[3]), "l"(db), "n"(OB));
}
template <int OB> __device__ __forceinline__ void wg_pv_acc(float (&d)[64], const uint32_t* a, uint64_t db) {
  asm volatile("{\n.reg .pred p;\n.reg .b64 da, db;\nadd.s64 db, %68, %69;\nsetp.eq.b32 p, 0, 0;\n"
    "wgmma.mma_async.sync.aligned.m64n128k16.f32.bf16.bf16 {"
    "%0, %1, %2, %3, %4, %5, %6, %7, %8, %9, %10, %11, %12, %13, %14, %15, %16, %17, %18, %19, %20, %21, %22, %23, %24, %25, %26, %27, %28, %29, %30, %31, "
    "%32, %33, %34, %35, %36, %37, %38, %39, %40, %41, %42, %43, %44, %45, %46, %47, %48, %49, %50, %51, %52, %53, %54, %55, %56, %57, %58, %59, %60, %61, %62, %63}, "
    "{%64, %65, %66, %67}, db, p, 1, 1, 1;\n}\n"
    : "+f"(d[0]), "+f"(d[1]), "+f"(d[2]), "+f"(d[3]), "+f"(d[4]), "+f"(d[5]), "+f"(d[6]), "+f"(d[7]), "+f"(d[8]), "+f"(d[9]), "+f"(d[10]), "+f"(d[11]), "+f"(d[12]), "+f"(d[13]), "+f"(d[14]), "+f"(d[15]),
      "+f"(d[16]), "+f"(d[17]), "+f"(d[18]), "+f"(d[19]), "+f"(d[20]), "+f"(d[21]), "+f"(d[22]), "+f"(d[23]), "+f"(d[24]), "+f"(d[25]), "+f"(d[26]), "+f"(d[27]), "+f"(d[28]), "+f"(d[29]), "+f"(d[30]), "+f"(d[31]),
      "+f"(d[32]), "+f"(d[33]), "+f"(d[34]), "+f"(d[35]), "+f"(d[36]), "+f"(d[37]), "+f"(d[38]), "+f"(d[39]), "+f"(d[40]), "+f"(d[41]), "+f"(d[42]), "+f"(d[43]), "+f"(d[44]), "+f"(d[45]), "+f"(d[46]), "+f"(d[47]),
      "+f"(d[48]), "+f"(d[49]), "+f"(d[50]), "+f"(d[51]), "+f"(d[52]), "+f"(d[53]), "+f"(d[54]), "+f"(d[55]), "+f"(d[56]), "+f"(d[57]), "+f"(d[58]), "+f"(d[59]), "+f"(d[60]), "+f"(d[61]), "+f"(d[62]), "+f"(d[63])
    : "r"(a[0]), "r"(a[1]), "r"(a[2]), "r"(a[3]), "l"(db), "n"(OB));
}

struct Cons {
  uint32_t d0, da;
  uint32_t sb;
  uint32_t rel;
  uint32_t p0, p1;
  uint32_t lead, round, fpar;
};

template <uint32_t OFF, uint32_t GROUP> __device__ __forceinline__ void tile_write(const uint32_t (&pk)[32], uint32_t base) {
  const uint32_t lane = threadIdx.x & 31, wq = (threadIdx.x >> 5) & 3;
  const uint32_t a = base + (wq * 16 + (lane & 15)) * 128 + (((lane >> 4) ^ (lane & 7)) << 4);
#define TW(j) stmatrix_x4<OFF + (j >> 2) * GROUP>(a ^ ((j & 3) * 32), pk[4 * j + 0], pk[4 * j + 1], pk[4 * j + 2], pk[4 * j + 3])
  TW(0); TW(1); TW(2); TW(3); TW(4); TW(5); TW(6); TW(7);
#undef TW
}
template <uint32_t OFF, uint32_t GROUP, int A0> __device__ __forceinline__ void tile_pack_write(const float (&acc)[128], uint32_t (&pk)[32], uint32_t base) {
  const uint32_t lane = threadIdx.x & 31, wq = (threadIdx.x >> 5) & 3;
  const uint32_t a = base + (wq * 16 + (lane & 15)) * 128 + (((lane >> 4) ^ (lane & 7)) << 4);
#define TW(j) \
  pk[4 * j + 0] = v_pack(acc[A0 + 8 * j + 0], acc[A0 + 8 * j + 1]); pk[4 * j + 1] = v_pack(acc[A0 + 8 * j + 2], acc[A0 + 8 * j + 3]); \
  pk[4 * j + 2] = v_pack(acc[A0 + 8 * j + 4], acc[A0 + 8 * j + 5]); pk[4 * j + 3] = v_pack(acc[A0 + 8 * j + 6], acc[A0 + 8 * j + 7]); \
  stmatrix_x4<OFF + (j >> 2) * GROUP>(a ^ ((j & 3) * 32), pk[4 * j + 0], pk[4 * j + 1], pk[4 * j + 2], pk[4 * j + 3])
  TW(0); TW(1); TW(2); TW(3); TW(4); TW(5); TW(6); TW(7);
#undef TW
}
__device__ __forceinline__ void stage_write(const uint32_t (&pk)[32], int w, const Cons& cs) {
  mbar_wait<BAR(B_STGE)>(cs.sb + w * 8, (cs.round & 1) ^ 1);
  tile_write<OFF_STG, 8192>(pk, cs.sb + w * 16384);
}
__device__ __forceinline__ void stage_publish(int w, Cons& cs) {
  fence_async_smem();
  __syncwarp();
  mbar_arrive_if<BAR(B_STGF)>(cs.sb + w * 8, (threadIdx.x & 31) == 0);
  cs.round++;
}

template <int ST, bool INIT, bool FIRST = INIT, int NA> __device__ __forceinline__ void g_issue(float (&acc)[NA], const Cons& cs) {
  constexpr int B2 = NA == 128 ? 256 : 768, Z = FIRST ? 128 : 0;
  uint32_t a, b;
  asm volatile("add.u32 %0, %2, %4;\nadd.u32 %1, %3, %5;" : "=r"(a), "=r"(b) : "r"(cs.da), "r"(cs.d0), "n"(dlo(OFF_A + ST * 16384, NA + (FIRST ? 16 : 0))), "n"(dlo(OFF_B + ST * 32768, NA == 128 ? 8192 : 4096) + Z));
  const uint64_t A = desc(a), B = desc(b);
  wg_fence();
  if (INIT) wg_gemm_init<0, -Z>(acc, A, B); else wg_gemm_acc<0, -Z>(acc, A, B);
  wg_gemm_acc<2, 128 - Z>(acc, A, B);
  wg_gemm_acc<4, B2 - Z>(acc, A, B);
  wg_gemm_acc<6, B2 + 128 - Z>(acc, A, B);
  wg_commit();
}
template <int NA, class F>
__device__ __forceinline__ uint32_t gemm_tile(float (&acc)[NA], int nk4, int idx, int w, Cons& cs, uint32_t pend, const uint32_t (&pkA)[32], const uint32_t (&pkB)[32], F&& before_end) {
  const uint32_t sb = cs.sb, rel = cs.rel;
  constexpr int SA = NA == 128 ? STGA : STGAL, SBB = NA == 128 ? STGB : STGBL;
#define HOOK(n) \
  if (n == 0 && (pend & 8)) stage_publish(w, cs); \
  if (n == 0 && (pend & 16) && w == 0) bar_sync(5, 256); \
  if (n == SA && (pend & 1)) stage_write(pkA, w, cs); \
  if (n == SA + 1 && (pend & 1)) { stage_publish(w, cs); pend &= 6; } \
  if (n == SBB && (pend & 2)) { stage_write(pkB, w, cs); pend = 4; } \
  if (n == SBB + 1 && (pend & 4)) { stage_publish(w, cs); pend = 0; }
  mbar_wait<BAR(B_FULL + 0)>(sb, cs.p0);
  g_issue<0, true>(acc, cs);
  HOOK(0);
  mbar_wait<BAR(B_FULL + 1)>(sb, cs.p1);
  g_issue<1, false, true>(acc, cs);
  HOOK(2);
  wg_wait<1>();
  mbar_arrive_cl<BAR(B_EMPTY + 0)>(rel);
  HOOK(3);
  mbar_wait<BAR(B_FULL + 2)>(sb, cs.p0);
  g_issue<2, false, true>(acc, cs);
  HOOK(4);
  wg_wait<1>();
  mbar_arrive_cl<BAR(B_EMPTY + 1)>(rel);
  HOOK(5);
  mbar_wait<BAR(B_FULL + 3)>(sb, cs.p1);
  g_issue<3, false, true>(acc, cs);
  HOOK(6);
  const uint32_t ncode = item(sb, idx + 1);
  wg_wait<1>();
  mbar_arrive_cl<BAR(B_EMPTY + 2)>(rel);
  HOOK(7);
  cs.p0 ^= 1; cs.p1 ^= 1;
  const bool final_tile = NA == 128 && (ncode >> 9) == K_END;
#pragma unroll 1
  for (int q = 1; q < nk4; q++) {
    const bool tail = q == nk4 - 1;
    mbar_wait<BAR(B_FULL + 0)>(sb, cs.p0);
    g_issue<0, false>(acc, cs);
    HOOK(8);
    wg_wait<1>();
    mbar_arrive_cl<BAR(B_EMPTY + 3)>(rel);
    HOOK(9);
    mbar_wait<BAR(B_FULL + 1)>(sb, cs.p1);
    uint32_t rel0 = rel;
    if (final_tile && tail && w == 1) {
      wg_wait<0>();
      mbar_arrive_cl<BAR(B_EMPTY + 0)>(rel);
      rel0 = 0;
      mbar_wait<BAR(B_LEAD)>(sb, cs.lead);
    }
    g_issue<1, false>(acc, cs);
    HOOK(10);
    wg_wait<1>();
    mbar_arrive_cl<BAR(B_EMPTY + 0)>(rel0);
    HOOK(11);
    mbar_wait<BAR(B_FULL + 2)>(sb, cs.p0);
    uint32_t rel1 = rel;
    if (!final_tile && tail && w == 1) {
      wg_wait<0>();
      mbar_arrive_cl<BAR(B_EMPTY + 1)>(rel);
      rel1 = 0;
      mbar_wait<BAR(B_LEAD)>(sb, cs.lead);
    }
    g_issue<2, false>(acc, cs);
    HOOK(12);
    wg_wait<1>();
    mbar_arrive_cl<BAR(B_EMPTY + 1)>(rel1);
    HOOK(13);
    mbar_wait<BAR(B_FULL + 3)>(sb, cs.p1);
    g_issue<3, false>(acc, cs);
    mbar_arrive_if<BAR(B_LEAD)>(sb, tail && threadIdx.x == 128);
    HOOK(14);
    wg_wait<1>();
    mbar_arrive_cl<BAR(B_EMPTY + 2)>(rel);
    cs.p0 ^= 1; cs.p1 ^= 1;
  }
#undef HOOK
  cs.lead ^= 1;
  before_end();
  wg_wait<0>();
  fence_regs(acc);
  mbar_arrive_cl<BAR(B_EMPTY + 3)>(rel);
  return ncode;
}

__device__ __forceinline__ void local_probs(bool first, const float (&S)[3][4], uint32_t (&pb)[4]) {
  const int lane = threadIdx.x & 31, g = lane >> 2, t = lane & 3;
  const bool c0 = 2 * t > g, c1 = 2 * t + 1 > g;
  float x0 = c0 ? S[0][0] : S[1][0], x1 = c1 ? S[0][1] : S[1][1], y0 = c0 ? S[1][2] : S[2][2], y1 = c1 ? S[1][3] : S[2][3];
  if (first && c0) x0 = -INFINITY;
  if (first && c1) x1 = -INFINITY;
  float m0 = fmaxf(x0, x1), m1 = fmaxf(y0, y1);
  m0 = fmaxf(fmaxf(m0, __shfl_xor_sync(0xffffffffu, m0, 1)), fmaxf(__shfl_xor_sync(0xffffffffu, m0, 2), __shfl_xor_sync(0xffffffffu, m0, 3)));
  m1 = fmaxf(fmaxf(m1, __shfl_xor_sync(0xffffffffu, m1, 1)), fmaxf(__shfl_xor_sync(0xffffffffu, m1, 2), __shfl_xor_sync(0xffffffffu, m1, 3)));
  constexpr float C = 0.17677669529663687f * 1.4426950408889634f;
  const float b0 = -m0 * C, b1 = -m1 * C;
  x0 = ex2(fmaf(x0, C, b0)); x1 = ex2(fmaf(x1, C, b0)); y0 = ex2(fmaf(y0, C, b1)); y1 = ex2(fmaf(y1, C, b1));
  const float l0 = rcp(quad_sum(x0 + x1)), l1 = rcp(quad_sum(y0 + y1));
  const uint32_t px = pack_bf16(x0 * l0, x1 * l0), py = pack_bf16(y0 * l1, y1 * l1);
  const uint32_t m = (c0 ? 0xffffu : 0u) | (c1 ? 0xffff0000u : 0u);
  pb[0] = px & m; pb[1] = px & ~m; pb[2] = py & m; pb[3] = py & ~m;
}
struct Loc { uint32_t xa, ra, oa; };
__device__ __forceinline__ Loc local_prepare(uint32_t code, int w, Cons& cs) {
  const uint32_t lane = threadIdx.x & 31, wq = (threadIdx.x >> 5) & 3;
  const bool has_halo = (code & 15) != 0;
  Loc l;
  l.xa = cs.sb + OFF_STG + 8192 + w * 16384 + wq * 2048 + lane * 8;
  l.ra = l.xa - (wq == 0 ? 16384 - 3 * 2048 : 2048);
  if (w + wq == 0) l.ra = has_halo ? cs.sb + OFF_HALO + lane * 8 : l.xa;
  l.oa = cs.sb + w * 16384 + (wq * 16 + (lane & 7)) * 128 + (((lane >> 3) ^ (lane & 7)) << 4);
  asm volatile("{\n.reg .pred p;\nsetp.eq.u32 p, %0, 0;\n@p st.shared.u32 [%1], %2;\n}\n" ::"r"(l.xa), "r"(l.ra), "r"(l.oa) : "memory");
  mbar_wait<BAR(B_STGE)>(cs.sb + w * 8, (cs.round & 1) ^ 1);
  if (has_halo && w == 0) mbar_wait<BAR(B_HFULL)>(cs.sb, cs.fpar >> 1);
  cs.fpar ^= has_halo ? 2 : 0;
  return l;
}
__device__ __forceinline__ void local_epilogue(const float (&acc)[96], uint32_t code, int w, Cons& cs, const Loc& l) {
  const uint32_t cw = (threadIdx.x >> 5) - 4;
  const bool has_halo = (code & 15) != 0;
  uint32_t kf[3][8], vt[3][8];
#pragma unroll
  for (int j = 0; j < 8; j++) { kf[2][j] = pack_bf16(acc[32 + 4 * j + 2], acc[32 + 4 * j + 3]); vt[2][j] = transpose8(pack_bf16(acc[64 + 4 * j + 2], acc[64 + 4 * j + 3])); }
  sts64<0>(l.xa, &kf[2][0]); sts64<256>(l.xa, &kf[2][2]); sts64<512>(l.xa, &kf[2][4]); sts64<768>(l.xa, &kf[2][6]);
  sts64<1024>(l.xa, &vt[2][0]); sts64<1280>(l.xa, &vt[2][2]); sts64<1536>(l.xa, &vt[2][4]); sts64<1792>(l.xa, &vt[2][6]);
  if (cw == 3) bar_arrive(4, 160);
  uint32_t q[8][2];
#pragma unroll
  for (int j = 0; j < 8; j++) {
    q[j][0] = pack_bf16(acc[4 * j], acc[4 * j + 1]); q[j][1] = pack_bf16(acc[4 * j + 2], acc[4 * j + 3]);
    kf[1][j] = pack_bf16(acc[32 + 4 * j], acc[32 + 4 * j + 1]);
  }
  bar_sync(3 + w, 128 + 32 * w);
  uint32_t z[4];
  lds128<OFF_FILLS + 16>(z, cs.sb);
  lds64<0>(&kf[0][0], l.ra); lds64<512>(&kf[0][4], l.ra); lds64<256>(&kf[0][2], l.ra); lds64<768>(&kf[0][6], l.ra);
  lds64<1024>(&vt[0][0], l.ra); lds64<1280>(&vt[0][2], l.ra); lds64<1536>(&vt[0][4], l.ra); lds64<1792>(&vt[0][6], l.ra);
  float S[2][3][4];
#pragma unroll
  for (int n = 2; n >= 0; n--)
#pragma unroll
    for (int u = 0; u < 2; u++) mma16816z(S[u][n], q[4 * u][0], q[4 * u][1], q[4 * u + 1][0], q[4 * u + 1][1], kf[n][4 * u], kf[n][4 * u + 1], z);
#pragma unroll
  for (int n = 2; n >= 0; n--)
#pragma unroll
    for (int u = 0; u < 2; u++) mma16816(S[u][n], q[4 * u + 2][0], q[4 * u + 2][1], q[4 * u + 3][0], q[4 * u + 3][1], kf[n][4 * u + 2], kf[n][4 * u + 3]);
#pragma unroll
  for (int j = 0; j < 8; j++) vt[1][j] = transpose8(pack_bf16(acc[64 + 4 * j], acc[64 + 4 * j + 1]));
  uint32_t pb[2][4];
#pragma unroll
  for (int u = 0; u < 2; u++) local_probs(cw == 0 && !has_halo, S[u], pb[u]);
  const uint32_t oa = l.oa;
#pragma unroll
  for (int u = 0; u < 2; u++)
#pragma unroll
    for (int hf = 0; hf < 2; hf++) {
      float O[2][4];
#pragma unroll
      for (int mt = 0; mt < 2; mt++) {
        O[mt][0] = O[mt][1] = O[mt][2] = O[mt][3] = 0.f;
        mma16816(O[mt], vt[hf][4 * u + 2 * mt], vt[hf][4 * u + 2 * mt + 1], vt[hf + 1][4 * u + 2 * mt], vt[hf + 1][4 * u + 2 * mt + 1], pb[u][2 * hf], pb[u][2 * hf + 1]);
      }
      const uint32_t o0 = pack_bf16(O[0][0], O[0][1]), o1 = pack_bf16(O[0][2], O[0][3]), o2 = pack_bf16(O[1][0], O[1][1]), o3 = pack_bf16(O[1][2], O[1][3]);
      if (hf == 0) stmatrix_x4_trans<OFF_STG>(oa ^ (u * 64), o0, o1, o2, o3); else stmatrix_x4_trans<OFF_STG + 1024>(oa ^ (u * 64), o0, o1, o2, o3);
    }
  mbar_arrive_if<BAR(B_HEMPTY)>(cs.sb, has_halo && threadIdx.x == 128);
}

constexpr float SCALE_LOG2 = 0.08838834764831845f * 1.4426950408889634f;
#define SUM_LO 8.673617379884035e-19f
#define SUM_HI 1152921504606846976.f
template <int J0> __device__ __forceinline__ void causal_mask(float (&S)[64], int r) {
#pragma unroll
  for (int j = 0; j < 8; j++) {
    if (8 * j > r) S[4 * (J0 + j) + 0] = -INFINITY;
    if (8 * j + 1 > r) S[4 * (J0 + j) + 1] = -INFINITY;
    if (8 * j - 8 > r) S[4 * (J0 + j) + 2] = -INFINITY;
    if (8 * j - 7 > r) S[4 * (J0 + j) + 3] = -INFINITY;
  }
}
__device__ __forceinline__ float v_ex2(float x) { float y; asm volatile("ex2.approx.ftz.f32 %0, %1;" : "=f"(y) : "f"(x)); return y; }
__device__ __forceinline__ float v_add(float a, float b) { float y; asm volatile("add.f32 %0, %1, %2;" : "=f"(y) : "f"(a), "f"(b)); return y; }
__device__ __forceinline__ float v_mul(float a, float b) { float y; asm volatile("mul.f32 %0, %1, %2;" : "=f"(y) : "f"(a), "f"(b)); return y; }
template <int MJ> __device__ __forceinline__ float exp_el(float x, int j, int e, int r) {
  float p = v_ex2(x);
  if (j >= MJ) asm volatile("{\n.reg .pred q;\nsetp.lt.s32 q, %1, %2;\n@q mov.b32 %0, 0f00000000;\n}\n" : "+f"(p) : "r"(r), "r"(8 * (j - MJ) + (e & 1) - 4 * (e & 2)));
  return p;
}
template <int J0, int J1, int MJ = 16> __device__ __forceinline__ void exp_inplace(float (&S)[64], float& l0, float& l1, int r = 0) {
#pragma unroll
  for (int j = J0; j < J1; j++) {
#pragma unroll
    for (int e = 0; e < 4; e++) S[4 * j + e] = exp_el<MJ>(S[4 * j + e], j, e, r);
    l0 = v_add(l0, S[4 * j + 0]); l1 = v_add(l1, S[4 * j + 2]); l0 = v_add(l0, S[4 * j + 1]); l1 = v_add(l1, S[4 * j + 3]);
  }
}
template <int JS, int MJ, bool OUT>
__device__ __forceinline__ void exp_pack(float (&S)[64], uint32_t (&P)[32], float& l0, float& l1, int r, const float (&O)[64], float a0, float a1, uint32_t (&pk)[32]) {
#pragma unroll
  for (int j = JS; j < 16; j++) {
    const float p0 = exp_el<MJ>(S[4 * j + 0], j, 0, r), p1 = exp_el<MJ>(S[4 * j + 1], j, 1, r), p2 = exp_el<MJ>(S[4 * j + 2], j, 2, r), p3 = exp_el<MJ>(S[4 * j + 3], j, 3, r);
#pragma unroll
    for (int k = (j - JS) * JS / (16 - JS); k < (j + 1 - JS) * JS / (16 - JS); k++) { P[2 * k] = v_pack(S[4 * k + 0], S[4 * k + 1]); P[2 * k + 1] = v_pack(S[4 * k + 2], S[4 * k + 3]); }
    if (OUT) {
#pragma unroll
      for (int k = (j - JS) * 16 / (16 - JS); k < (j + 1 - JS) * 16 / (16 - JS); k++) {
        pk[2 * k] = v_pack(v_mul(O[4 * k + 0], a0), v_mul(O[4 * k + 1], a0)); pk[2 * k + 1] = v_pack(v_mul(O[4 * k + 2], a1), v_mul(O[4 * k + 3], a1));
      }
    }
    l0 = v_add(l0, p0); l1 = v_add(l1, p2); l0 = v_add(l0, p1); l1 = v_add(l1, p3);
    P[2 * j] = v_pack(p0, p1); P[2 * j + 1] = v_pack(p2, p3);
  }
}
__device__ __forceinline__ void pin_after(float a, float b) {
  asm volatile("{\n.reg .pred p;\nsetp.eq.u32 p, %0, 0xffffffff;\n@p st.shared.b32 [%1], %1;\n}\n" ::"r"(__float_as_uint(a)), "r"(__float_as_uint(b)) : "memory");
}
template <bool HALF, int SITE> __device__ __forceinline__ void issue_qk(float (&S)[64], uint32_t qlo, uint32_t klo) {
  uint32_t q, k;
  asm volatile("add.u32 %0, %2, %4;\nadd.u32 %1, %3, %4;" : "=r"(q), "=r"(k) : "r"(qlo), "r"(klo), "n"(SITE << 16));
  const uint64_t qd = desc(q), kd = desc(k);
  wg_fence();
  if (HALF) wg_qk64_init<0, 0>(S, qd, kd); else wg_qk_init<0, 0>(S, qd, kd);
#define QK(o) if (HALF) wg_qk64_acc<o, o>(S, qd, kd); else wg_qk_acc<o, o>(S, qd, kd)
  QK(2); QK(4); QK(6); QK(1024); QK(1026); QK(1028); QK(1030);
#undef QK
  wg_commit();
}
template <int NK, int ACC, int SITE> __device__ __forceinline__ void issue_pv(float (&O)[64], const uint32_t (&P)[32], uint32_t vlo) {
  constexpr int Z = 128 * SITE;
  uint32_t v;
  asm volatile("add.u32 %0, %1, %2;" : "=r"(v) : "r"(vlo), "n"(Z));
  const uint64_t vd = desc(v);
  wg_fence();
  if (ACC) wg_pv_acc<-Z>(O, &P[0], vd); else wg_pv_init<-Z>(O, &P[0], vd);
  wg_pv_acc<128 - Z>(O, &P[4], vd); wg_pv_acc<256 - Z>(O, &P[8], vd); wg_pv_acc<384 - Z>(O, &P[12], vd);
  if (NK == 8) { wg_pv_acc<512 - Z>(O, &P[16], vd); wg_pv_acc<640 - Z>(O, &P[20], vd); wg_pv_acc<768 - Z>(O, &P[24], vd); wg_pv_acc<896 - Z>(O, &P[28], vd); }
  wg_commit();
}
__device__ __forceinline__ uint32_t row_norm(float l0, float l1, float& a0, float& a1) {
  const float q0 = quad_sum(l0), q1 = quad_sum(l1);
  a0 = rcp(q0); a1 = rcp(q1);
  return __reduce_or_sync(0xffffffffu, (q0 >= SUM_LO && q0 <= SUM_HI && q1 >= SUM_LO && q1 <= SUM_HI) ? 0u : 1u);
}
__device__ __forceinline__ void slow_item(float (&O)[64], float& a0, float& a1, int head, int tile, uint32_t qbase, int w) {
  const int lane = threadIdx.x & 31, g = lane >> 2, t = lane & 3;
  const int rw = w * 64 + (int)__reduce_or_sync(0xffffffffu, (threadIdx.x >> 1) & 48);
  const int row0 = tile * 128 + rw;
  const uint32_t qa_ = qbase + (rw + g) * 128 + ((t ^ g) << 4);
  const __nv_bfloat16* kp = g_kv + ((size_t)head * SEQ + g) * 256 + 8 * t;
  const __nv_bfloat16* vp = g_kv + ((size_t)head * SEQ + 2 * t) * 256 + 128 + g;
  float m0 = -INFINITY, m1 = -INFINITY, l0 = 0.f, l1 = 0.f;
#pragma unroll
  for (int i = 0; i < 64; i++) O[i] = 0.f;
#pragma unroll 1
  for (int key0 = 0; key0 < row0 + 16; key0 += 16) {
    float c[2][4] = {{0.f, 0.f, 0.f, 0.f}, {0.f, 0.f, 0.f, 0.f}};
#pragma unroll 1
    for (int cc = 0; cc < 4; cc++) {
      uint32_t qa[4], qb[4];
      const uint32_t a = (qa_ ^ ((cc & 1) * 64)) + (cc >> 1) * 16384;
      lds128<0>(qa, a); lds128<1024>(qb, a);
#pragma unroll
      for (int n = 0; n < 2; n++) {
        const uint4 kf = ldg128(kp + (size_t)(key0 + 8 * n) * 256 + cc * 32);
        mma16816(c[n], qa[0], qb[0], qa[1], qb[1], kf.x, kf.y);
        mma16816(c[n], qa[2], qb[2], qa[3], qb[3], kf.z, kf.w);
      }
    }
#pragma unroll
    for (int n = 0; n < 2; n++)
#pragma unroll
      for (int e = 0; e < 4; e++)
        if (key0 + 8 * n + 2 * t + (e & 1) > row0 + g + (e >> 1) * 8) c[n][e] = -INFINITY;
    float x0 = fmaxf(fmaxf(c[0][0], c[0][1]), fmaxf(c[1][0], c[1][1])), x1 = fmaxf(fmaxf(c[0][2], c[0][3]), fmaxf(c[1][2], c[1][3]));
    x0 = fmaxf(x0, __shfl_xor_sync(0xffffffffu, x0, 1)); x1 = fmaxf(x1, __shfl_xor_sync(0xffffffffu, x1, 1));
    x0 = fmaxf(x0, __shfl_xor_sync(0xffffffffu, x0, 2)); x1 = fmaxf(x1, __shfl_xor_sync(0xffffffffu, x1, 2));
    const float n0 = fmaxf(m0, x0), n1 = fmaxf(m1, x1);
    const float r0 = ex2(m0 - n0), r1 = ex2(m1 - n1);
    m0 = n0; m1 = n1;
#pragma unroll
    for (int n = 0; n < 2; n++) { c[n][0] = ex2(c[n][0] - n0); c[n][1] = ex2(c[n][1] - n0); c[n][2] = ex2(c[n][2] - n1); c[n][3] = ex2(c[n][3] - n1); }
    l0 = l0 * r0 + ((c[0][0] + c[0][1]) + (c[1][0] + c[1][1]));
    l1 = l1 * r1 + ((c[0][2] + c[0][3]) + (c[1][2] + c[1][3]));
    const uint32_t p0 = pack_bf16(c[0][0], c[0][1]), p1 = pack_bf16(c[0][2], c[0][3]), p2 = pack_bf16(c[1][0], c[1][1]), p3 = pack_bf16(c[1][2], c[1][3]);
#pragma unroll
    for (int j = 0; j < 16; j++) {
      const __nv_bfloat16* v = vp + (size_t)key0 * 256 + j * 8;
      const uint32_t b0 = ldg16(v) | (ldg16(v + 256) << 16), b1 = ldg16(v + 8 * 256) | (ldg16(v + 9 * 256) << 16);
      float o[4] = {O[4 * j] * r0, O[4 * j + 1] * r0, O[4 * j + 2] * r1, O[4 * j + 3] * r1};
      mma16816(o, p0, p1, p2, p3, b0, b1);
      O[4 * j] = o[0]; O[4 * j + 1] = o[1]; O[4 * j + 2] = o[2]; O[4 * j + 3] = o[3];
    }
  }
  a0 = rcp(quad_sum(l0)); a1 = rcp(quad_sum(l1));
}
__device__ __forceinline__ void att_output(const float (&O)[64], float a0, float a1, uint32_t (&pk)[32]) {
#pragma unroll
  for (int k = 0; k < 16; k++) { pk[2 * k] = v_pack(v_mul(O[4 * k + 0], a0), v_mul(O[4 * k + 1], a0)); pk[2 * k + 1] = v_pack(v_mul(O[4 * k + 2], a1), v_mul(O[4 * k + 3], a1)); }
}
template <int J1> __device__ __forceinline__ void exp_stage(float (&S)[64], float& l0, float& l1, const uint32_t (&P)[32], int w, const Cons& cs, uint32_t on) {
  const uint32_t lane = threadIdx.x & 31, wq = (threadIdx.x >> 5) & 3;
  const uint32_t a = cs.sb + w * 16384 + (wq * 16 + (lane & 15)) * 128 + (((lane >> 4) ^ (lane & 7)) << 4);
#define ES(c) \
  exp_inplace<c * J1 / 8, (c + 1) * J1 / 8>(S, l0, l1); \
  stmatrix_x4_after<OFF_STG + (c >> 2) * 8192>(a ^ ((c & 3) * 32), P[4 * c + 0], P[4 * c + 1], P[4 * c + 2], P[4 * c + 3], (c & 1) ? l1 : l0, on)
  ES(0); ES(1); ES(2); ES(3); ES(4); ES(5); ES(6); ES(7);
#undef ES
}
struct Att { uint32_t qd, kd, vd, c8, cb, xc, xp, pub; };
__device__ __forceinline__ void att_advance(Att& t) {
  constexpr uint32_t SLOT = 32768 >> 4;
  t.kd ^= SLOT; t.vd ^= SLOT; t.c8 ^= 8; t.cb ^= 8;
  const uint32_t x = t.xc; t.xc = t.xp ^ 1; t.xp = x;
}
__device__ __forceinline__ void head_sums(float& l0, float& l1, float& a0, float& a1, uint32_t& unsafe, const Cons& cs) {
  unsafe = row_norm(l0, l1, a0, a1);
  mbar_arrive_if<BAR(B_QEMPTY)>(cs.sb, (threadIdx.x & 31) == 0 && !unsafe);
  l0 = l1 = 0.f;
}
template <bool SECOND>
__device__ __forceinline__ uint32_t diag_full(float (&S)[64], float (&O)[64], uint32_t (&P)[32], uint32_t (&pk)[32], float& l0, float& l1, float& a0, float& a1, uint32_t& unsafe, Att& t, int r, Cons& cs) {
  constexpr int JD = SECOND ? JDIAG2 : JDIAG, w = 1;
  bar_sync(2, 256);
  issue_qk<false, 2 + SECOND>(S, t.qd, t.kd);
  if (!SECOND && t.pub) { stage_publish(w, cs); t.pub = 0; }
  mbar_wait<BAR(B_FULL + 2)>(t.cb ^ 8, t.xp);
  issue_pv<8, 1, 4 + SECOND>(O, P, t.vd);
  bar_arrive(1, 256);
  att_advance(t);
  wg_wait<1>();
  fence_regs(S);
  mbar_arrive_cl<BAR(B_EMPTY)>(cs.rel, t.c8 ^ 8);
  if (SECOND) head_sums(l0, l1, a0, a1, unsafe, cs);
  exp_inplace<0, JD, 8>(S, l0, l1, r);
  pin_after(l0, l1);
  wg_wait<0>();
  fence_regs(O);
  fence_regs(P);
  mbar_arrive_cl<BAR(B_EMPTY + 2)>(cs.rel, t.c8);
  uint32_t ready = mbar_test<BAR(B_FULL)>(t.cb, t.xc);
  if (!SECOND) ready &= mbar_test<BAR(B_QFULL)>(cs.sb, cs.fpar & 1);
  exp_pack<JD, 8, SECOND>(S, P, l0, l1, r, O, a0, a1, pk);
  return __reduce_or_sync(0xffffffffu, ready ^ 1);
}
__device__ __forceinline__ void diag_half(bool second, float (&S)[64], float (&O)[64], uint32_t (&P)[32], float& l0, float& l1, float& a0, float& a1, uint32_t& unsafe, Att& t, int r, Cons& cs) {
  constexpr int w = 0;
  bar_sync(1, 256);
  issue_qk<true, 4>(S, t.qd, t.kd);
  mbar_wait<BAR(B_FULL + 2)>(t.cb ^ 8, t.xp);
  if (second) issue_pv<4, 1, 1>(O, P, t.vd); else issue_pv<8, 1, 3>(O, P, t.vd);
  bar_arrive(2, 256);
  if (t.pub) { stage_publish(w, cs); t.pub = 0; }
  att_advance(t);
  if (second) head_sums(l0, l1, a0, a1, unsafe, cs);
  wg_wait<1>();
  fence_regs<0, 32>(S);
  mbar_arrive_cl<BAR(B_EMPTY)>(cs.rel, t.c8 ^ 8);
  exp_inplace<0, 8, 0>(S, l0, l1, r);
  pin_after(l0, l1);
  wg_wait<0>();
  fence_regs(O);
  fence_regs(P);
  mbar_arrive_cl<BAR(B_EMPTY + 2)>(cs.rel, t.c8);
#pragma unroll
  for (int k = 0; k < 8; k++) { P[2 * k] = v_pack(S[4 * k + 0], S[4 * k + 1]); P[2 * k + 1] = v_pack(S[4 * k + 2], S[4 * k + 3]); }
}
__device__ __forceinline__ void attention(uint32_t code, uint32_t rank, int idx, int w, Cons& cs, uint32_t (&P)[32], uint32_t (&pk)[32]) {
  const int lane = threadIdx.x & 31, wq = (threadIdx.x >> 5) & 3;
  constexpr int JS = JSPLIT, JE = JEDGE;
  const uint32_t sb = cs.sb;
  const int y = (code & 15) * 2 + rank;
  const int r = wq * 16 + (lane >> 2) - 2 * (lane & 3);
  float O[64], S[64];
  float l0 = 0.f, l1 = 0.f;
  Att t = {cs.da + dlo(OFF_A, 16), cs.d0 + dlo(OFF_B, 16), cs.d0 + dlo(OFF_B + 98304, 16384), 0, sb, cs.p0, cs.p1, 0};
  uint32_t unsafe = 0, late;
  int ns;
  auto stage_step = [&](uint32_t on) {
    att_advance(t);
    t.pub = 1;
    wg_wait<1>();
    fence_regs(S);
    mbar_arrive_cl<BAR(B_EMPTY)>(cs.rel, t.c8 ^ 8);
    exp_stage<JE>(S, l0, l1, pk, w, cs, on);
    pin_after(l0, l1);
    wg_wait<0>();
    fence_regs(O);
    fence_regs(P);
    mbar_arrive_cl<BAR(B_EMPTY + 2)>(cs.rel, t.c8);
    const uint32_t ready = mbar_test<BAR(B_FULL)>(t.cb, t.xc);
    exp_pack<JE, 16, false>(S, P, l0, l1, r, O, 0.f, 0.f, pk);
    late = __reduce_or_sync(0xffffffffu, ready ^ 1);
  };
  bar_sync(3 - w, 128 + 128 * w);
  if (y >= 2) {
    issue_qk<false, 6>(O, t.qd, cs.d0 + dlo(OFF_B + 32768, 16));
    mbar_wait<BAR(B_FULL)>(sb, t.xc);
    issue_qk<false, 7>(S, t.qd, t.kd);
    bar_arrive(1 + (w ^ 1), 256);
    wg_wait<1>();
    fence_regs(O);
    mbar_arrive_cl<BAR(B_EMPTY + 1)>(cs.rel);
    exp_stage<JP>(O, l0, l1, pk, w, cs, w ^ 1);
    pin_after(l0, l1);
    const uint32_t rd = mbar_test<BAR(B_FULL + 3)>(sb, t.xp);
    exp_pack<JP, 16, false>(O, P, l0, l1, r, O, 0.f, 0.f, pk);
    if (UNLIKELY(__reduce_or_sync(0xffffffffu, rd ^ 1))) mbar_wait<BAR(B_FULL + 3)>(sb, t.xp);
    bar_sync(1 + w, 256);
    issue_pv<8, 0, 6>(O, P, t.vd);
    bar_arrive(1 + (w ^ 1), 256);
    stage_step(w);
    ns = y - 2;
  } else {
    issue_qk<false, 8>(S, t.qd, cs.d0 + dlo(OFF_B + 32768, 16));
    bar_arrive(1 + (w ^ 1), 256);
    wg_wait<0>();
    fence_regs(S);
    mbar_arrive_cl<BAR(B_EMPTY + 1)>(cs.rel);
    causal_mask<0>(S, r + 64 * w + 128 * y);
    causal_mask<8>(S, r + 64 * w + 128 * y - 64);
    exp_pack<0, 16, false>(S, P, l0, l1, r, S, 0.f, 0.f, pk);
#pragma unroll
    for (int i = 0; i < 64; i++) O[i] = 0.f;
    late = 1;
    ns = 0;
  }
#pragma unroll 1
  for (uint32_t head = 0;; head++) {
    while (ns > 0) {
      if (UNLIKELY(late)) mbar_wait<BAR(B_FULL)>(t.cb, t.xc);
      bar_sync(1 + w, 256);
      issue_qk<false, 9>(S, t.qd, t.kd);
      if (t.pub) { stage_publish(w, cs); t.pub = 0; }
      mbar_wait<BAR(B_FULL + 2)>(t.cb ^ 8, t.xp);
      issue_pv<8, 1, 0>(O, P, t.vd);
      bar_arrive(1 + (w ^ 1), 256);
      ns--;
      att_advance(t);
      wg_wait<1>();
      fence_regs(S);
      mbar_arrive_cl<BAR(B_EMPTY)>(cs.rel, t.c8 ^ 8);
      exp_inplace<0, JS>(S, l0, l1);
      pin_after(l0, l1);
      wg_wait<0>();
      fence_regs(O);
      fence_regs(P);
      mbar_arrive_cl<BAR(B_EMPTY + 2)>(cs.rel, t.c8);
      const uint32_t rd = mbar_test<BAR(B_FULL)>(t.cb, t.xc);
      exp_pack<JS, 16, false>(S, P, l0, l1, 0, O, 0.f, 0.f, pk);
      late = __reduce_or_sync(0xffffffffu, rd ^ 1);
    }
    float a0 = 0.f, a1 = 0.f;
    if (head == 0) {
      if (w == 1) {
        if (y != 0) {
          if (UNLIKELY(late)) mbar_wait<BAR(B_FULL)>(t.cb, t.xc);
          late = diag_full<false>(S, O, P, pk, l0, l1, a0, a1, unsafe, t, r, cs);
        }
        t.qd += 32768 >> 4;
        if (UNLIKELY(late)) { mbar_wait<BAR(B_QFULL)>(sb, cs.fpar & 1); mbar_wait<BAR(B_FULL)>(t.cb, t.xc); }
        late = diag_full<true>(S, O, P, pk, l0, l1, a0, a1, unsafe, t, r, cs);
      } else {
#pragma unroll 1
        for (int second = y == 0; second < 2; second++) {
          if (second) {
            t.qd += 32768 >> 4;
            mbar_wait<BAR(B_QFULL)>(sb, cs.fpar & 1);
          }
          if (late) mbar_wait<BAR(B_FULL)>(t.cb, t.xc);
          diag_half(second, S, O, P, l0, l1, a0, a1, unsafe, t, r, cs);
          late = 1;
        }
      }
    } else {
      bar_sync(1 + w, 256);
      mbar_wait<BAR(B_FULL + 2)>(t.cb ^ 8, t.xp);
      if (y != 1 || w) issue_pv<8, 1, 7>(O, P, t.vd); else issue_pv<4, 1, 2>(O, P, t.vd);
      if (w == 0) bar_arrive(2, 256);
      if (t.pub) stage_publish(w, cs);
      unsafe = row_norm(l0, l1, a0, a1);
      mbar_arrive_if<BAR(B_QEMPTY + 1)>(sb, lane == 0 && !unsafe);
      wg_wait<0>();
      fence_regs(O);
      fence_regs(P);
      mbar_arrive_cl<BAR(B_EMPTY + 2)>(cs.rel, t.c8 ^ 8);
    }
    if (head >= w) att_output(O, a0, a1, pk);
    if (UNLIKELY(unsafe)) {
      slow_item(S, a0, a1, ((code >> 4) & 31) * 2 + head, y ^ head, sb + OFF_A + head * 32768, w);
      __syncwarp();
      mbar_arrive_if<BAR(B_QEMPTY)>(sb + head * 8, lane == 0);
      att_output(S, a0, a1, pk);
    }
    if (head) break;
    if (y != 1) {
      if (UNLIKELY(late)) mbar_wait<BAR(B_FULL)>(t.cb, t.xc);
      bar_sync(1 + w, 256);
      issue_qk<false, 10>(S, t.qd, t.kd);
      mbar_wait<BAR(B_STGE)>(sb + w * 8, (cs.round & 1) ^ 1);
      mbar_wait<BAR(B_FULL + 2)>(t.cb ^ 8, t.xp);
      if (w == 0) issue_pv<4, 0, 3>(O, P, t.vd); else issue_pv<8, 0, 6>(O, P, t.vd);
      bar_arrive(1 + (w ^ 1), 256);
      stage_step(1);
      ns = (y ^ 1) - 1;
    } else {
      stage_write(pk, w, cs);
      t.pub = 1;
#pragma unroll
      for (int i = 0; i < 64; i++) O[i] = 0.f;
    }
  }
  cs.p1 = t.xp ^ 1; cs.p0 = t.xc;
  cs.fpar ^= 1;
}

struct Src { const CUtensorMap *ma, *mb; int a0, a1, b0, b1, b2; uint32_t hb; };
__device__ __forceinline__ Src gemm_src(const Params& p, uint32_t code, uint32_t rank, uint32_t h) {
  const int kind = code >> 9, x = (code >> 4) & 31, m = code & 15;
  Src s;
  s.ma = &p.maps[M_AX + kind];
  s.mb = &p.maps[(kind == K_KV && h) ? M_WUV : M_WQKV + kind];
  if (kind == K_QL) { s.a0 = rank * 1024; s.a1 = m * 128; s.b0 = x * 64; s.b1 = h * 32; s.b2 = 0; s.hb = 12288; }
  else { s.a0 = 0; s.a1 = (2 * m + rank) * 128; s.b0 = 0; s.b1 = 0; s.b2 = kind == K_KV ? x * 2 : x * 4 + h * 2; s.hb = 16384; }
  return s;
}
__global__ void __cluster_dims__(2, 1, 1) __launch_bounds__(384, 1) mega_kernel(const __grid_constant__ Params p) {
  extern __shared__ __align__(1024) uint8_t smem_raw[];
  const uint32_t sb = smem_u32(smem_raw), sb0 = sb;
  const uint32_t bid = blockIdx.x, rank = bid & 1;
  const int warp = __shfl_sync(0xffffffffu, threadIdx.x >> 5, 0);
#define BI(b) mbar_init<BAR(b)>(sb, bar_count(b))
  static_assert(B_COUNT == 25, "barrier set-up");
  if (warp == 0) {
    const uint32_t c0 = p.sched[bid >> 1][threadIdx.x & 1];
    if (elect_one()) {
      BI(0); BI(1); BI(2); BI(3);
      asm volatile("fence.mbarrier_init.release.cluster;" ::: "memory");
    }
    __syncwarp();
    const uint32_t code0 = __shfl_sync(0xffffffffu, c0, 0) & 4095;
    const Src u = gemm_src(p, code0, rank, 0), v = gemm_src(p, code0, rank, 1);
#pragma unroll
    for (int s = 0; s < EARLYN; s++) {
      if (elect_one()) {
        const uint32_t bar = sb + BAR(B_FULL) + s * 8;
        mbar_expect_tx<0>(bar, 16384 + 2 * u.hb);
        tma_load_2d(sb + OFF_A + s * 16384, u.ma, u.a0 + s * 64, u.a1, bar);
        tma_load_3d(sb + OFF_B + s * 32768, u.mb, u.b0, u.b1 + s * 64, u.b2, bar);
        tma_load_3d(sb + OFF_B + s * 32768 + u.hb, v.mb, v.b0, v.b1 + s * 64, v.b2, bar);
      }
    }
  }
  if (threadIdx.x == 32 || threadIdx.x == 64 || threadIdx.x == 96) {
    if (threadIdx.x == 32) { BI(4); BI(5); BI(6); BI(7); BI(8); BI(9); BI(21); }
    else if (threadIdx.x == 64) { BI(10); BI(11); BI(12); BI(13); BI(14); BI(15); BI(22); }
    else {
      BI(16); BI(17); BI(18); BI(19); BI(20); BI(23); BI(24);
      asm volatile("st.shared.u32 [%0+%2], %1;\nst.shared.v4.u32 [%0+%3], {%1, %1, %1, %1};" ::"r"(sb), "r"(0), "n"(OFF_FILLS), "n"(OFF_FILLS + 16) : "memory");
      if ((sb & 0xffffffu) != SB) __trap();
    }
    asm volatile("fence.mbarrier_init.release.cluster;" ::: "memory");
  }
#undef BI
  if (warp == 4) {
    const int i = threadIdx.x - 128;
    if (i < MAX_ITEMS / 4) {
      const uint4 v = *reinterpret_cast<const uint4*>(&p.sched[bid >> 1][4 * i]);
      asm volatile("st.shared.v4.u32 [%0+%5], {%1, %2, %3, %4};" ::"r"(sb + i * 16), "r"(v.x), "r"(v.y), "r"(v.z), "r"(v.w), "n"(OFF_LIST) : "memory");
    }
    asm volatile("st.shared.v2.u32 [%0+%2], {%1, %1};" ::"r"(sb + i * 8), "r"(0), "n"(OFF_MASK) : "memory");
  }
  bar_sync(0, 384);
  cluster_arrive_relaxed();
  const int wg = warp >> 2;
  if (wg == 0) {
    reg_dealloc<REG_PROD>();
    cluster_wait();
    const int lane = threadIdx.x & 31;
    auto need = [&](uint32_t& have, int i, int b) {
      if (!((have >> b) & 1)) {
        uint32_t n = 0;
        while (have = __reduce_or_sync(0xffffffffu, lds_acquire<OFF_MASK>(sb + i * 4)), !((have >> b) & 1)) { __nanosleep(32); if (++n > (1u << 22)) __trap(); }
        fence_async_glob();
      }
    };
    if (warp == 0) {
      uint32_t e0 = 1, e1 = 1;
      uint32_t qe = 0, after_att = 0, fills = 0;
      const uint64_t pol_first = policy_evict_first(), pol_normal = POL_NORMAL;
      for (int idx = 0;; idx++) {
        const uint32_t full = item_full(sb, idx), code = full & 4095;
        const int kind = code >> 9, x = (code >> 4) & 31, m = code & 15, y = 2 * m + rank;
        if (kind == K_END) break;
        const uint32_t last = kind >= K_OA ? 0u : full;
        {
          const Src u = gemm_src(p, code, rank, rank);
          const uint64_t pa = (last & 0x1000) ? pol_first : pol_normal, pb = (last & 0x2000) ? pol_first : pol_normal;
          const int nk = kind == K_KV ? 8 : kind == K_OB ? 64 : 16;
          uint32_t have = kind >= K_OA ? 0u : 0xffffffffu;
#pragma unroll 1
          for (int k = idx == 0 ? EARLYN : 0; k < nk; k++) {
            const uint32_t s = k & 3;
            int kk = k;
            if (k >= 64 - 4 * HLATE) { const int j = (k >> 1) - (32 - 2 * HLATE); kk = (32 - 2 * HLATE + (j < HLATE ? 2 * j : 2 * (j - HLATE) + 1)) * 2 + (k & 1); }
            need(have, (kind == K_OA ? F_QL : F_CTX) + y, kind == K_OA ? k : kk >> 1);
            if (after_att && !(k & 1)) {
              mbar_wait_b<BAR(B_QEMPTY)>(sb + k * 4, qe);
              if (k == 2) { after_att = 0; qe ^= 1; }
            }
            fill_gemm(sb + s * 8, (s & 1) ? e1 : e0, 16384 + 2 * u.hb, sb + OFF_B + s * 32768 + rank * u.hb, u.mb, u.b0, u.b1 + kk * 64, u.b2, sb + OFF_A + s * 16384, u.ma, u.a0 + kk * 64, u.a1, pb, pa);
            asm volatile("st.volatile.shared.u32 [%0+%2], %1;" ::"r"(sb), "r"(++fills), "n"(OFF_FILLS) : "memory");
            if (s == 3) { e0 ^= 1; e1 ^= 1; }
          }
        }
        if (kind == K_QF) {
          uint32_t have = 0, xc = e1, xp = e0 ^ 1;
#pragma unroll 1
          for (int j = 0; j < 8 * m + 8; j++) {
            const int i = j >> 1, v = j & 1;
            if (v ? i == 0 : i == 4 * m + 3) continue;
            const int ib = i - v;
            if (i == 2 * m + 1 + rank && !v) have = 0;
            const int h = 2 * x + (ib >= 2 * m + 1 + (int)rank), blk = ib <= 2 * m + 1 ? ib : 4 * m + 2 - ib;
            const int row = h * SEQ + blk * 128;
            if (!v) need(have, F_KV + h, blk);
            const uint32_t b = 2 * v + ((ib + 1) & 1);
            const uint32_t dst = sb + OFF_B + b * 32768;
            const bool own = ib == 2 * m + 1;
            const uint64_t pol = ((last >> (16 + (h & 1) * 8 + (blk >> 1))) & 1) ? pol_first : pol_normal;
            fill_kv(sb + b * 8, v ? xp : xc, dst + rank * 16384, &p.maps[M_KV_LD], (2 * v + rank) * 64, row, own ? 1 + rank : 3, pol);
            if (own) tma_load_2d_h(dst + (rank ^ 1) * 16384, &p.maps[M_KV_LD], (2 * v + (rank ^ 1)) * 64, row, sb + BAR(B_FULL) + b * 8, pol);
            if (v || i == 0) { const uint32_t t = xc; xc = xp ^ 1; xp = t; }
          }
          e0 ^= 1;
          after_att = 1;
        }
      }
    } else if (warp == 2) {
      const uint32_t epoch = g_flags.epoch[bid];
      const uint64_t full = (lane >> 3) == 2 ? ~0ull : 0x0000ffff0000ffffull, flip = 0ull - (epoch & 1);
      uint64_t seen = 0;
      uint32_t tries = 0, hp = 1, hcode;
      int hidx = -1;
      auto next_halo = [&]() { do hcode = item(sb, ++hidx); while ((hcode >> 9) != K_END && ((hcode >> 9) != K_QL || (hcode & 15) == 0)); };
      next_halo();
      while (true) {
        const bool all = __all_sync(0xffffffffu, seen == full);
        if (all && (hcode >> 9) == K_END) break;
        if (!all) {
          uint64_t v;
          asm volatile("ld.acquire.gpu.global.u64 %0, [%1];" : "=l"(v) : "l"(&g_flags.m[2 * lane]) : "memory");
          v = (v ^ flip) & full;
          if (v != seen) { seen = v; asm volatile("st.release.cta.shared::cta.u64 [%0+%2], %1;" ::"r"(sb + lane * 8), "l"(v), "n"(OFF_MASK) : "memory"); }
        }
        if ((hcode >> 9) != K_END) {
          const int x = (hcode >> 4) & 31, m = hcode & 15;
          bool there = __any_sync(0xffffffffu, lane == F_QL / 2 + m - 1 && ((seen >> (32 * rank + x)) & 1));
          if (there && __all_sync(0xffffffffu, mbar_test<BAR(B_HEMPTY)>(sb, hp))) {
            __syncwarp();
            fence_async_glob();
            if (elect_one()) mbar_expect_tx<BAR(B_HFULL)>(sb, 2048);
            bulk_load(sb + OFF_HALO, g_halo + ((2 * m + rank - 2) * 16 + x) * 2048, 2048, sb + BAR(B_HFULL));
            hp ^= 1;
            next_halo();
          }
        }
        __nanosleep(WATCH_NS);
        if (++tries > (1u << 20)) __trap();
      }
      if (lane == 0) g_flags.epoch[bid] = epoch + 1;
    } else if (warp == 3) {
      uint32_t n = 0;
      for (int idx = 0;; idx++) {
        const uint32_t code = item(sb, idx);
        const int kind = code >> 9, x = (code >> 4) & 31, y = 2 * (code & 15) + rank;
        if (kind == K_END) break;
        if (kind > K_KV) continue;
#pragma unroll 1
        for (int r = 0; r <= (kind == K_QF); r++, n++) {
          mbar_wait_long<BAR(B_RELF)>(sb + (n & 1) * 8, (n >> 1) & 1);
          mbar_arrive_if<BAR(B_RELE)>(sb + (n & 1) * 8, lane == 0);
          flag_toggle(&g_flags.m[kind == K_QL ? F_QL + y : kind == K_KV ? F_KV + x : F_CTX + (y ^ r)], 1u << (kind == K_QL ? x : kind == K_KV ? y : 2 * x + r));
        }
      }
    } else {
      {
        uint32_t round = 0, fpar = 0, nrel = 0;
        const uint32_t rb = mapa(sb, rank ^ 1);
        const uint64_t pol_first = policy_evict_first(), pol_normal = POL_NORMAL;
        auto pace = [&]() {
          uint32_t c0, c, t0, t;
          asm volatile("ld.volatile.shared.u32 %0, [%1+%2];" : "=r"(c0) : "r"(sb), "n"(OFF_FILLS) : "memory");
          asm volatile("mov.u32 %0, %clock;" : "=r"(t0));
          do {
            asm volatile("ld.volatile.shared.u32 %0, [%1+%2];" : "=r"(c) : "r"(sb), "n"(OFF_FILLS) : "memory");
            asm volatile("mov.u32 %0, %clock;" : "=r"(t));
          } while (__all_sync(0xffffffffu, c == c0 && t - t0 < PACE_MAX));
        };
        for (int idx = 0;; idx++) {
          const uint32_t code = item(sb, idx);
          const int kind = code >> 9, x = (code >> 4) & 31, m = code & 15, y = 2 * m + rank;
          if (kind == K_END) break;
          const bool last = (item(sb, idx + 1) >> 9) == K_END;
          if (kind == K_QF) {
            if (elect_one()) mbar_expect_tx<BAR(B_QFULL)>(sb, 32768);
            mbar_wait_long<BAR(B_QX)>(sb, fpar);
#pragma unroll 1
            for (int v = 0; v < 2; v++) {
              mbar_wait_b<BAR(B_STGF)>(sb + v * 8, round & 1);
              bulk_send(rb + OFF_A + 32768 + v * 8192, sb + OFF_STG + v * 16384, 8192, rb + BAR(B_QFULL));
              bulk_send(rb + OFF_A + 49152 + v * 8192, sb + OFF_STG + v * 16384 + 8192, 8192, rb + BAR(B_QFULL));
            }
            mbar_wait_b<BAR(B_QFULL)>(sb, fpar);
            mbar_arrive_cl<BAR(B_STGE)>(lane < 2 ? rb : 0, lane * 8);
            round++; fpar ^= 1;
          }
          const CUtensorMap* mc = &p.maps[M_OA_ST + kind];
          const uint64_t pol = (kind >= K_OA || kind == K_QF) ? pol_first : pol_normal;
          int row = kind == K_KV ? x * SEQ + y * 128 : kind == K_OA ? m * 128 : y * 128;
          int cg = kind == K_QL ? x : kind == K_QF ? x * 4 : kind == K_KV ? 0 : kind == K_OA ? rank * 32 + x * 4 : 16 + x * 4;
          const int nr = kind == K_QL ? 1 : 2;
#pragma unroll 1
          for (int r = 0; r < nr; r++) {
            mbar_wait_long<BAR(B_STGF)>(sb, round & 1);
            if (last && kind >= K_KV) {
              tma_store_3d(mc, sb + OFF_STG, 0, row, cg, pol);
              mbar_wait_b<BAR(B_FIN)>(sb, 0);
              tma_store_3d(mc, sb + OFF_B, 0, row, cg + 2, pol);
              mbar_wait_b<BAR(B_STGF + 1)>(sb, round & 1);
              tma_store_3d(mc, sb + OFF_STG + 16384, 0, row + 64, cg, pol);
              mbar_wait_b<BAR(B_FIN + 1)>(sb, 0);
              tma_store_3d(mc, sb + OFF_B + 16384, 0, row + 64, cg + 2, pol);
              bulk_commit();
              r = 1;
            } else {
              const bool paced = !last && (kind >= K_KV || r == 1);
              if (paced) pace();
              tma_store_3d(mc, sb + OFF_STG, 0, row, cg, pol);
              bulk_commit();
              mbar_wait_b<BAR(B_STGF + 1)>(sb, round & 1);
              if (paced) pace();
              tma_store_3d(mc, sb + OFF_STG + 16384, 0, row + 64, cg, pol);
              if (kind == K_QL) bulk_store(g_halo + (y * 16 + x) * 2048, sb + OFF_STG + 16384 + 8192 + 3 * 2048, 2048);
              bulk_commit();
              bulk_wait_read<1>();
              mbar_arrive_if<BAR(B_STGE)>(sb, lane == 0);
              bulk_wait_read<0>();
              mbar_arrive_if<BAR(B_STGE + 1)>(sb, lane == 0);
              round++;
            }
            if (kind == K_QF || (kind <= K_KV && r == nr - 1)) {
              bulk_wait_all();
              mbar_wait_b<BAR(B_RELE)>(sb + (nrel & 1) * 8, ((nrel >> 1) & 1) ^ 1);
              __syncwarp();
              mbar_arrive_if<BAR(B_RELF)>(sb + (nrel & 1) * 8, lane == 0);
              nrel++;
            }
            cg += 2;
            if (kind == K_QF) row ^= 128;
          }
        }
        bulk_wait_all();
      }
      cluster_arrive_relaxed();
      cluster_wait();
    }
  } else {
    reg_alloc<REG_CONS>();
    cluster_wait();
    const int w = wg - 1;
    Cons cs;
    cs.sb = __reduce_or_sync(0xffffffffu, sb0);
    const uint32_t sb = cs.sb;
    cs.d0 = (sb & 0x3ffff) >> 4;
    cs.da = cs.d0 + w * 512;
    cs.rel = (threadIdx.x & 127) == 0 ? sb : (threadIdx.x & 127) == 1 ? mapa(sb, rank ^ 1) : 0;
    cs.p0 = cs.p1 = cs.lead = cs.round = cs.fpar = 0;
    uint32_t pkA[32], pkB[32], pend = 0;
#pragma unroll
    for (int i = 0; i < 32; i++) pkA[i] = pkB[i] = 0;
    uint32_t code = item(sb, 0);
    int idx = 0;
    do {
      const int kind = code >> 9;
      uint32_t ncode;
      if (kind == K_QL) {
        float acc[96];
        Loc l;
        ncode = gemm_tile(acc, 4, idx, w, cs, pend, pkA, pkB, [&] { l = local_prepare(code, w, cs); });
        local_epilogue(acc, code, w, cs, l);
        pend = 24;
        if (w == 1 && (ncode >> 9) != K_END) bar_arrive(5, 256);
        if ((ncode >> 9) >= K_OA) { stage_publish(w, cs); pend = 16; }
      } else {
        float acc[128];
        ncode = gemm_tile(acc, kind == K_KV ? 2 : kind == K_OB ? 16 : 4, idx, w, cs, pend, pkA, pkB, [] {});
        if (kind == K_QF) {
          mbar_arrive_cl<BAR(B_QX)>((threadIdx.x & 1) ? cs.rel : 0);
          tile_pack_write<OFF_A, 16384, 0>(acc, pkB, sb + w * 8192);
#pragma unroll
          for (int i = 0; i < 32; i++) pkA[i] = v_pack(acc[64 + 2 * i], acc[64 + 2 * i + 1]);
          mbar_wait<BAR(B_STGE)>(sb + w * 8, (cs.round & 1) ^ 1);
          if ((code & 15) == 0) { tile_write<OFF_STG, 8192>(pkA, sb + w * 16384); stage_publish(w, cs); }
          mbar_wait<BAR(B_FULL + 1)>(sb, cs.p1);
          fence_async_smem();
          attention(code, rank, idx, w, cs, pkB, pkA);
          pend = 1;
        } else {
          if (kind == K_KV) {
#pragma unroll
            for (int i = 0; i < 64; i++) acc[i] *= SCALE_LOG2;
          }
#pragma unroll
          for (int i = 0; i < 32; i++) pkA[i] = pack_bf16(acc[2 * i], acc[2 * i + 1]);
#pragma unroll
          for (int i = 0; i < 32; i++) pkB[i] = pack_bf16(acc[64 + 2 * i], acc[64 + 2 * i + 1]);
          pend = 3;
        }
      }
      code = ncode;
      idx++;
    } while ((code >> 9) != K_END);
    if (pend & 1) { stage_write(pkA, w, cs); stage_publish(w, cs); }
    if (pend & 2) {
      mbar_wait<BAR(B_EMPTY)>(sb, cs.p0 ^ 1);
      tile_write<OFF_B, 8192>(pkB, sb + w * 16384);
      fence_async_smem();
      __syncwarp();
      mbar_arrive_if<BAR(B_FIN)>(sb + w * 8, (threadIdx.x & 31) == 0);
    }
    cluster_arrive();
  }
}

typedef CUresult (*EncodeFn)(CUtensorMap*, CUtensorMapDataType, cuuint32_t, void*, const cuuint64_t*, const cuuint64_t*, const cuuint32_t*,
                             const cuuint32_t*, CUtensorMapInterleave, CUtensorMapSwizzle, CUtensorMapL2promotion, CUtensorMapFloatOOBfill);

void make_map_2d(EncodeFn enc, CUtensorMap* tm, const void* ptr, uint64_t cols, uint64_t rows) {
  cuuint64_t dims[2] = {cols, rows};
  cuuint64_t str[1] = {cols * 2};
  cuuint32_t box[2] = {64, 128};
  cuuint32_t es[2] = {1, 1};
  enc(tm, CU_TENSOR_MAP_DATA_TYPE_BFLOAT16, 2, const_cast<void*>(ptr), dims, str, box, es, CU_TENSOR_MAP_INTERLEAVE_NONE, CU_TENSOR_MAP_SWIZZLE_128B,
      CU_TENSOR_MAP_L2_PROMOTION_L2_256B, CU_TENSOR_MAP_FLOAT_OOB_FILL_NONE);
}
void make_map_3d(EncodeFn enc, CUtensorMap* tm, const void* ptr, uint64_t cols, uint64_t rows, uint64_t part, uint32_t br, uint32_t bg) {
  cuuint64_t dims[3] = {part, rows, cols / part};
  cuuint64_t str[2] = {cols * 2, part * 2};
  cuuint32_t box[3] = {64, br, bg};
  cuuint32_t es[3] = {1, 1, 1};
  enc(tm, CU_TENSOR_MAP_DATA_TYPE_BFLOAT16, 3, const_cast<void*>(ptr), dims, str, box, es, CU_TENSOR_MAP_INTERLEAVE_NONE, CU_TENSOR_MAP_SWIZZLE_128B,
      CU_TENSOR_MAP_L2_PROMOTION_L2_256B, CU_TENSOR_MAP_FLOAT_OOB_FILL_NONE);
}

static const uint32_t h_sched[NPAIR][MAX_ITEMS] = {
  {0x432,0x212,0x55,0x4c5,0x525,0x32251,0x5e4,0x2576,0x5f5,0x835,0xe00,0xe00,0xe00,0xe00,0xe00,0xe00,0xe00,0xe00,0xe00,0xe00},
  {0x402,0x242,0x45,0x505,0x4d4,0x20261,0x574,0x5c7,0x5f7,0x805,0xe00,0xe00,0xe00,0xe00,0xe00,0xe00,0xe00,0xe00,0xe00,0xe00},
  {0x452,0x222,0xd5,0x180264,0x593,0x5d7,0x825,0xe00,0xe00,0xe00,0xe00,0xe00,0xe00,0xe00,0xe00,0xe00,0xe00,0xe00,0xe00,0xe00},
  {0x412,0x232,0x65,0x4c7,0x4f4,0x544,0x32281,0x5e6,0x5b5,0x815,0xe00,0xe00,0xe00,0xe00,0xe00,0xe00,0xe00,0xe00,0xe00,0xe00},
  {0x427,0x241,0x74,0xff800277,0x817,0xe00,0xe00,0xe00,0xe00,0xe00,0xe00,0xe00,0xe00,0xe00,0xe00,0xe00,0xe00,0xe00,0xe00,0xe00},
  {0x60,0x236,0x40292,0x5b6,0x823,0xe00,0xe00,0xe00,0xe00,0xe00,0xe00,0xe00,0xe00,0xe00,0xe00,0xe00,0xe00,0xe00,0xe00,0xe00},
  {0x414,0x215,0x40262,0x2c3,0x132f0,0x613,0xe00,0xe00,0xe00,0xe00,0xe00,0xe00,0xe00,0xe00,0xe00,0xe00,0xe00,0xe00,0xe00,0xe00},
  {0xd0,0x51,0x43,0x4,0x46,0x503,0x4f6,0x581,0x290,0x592,0x5b4,0x816,0xe00,0xe00,0xe00,0xe00,0xe00,0xe00,0xe00,0xe00},
  {0x470,0x425,0x12,0x475,0x256,0x4002f6,0x607,0xe00,0xe00,0xe00,0xe00,0xe00,0xe00,0xe00,0xe00,0xe00,0xe00,0xe00,0xe00,0xe00},
  {0x403,0x224,0x521,0x541,0x560,0x554,0x585,0x2002c5,0x20a7,0x612,0xe00,0xe00,0xe00,0xe00,0xe00,0xe00,0xe00,0xe00,0xe00,0xe00},
  {0x411,0x233,0xe6,0x507,0x100294,0x814,0xe00,0xe00,0xe00,0xe00,0xe00,0xe00,0xe00,0xe00,0xe00,0xe00,0xe00,0xe00,0xe00,0xe00},
  {0x10,0x473,0x246,0x5c1,0x808002e7,0x605,0xe00,0xe00,0xe00,0xe00,0xe00,0xe00,0xe00,0xe00,0xe00,0xe00,0xe00,0xe00,0xe00,0xe00},
  {0x497,0x202,0x4e0,0x66,0x4f0,0x24f1,0x802a3,0x827,0xe00,0xe00,0xe00,0xe00,0xe00,0xe00,0xe00,0xe00,0xe00,0xe00,0xe00,0xe00},
  {0x407,0x204,0x10a6,0x40282,0x5e5,0x5d6,0x803,0xe00,0xe00,0xe00,0xe00,0xe00,0xe00,0xe00,0xe00,0xe00,0xe00,0xe00,0xe00,0xe00},
  {0x450,0x205,0x513,0x511,0x537,0x564,0x570,0x597,0x2d3,0x2087,0x603,0xe00,0xe00,0xe00,0xe00,0xe00,0xe00,0xe00,0xe00,0xe00},
  {0xa0,0xa1,0x83,0xf4,0x86,0x4d6,0x4f2,0x562,0x5e0,0x556,0x2b0,0x806,0xe00,0xe00,0xe00,0xe00,0xe00,0xe00,0xe00,0xe00},
  {0x495,0x31,0xff800247,0x2a0,0x15d3,0x802e3,0x627,0xe00,0xe00,0xe00,0xe00,0xe00,0xe00,0xe00,0xe00,0xe00,0xe00,0xe00,0xe00,0xe00},
  {0x453,0x214,0x502,0x250,0x5a1,0x2b2,0x402e2,0x622,0xe00,0xe00,0xe00,0xe00,0xe00,0xe00,0xe00,0xe00,0xe00,0xe00,0xe00,0xe00},
  {0x461,0x213,0x36,0x4d7,0x514,0x533,0x402a2,0x834,0xe00,0xe00,0xe00,0xe00,0xe00,0xe00,0xe00,0xe00,0xe00,0xe00,0xe00,0xe00},
  {0x0,0x235,0x546,0x531,0x5c2,0x573,0x5c4,0x2002f5,0x635,0xe00,0xe00,0xe00,0xe00,0xe00,0xe00,0xe00,0xe00,0xe00,0xe00,0xe00},
  {0x437,0x211,0x2496,0x75,0x286,0x837,0xe00,0xe00,0xe00,0xe00,0xe00,0xe00,0xe00,0xe00,0xe00,0xe00,0xe00,0xe00,0xe00,0xe00},
  {0x30,0xff800237,0x5a2,0x2b1,0x813,0xe00,0xe00,0xe00,0xe00,0xe00,0xe00,0xe00,0xe00,0xe00,0xe00,0xe00,0xe00,0xe00,0xe00,0xe00},
  {0x405,0xff800227,0x582,0x584,0x590,0x577,0x2d0,0x25d0,0x2027,0x2047,0x624,0xe00,0xe00,0xe00,0xe00,0xe00,0xe00,0xe00,0xe00,0xe00},
  {0x440,0x471,0xb2,0xc3,0x4c1,0xffc00267,0x826,0xe00,0xe00,0xe00,0xe00,0xe00,0xe00,0xe00,0xe00,0xe00,0xe00,0xe00,0xe00,0xe00},
  {0x400,0x21,0x493,0x4a0,0x2477,0x266,0x25a7,0x1002e4,0x617,0xe00,0xe00,0xe00,0xe00,0xe00,0xe00,0xe00,0xe00,0xe00,0xe00,0xe00},
  {0x413,0x426,0x464,0x3,0xe4,0xb6,0x4d3,0xffe00297,0x35f0,0x2017,0x20e7,0xe00,0xe00,0xe00,0xe00,0xe00,0xe00,0xe00,0xe00,0xe00},
  {0x491,0x223,0xd6,0x4e7,0x2a4,0x824,0xe00,0xe00,0xe00,0xe00,0xe00,0xe00,0xe00,0xe00,0xe00,0xe00,0xe00,0xe00,0xe00,0xe00},
  {0x50,0x243,0x4b1,0x504,0x545,0x530,0x551,0x591,0x5a4,0x2002e5,0x615,0xe00,0xe00,0xe00,0xe00,0xe00,0xe00,0xe00,0xe00,0xe00},
  {0x417,0x201,0x486,0xe5,0x100274,0x594,0x25e7,0x807,0xe00,0xe00,0xe00,0xe00,0xe00,0xe00,0xe00,0xe00,0xe00,0xe00,0xe00,0xe00},
  {0xf0,0x234,0x284,0x5f6,0x833,0xe00,0xe00,0xe00,0xe00,0xe00,0xe00,0xe00,0xe00,0xe00,0xe00,0xe00,0xe00,0xe00,0xe00,0xe00},
  {0x415,0x225,0x40272,0x2c2,0x322d1,0x614,0xe00,0xe00,0xe00,0xe00,0xe00,0xe00,0xe00,0xe00,0xe00,0xe00,0xe00,0xe00,0xe00,0xe00},
  {0x20,0xc1,0x23,0x54,0x16,0x526,0x512,0x517,0x5c0,0x566,0x5c3,0x5b0,0x5b1,0x836,0xe00,0xe00,0xe00,0xe00,0xe00,0xe00},
  {0x480,0x465,0x32,0x466,0x255,0x2557,0x4002e6,0x637,0xe00,0xe00,0xe00,0xe00,0xe00,0xe00,0xe00,0xe00,0xe00,0xe00,0xe00,0xe00},
  {0x463,0x444,0x12220,0x4c0,0x4a7,0x4b6,0x283,0x1f22c4,0x20c7,0x623,0xe00,0xe00,0xe00,0xe00,0xe00,0xe00,0xe00,0xe00,0xe00,0xe00},
  {0x421,0x203,0x76,0x4f7,0x293,0x5d5,0x804,0xe00,0xe00,0xe00,0xe00,0xe00,0xe00,0xe00,0xe00,0xe00,0xe00,0xe00,0xe00,0xe00},
  {0x40,0x483,0x245,0x534,0x550,0x808002f7,0x625,0xe00,0xe00,0xe00,0xe00,0xe00,0xe00,0xe00,0xe00,0xe00,0xe00,0xe00,0xe00,0xe00},
  {0x451,0x226,0x2a5,0x402f2,0x1610,0xe00,0xe00,0xe00,0xe00,0xe00,0xe00,0xe00,0xe00,0xe00,0xe00,0xe00,0xe00,0xe00,0xe00,0xe00},
  {0x494,0xb1,0xf2,0x485,0xfff00257,0x5d4,0x832,0xe00,0xe00,0xe00,0xe00,0xe00,0xe00,0xe00,0xe00,0xe00,0xe00,0xe00,0xe00,0xe00},
  {0x436,0x91,0xe2,0xb4,0x35,0x24b0,0x540,0x516,0x536,0x2b3,0x5d1,0x202f1,0x636,0xe00,0xe00,0xe00,0xe00,0xe00,0xe00,0xe00},
  {0x420,0x210,0xf3,0x15,0x4e3,0x4d2,0x543,0x12260,0x2587,0x596,0x5d2,0x800,0xe00,0xe00,0xe00,0xe00,0xe00,0xe00,0xe00,0xe00},
  {0x433,0xff800217,0x808002c7,0x20d7,0x631,0xe00,0xe00,0xe00,0xe00,0xe00,0xe00,0xe00,0xe00,0xe00,0xe00,0xe00,0xe00,0xe00,0xe00,0xe00},
  {0x90,0x492,0x244,0x32271,0x4002d6,0x600,0xe00,0xe00,0xe00,0xe00,0xe00,0xe00,0xe00,0xe00,0xe00,0xe00,0xe00,0xe00,0xe00,0xe00},
  {0x457,0x490,0x22,0x53,0x2487,0x4c4,0x501,0x522,0x24d0,0x561,0x2b5,0x122e0,0x626,0xe00,0xe00,0xe00,0xe00,0xe00,0xe00,0xe00},
  {0x435,0x230,0x2467,0x94,0x500,0x40252,0x2c1,0x831,0xe00,0xe00,0xe00,0xe00,0xe00,0xe00,0xe00,0xe00,0xe00,0xe00,0xe00,0xe00},
  {0x434,0x41,0x72,0x4a1,0x4a3,0x4b5,0x200275,0x5f4,0x822,0xe00,0xe00,0xe00,0xe00,0xe00,0xe00,0xe00,0xe00,0xe00,0xe00,0xe00},
  {0x476,0x11,0xc2,0x24,0xf5,0xc6,0x524,0x535,0x5a0,0x571,0x575,0x2002d5,0x606,0xe00,0xe00,0xe00,0xe00,0xe00,0xe00,0xe00},
  {0x460,0xf1,0x240,0x4b4,0x26,0x506,0x4f3,0x280,0x5e3,0x5c6,0x5b2,0x830,0xe00,0xe00,0xe00,0xe00,0xe00,0xe00,0xe00,0xe00},
  {0x406,0x216,0x510,0x552,0x4002c6,0x20b7,0x601,0xe00,0xe00,0xe00,0xe00,0xe00,0xe00,0xe00,0xe00,0xe00,0xe00,0xe00,0xe00,0xe00},
  {0xe0,0x71,0x13,0x34,0xa5,0x4d5,0x523,0xfff002a7,0x2037,0x30f7,0xe00,0xe00,0xe00,0xe00,0xe00,0xe00,0xe00,0xe00,0xe00,0xe00},
  {0x441,0x472,0x82,0x63,0x85,0x6,0x24e6,0x2a6,0x202e1,0x604,0xe00,0xe00,0xe00,0xe00,0xe00,0xe00,0xe00,0xe00,0xe00,0xe00},
  {0x455,0x221,0xc4,0x4e2,0x4c6,0x4d1,0x547,0x563,0x565,0x202a1,0x811,0xe00,0xe00,0xe00,0xe00,0xe00,0xe00,0xe00,0xe00,0xe00},
  {0x481,0x1,0xd2,0x4a2,0x4c2,0x265,0x5a5,0x5f3,0x802,0xe00,0xe00,0xe00,0xe00,0xe00,0xe00,0xe00,0xe00,0xe00,0xe00,0xe00},
  {0xc0,0x474,0xa2,0x84,0x5,0x520,0x296,0x402d2,0x616,0xe00,0xe00,0xe00,0xe00,0xe00,0xe00,0xe00,0xe00,0xe00,0xe00,0xe00},
  {0x430,0x200,0x93,0x4a6,0x56,0x527,0x270,0x5e2,0x2567,0x5a6,0x5b7,0x820,0xe00,0xe00,0xe00,0xe00,0xe00,0xe00,0xe00,0xe00},
  {0x416,0xff800207,0x808002b7,0x2097,0x611,0xe00,0xe00,0xe00,0xe00,0xe00,0xe00,0xe00,0xe00,0xe00,0xe00,0xe00,0xe00,0xe00,0xe00,0xe00},
  {0x80,0xe1,0x33,0xa4,0x80253,0xc08002d7,0x632,0xe00,0xe00,0xe00,0xe00,0xe00,0xe00,0xe00,0xe00,0xe00,0xe00,0xe00,0xe00,0xe00},
  {0x424,0x423,0x42,0x73,0xb5,0x263,0x586,0x1f22b4,0x2067,0x634,0xe00,0xe00,0xe00,0xe00,0xe00,0xe00,0xe00,0xe00,0xe00,0xe00},
  {0x442,0x231,0x64,0x4c3,0x4e4,0x80273,0x5c5,0x5b3,0x801,0xe00,0xe00,0xe00,0xe00,0xe00,0xe00,0xe00,0xe00,0xe00,0xe00,0xe00},
  {0x431,0x81,0x446,0xe3,0x4a4,0x4b3,0x4b7,0x295,0x812,0xe00,0xe00,0xe00,0xe00,0xe00,0xe00,0xe00,0xe00,0xe00,0xe00,0xe00},
  {0x456,0x61,0x92,0x44,0xc5,0x96,0x4f5,0x583,0x553,0x5e1,0x2c0,0x821,0xe00,0xe00,0xe00,0xe00,0xe00,0xe00,0xe00,0xe00},
  {0x410,0x462,0x2,0x484,0x254,0x32291,0x5f2,0x810,0xe00,0xe00,0xe00,0xe00,0xe00,0xe00,0xe00,0xe00,0xe00,0xe00,0xe00,0xe00},
  {0x401,0x206,0x580,0x532,0x6002b6,0x2077,0x621,0xe00,0xe00,0xe00,0xe00,0xe00,0xe00,0xe00,0xe00,0xe00,0xe00,0xe00,0xe00,0xe00},
  {0x70,0xd1,0xb3,0xd4,0x95,0x4e5,0x542,0x515,0x555,0x5a3,0x572,0x595,0x1802d4,0x630,0xe00,0xe00,0xe00,0xe00,0xe00,0xe00},
  {0x454,0x482,0x62,0xa3,0x25,0xf6,0x380285,0x802f3,0x633,0xe00,0xe00,0xe00,0xe00,0xe00,0xe00,0xe00,0xe00,0xe00,0xe00,0xe00},
  {0xb0,0x443,0x52,0x14,0x4a5,0x4b2,0xffc00287,0x15f1,0x2007,0x2057,0x620,0xe00,0xe00,0xe00,0xe00,0xe00,0xe00,0xe00,0xe00,0xe00},
  {0x404,0x422,0x445,0x2447,0xd3,0x4e1,0x400276,0x1002f4,0x602,0xe00,0xe00,0xe00,0xe00,0xe00,0xe00,0xe00,0xe00,0xe00,0xe00,0xe00},
};

struct HostState { bool init; Params p; void* out; const void* in[9]; };
HostState g_hs;

void build_state(void* const* d_in, void* d_out) {
  void* fn = nullptr;
  cudaDriverEntryPointQueryResult qr;
  cudaGetDriverEntryPoint("cuTensorMapEncodeTiled", &fn, cudaEnableDefault, &qr);
  EncodeFn enc = (EncodeFn)fn;
  void *kv, *ctx, *oA;
  cudaGetSymbolAddress(&kv, g_kv);
  cudaGetSymbolAddress(&ctx, g_ctx);
  cudaGetSymbolAddress(&oA, g_oA);
  Params& p = g_hs.p;
  make_map_2d(enc, &p.maps[M_AX], d_in[0], 2048, SEQ / 2);
  make_map_2d(enc, &p.maps[M_BX], d_in[3], 1024, SEQ);
  make_map_2d(enc, &p.maps[M_CKV], d_in[4], 512, SEQ);
  make_map_2d(enc, &p.maps[M_OA], oA, 1024, SEQ);
  make_map_2d(enc, &p.maps[M_CTX], ctx, 4096, SEQ);
  make_map_3d(enc, &p.maps[M_WQKV], d_in[1], 3072, 1024, 1024, 32, 3);
  make_map_3d(enc, &p.maps[M_WQ], d_in[5], 4096, 1024, 64, 64, 2);
  make_map_3d(enc, &p.maps[M_WUK], d_in[6], 4096, 512, 64, 64, 2);
  make_map_3d(enc, &p.maps[M_WUV], d_in[7], 4096, 512, 64, 64, 2);
  make_map_3d(enc, &p.maps[M_WOA], d_in[2], 1024, 1024, 64, 64, 2);
  make_map_3d(enc, &p.maps[M_WOB], d_in[8], 1024, 4096, 64, 64, 2);
  make_map_2d(enc, &p.maps[M_KV_LD], kv, 256, 32 * SEQ);
  make_map_3d(enc, &p.maps[M_OA_ST], oA, 1024, SEQ, 64, 64, 1);
  make_map_3d(enc, &p.maps[M_CTX_ST], ctx, 4096, SEQ, 64, 64, 2);
  make_map_3d(enc, &p.maps[M_KV_ST], kv, 256, 32 * SEQ, 64, 64, 2);
  make_map_3d(enc, &p.maps[M_OUTA_ST], d_out, 4096, SEQ / 2, 64, 64, 2);
  make_map_3d(enc, &p.maps[M_OUTB_ST], d_out, 2048, SEQ, 64, 64, 2);
  for (int c = 0; c < NPAIR; c++)
    for (int i = 0; i < MAX_ITEMS; i++) p.sched[c][i] = h_sched[c][i];
  cudaFuncSetAttribute(mega_kernel, cudaFuncAttributeMaxDynamicSharedMemorySize, SMEM_BYTES);
}

}

extern "C" void kernel_launch(void* const* d_in, const int* in_sizes, int n_in, void* d_out, int out_size) {
  (void)in_sizes; (void)n_in; (void)out_size;
  bool same = g_hs.init && g_hs.out == d_out;
  for (int i = 0; i < 9 && same; i++) same = (g_hs.in[i] == d_in[i]);
  if (!same) {
    build_state(d_in, d_out);
    g_hs.init = true; g_hs.out = d_out;
    for (int i = 0; i < 9; i++) g_hs.in[i] = d_in[i];
  }
  mega_kernel<<<NCTA, 384, SMEM_BYTES, cudaStreamPerThread>>>(g_hs.p);
}
```
